```python
import torch

def _softmax(x, axis=-1):
    return torch.softmax(x, dim=axis)
def _gelu(x):
    return torch.nn.functional.gelu(x, approximate="tanh")
def _silu(x):
    return torch.nn.functional.silu(x)
def _sigmoid(x):
    return torch.sigmoid(x)
def _layernorm(x, axis=-1, eps=1e-5):
    m = x.mean(dim=axis, keepdim=True)
    v = x.var(dim=axis, keepdim=True, unbiased=False)
    return (x - m) / torch.sqrt(v + eps)
def _scatter_add(tgt, idx, src, axis=0):
    return tgt.clone().index_add_(axis, idx, src)
def _segment_sum(src, seg, n):
    out = torch.zeros((n,) + src.shape[1:], dtype=src.dtype)
    return out.index_add_(0, seg, src)
def _pad(x, pw):
    flat = tuple(v for pair in reversed(pw) for v in pair)
    return torch.nn.functional.pad(x, flat)

kernel_name = 'parallel_sum__sliding_block_cached__glu_gated_swiglu__decode'

def setup_inputs():

    _w = (lambda a: (lambda t: t.to(torch.bfloat16) if t.is_floating_point() else t)(torch.as_tensor(a)))
    def _A_setup():
        B, Sq, D = 4, 1, 640
        Hq, Hkv, Sk, Dh = 32, 32, 8192, 192
        assert Hq % Hkv == 0, (Hq, Hkv)
        return {
            "x": _w((lambda *s: torch.randn(*s, dtype=torch.bfloat16) * 0.05)(B, Sq, D)),
            "k_cache": _w((lambda *s: torch.randn(*s, dtype=torch.bfloat16) * 1.6)(B, Hkv, Sk, Dh)),
            "v_cache": _w((lambda *s: torch.randn(*s, dtype=torch.bfloat16) * 0.8)(B, Hkv, Sk, Dh)),
            "wq": _w((lambda *s: torch.randn(*s, dtype=torch.bfloat16) * 1.6)(D, Hq * Dh) * (D ** -0.5)),
            "wo": _w((lambda *s: torch.randn(*s, dtype=torch.bfloat16) * 0.8)(Hq * Dh, D) * ((Hq * Dh) ** -0.5)),
        }
    _A_in = _A_setup()

    def _B_setup():
        B, S, D, F = 4, 1, 640, 1536
        return {
            "x": _w((lambda *s: torch.randn(*s, dtype=torch.bfloat16) * 0.05)(B, S, D)),
            "w1": _w((lambda *s: torch.randn(*s, dtype=torch.bfloat16) * 0.4)(D, F) * (2.0 / D) ** 0.5),
            "w3": _w((lambda *s: torch.randn(*s, dtype=torch.bfloat16) * 0.4)(D, F) * (2.0 / D) ** 0.5),
            "w2": _w((lambda *s: torch.randn(*s, dtype=torch.bfloat16) * 0.4)(F, D) * (2.0 / F) ** 0.5),
        }
    _B_in = _B_setup()

    return {
        "A_x": _A_in["x"],
        "A_k_cache": _A_in["k_cache"],
        "A_v_cache": _A_in["v_cache"],
        "A_wq": _A_in["wq"],
        "A_wo": _A_in["wo"],
        "B_x": _B_in["x"],
        "B_w1": _B_in["w1"],
        "B_w3": _B_in["w3"],
        "B_w2": _B_in["w2"],
    }

def reference(A_x, A_k_cache, A_v_cache, A_wq, A_wo, B_x, B_w1, B_w3, B_w2):
    def _A_ref(x, k_cache, v_cache, wq, wo):
        B, Sq, D = x.shape
        Hq, Dh = 32, 192
        Hkv, Sk = k_cache.shape[1], k_cache.shape[2]
        W = min(4096, max(256, Sk // 4))
        rep = Hq // Hkv
        q = (lambda x, *d: x.permute(*d))((x @ wq).reshape(B, Sq, Hq, Dh), 0, 2, 1, 3)
        k = (lambda x, n, axis: torch.repeat_interleave(x, n, dim=axis))(k_cache[:, :, Sk - W:, :], rep, axis=1)
        v = (lambda x, n, axis: torch.repeat_interleave(x, n, dim=axis))(v_cache[:, :, Sk - W:, :], rep, axis=1)
        scores = torch.einsum("bhqd,bhkd->bhqk", q, k) * (Dh ** -0.5)
        p = _softmax(scores, axis=-1)
        o = torch.einsum("bhqk,bhkd->bhqd", p, v)
        return (lambda x, *d: x.permute(*d))(o, 0, 2, 1, 3).reshape(B, Sq, Hq * Dh) @ wo

    def _B_ref(x, w1, w3, w2):
        gate = torch.einsum("bsd,df->bsf", x, w1)
        up = torch.einsum("bsd,df->bsf", x, w3)
        h = _silu(gate) * up
        out = torch.einsum("bsf,fd->bsd", h, w2)
        return out

    x = A_x
    xn = _layernorm(x, axis=-1)
    return x + _A_ref(xn, A_k_cache, A_v_cache, A_wq, A_wo) + _B_ref(xn, B_w1, B_w3, B_w2)
```

```cpp
#include <cuda_runtime.h>
#include <cuda_bf16.h>
#include <stdint.h>

namespace {

typedef __nv_bfloat16 bf16;

constexpr int NB = 4, DM = 640, NH = 32, DH = 192, SK = 8192, WIN = 2048, FF = 1536;

#define P_G 8
#define P_DEPTH 4
#define P_NS 16
#define P_EF 1

constexpr int G = P_G;
constexpr int TK = 32;
constexpr int NT = WIN / TK / G;
constexpr int NK = NT * TK;
constexpr int NS = P_NS;
constexpr int SLOT = 12800;
constexpr int DEPTH = P_DEPTH;
constexpr int NATT = 128, NFFN = 4, NCTA = NATT + NFFN;
constexpr int NCW = 8;
constexpr int NTHR = (NCW + 1) * 32;
constexpr int NSRC = NH + NFFN;

constexpr int XS = 648;
constexpr int OS = 200;
constexpr int HS = 392;
constexpr int OPS = 200;

constexpr int SM_RING = 0;
constexpr int SM_XN = SM_RING + NS * SLOT;
constexpr int SM_QS = SM_XN + NB * XS * 2;
constexpr int SM_SC = SM_QS + G * DH * 2;
constexpr int SM_PW = SM_SC + NK * 16;
constexpr int SM_RED = SM_PW + NK * 4 + 16;
constexpr int SM_OS = SM_RED + 8 * DH * 4;
constexpr int SM_LS = SM_OS + NB * OS * 2;
constexpr int SM_BAR = SM_LS + 32;
constexpr int SM_TOTAL = SM_BAR + 2 * NS * 8;
static_assert(SM_TOTAL <= 232448, "smem");
static_assert(SM_SC % 16 == 0 && SM_PW % 16 == 0 && SM_RED % 16 == 0 && SM_BAR % 8 == 0, "align");

constexpr int ITEMS_ATT = 5 + 2 * NT * G + 6;
constexpr int ITEMS_FFN = 80 + 48;

__device__ unsigned g_epoch;
__device__ float g_qpart[NATT * NB * DH];
__device__ float g_opart[NATT * G * OPS];
__device__ float g_fin[NB * 80 * NSRC * 8];
#define TS(i)

constexpr unsigned SPIN_LIMIT = 1u << 24;

__device__ __forceinline__ void mbar_init(uint32_t bar, int cnt) {
    asm volatile("mbarrier.init.shared::cta.b64 [%0], %1;" ::"r"(bar), "r"(cnt) : "memory");
}
__device__ __forceinline__ void mbar_expect_tx(uint32_t bar, uint32_t bytes) {
    asm volatile("mbarrier.arrive.expect_tx.shared::cta.b64 _, [%0], %1;" ::"r"(bar), "r"(bytes) : "memory");
}
__device__ __forceinline__ void mbar_arrive(uint32_t bar) {
    asm volatile("mbarrier.arrive.shared::cta.b64 _, [%0];" ::"r"(bar) : "memory");
}
__device__ __forceinline__ void mbar_wait(uint32_t bar, uint32_t parity) {
    uint32_t ok;
    unsigned it = 0;
    do {
        asm volatile("{\n.reg .pred p;\nmbarrier.try_wait.parity.shared::cta.b64 p, [%1], %2;\nselp.u32 %0, 1, 0, p;\n}"
                     : "=r"(ok) : "r"(bar), "r"(parity) : "memory");
        if (++it > SPIN_LIMIT) __trap();
    } while (!ok);
}
__device__ __forceinline__ void bulk_load(uint32_t dst, const void* src, uint32_t bytes, uint32_t bar, uint64_t pol) {
    asm volatile("cp.async.bulk.shared::cluster.global.mbarrier::complete_tx::bytes.L2::cache_hint [%0], [%1], %2, [%3], %4;"
                 ::"r"(dst), "l"(src), "r"(bytes), "r"(bar), "l"(pol) : "memory");
}
__device__ __forceinline__ void cp16(uint32_t dst, const void* src, uint64_t pol) {
    asm volatile("cp.async.cg.shared.global.L2::cache_hint [%0], [%1], 16, %2;" ::"r"(dst), "l"(src), "l"(pol) : "memory");
}
template <int PITCH>
__device__ __forceinline__ void rows384(uint32_t dst, const char* src, int lane, uint64_t pol) {
    dst += (lane >> 3) * 400 + (lane & 7) * 16;
    src += (lane >> 3) * PITCH + (lane & 7) * 16;
#pragma unroll
    for (int rr = 0; rr < 8; rr++)
#pragma unroll
        for (int s = 0; s < 3; s++) cp16(dst + rr * 1600 + s * 128, src + rr * 4 * PITCH + s * 128, pol);
}
__device__ __forceinline__ void rows320(uint32_t dst, const char* src, int lane, uint64_t pol) {
    dst += (lane >> 2) * 336 + (lane & 3) * 16;
    src += (lane >> 2) * 1280 + (lane & 3) * 16;
#pragma unroll
    for (int rr = 0; rr < 4; rr++)
#pragma unroll
        for (int s = 0; s < 5; s++) cp16(dst + rr * 8 * 336 + s * 64, src + rr * 8 * 1280 + s * 64, pol);
}
__device__ __forceinline__ void ldsm_x4(uint32_t addr, uint32_t& r0, uint32_t& r1, uint32_t& r2, uint32_t& r3) {
    asm volatile("ldmatrix.sync.aligned.m8n8.x4.shared.b16 {%0,%1,%2,%3}, [%4];"
                 : "=r"(r0), "=r"(r1), "=r"(r2), "=r"(r3) : "r"(addr) : "memory");
}
__device__ __forceinline__ void ldsm_x4_t(uint32_t addr, uint32_t& r0, uint32_t& r1, uint32_t& r2, uint32_t& r3) {
    asm volatile("ldmatrix.sync.aligned.m8n8.x4.trans.shared.b16 {%0,%1,%2,%3}, [%4];"
                 : "=r"(r0), "=r"(r1), "=r"(r2), "=r"(r3) : "r"(addr) : "memory");
}
__device__ __forceinline__ void mma16816(float (&c)[4], uint32_t a0, uint32_t a1, uint32_t a2, uint32_t a3,
                                         uint32_t b0, uint32_t b1) {
    asm volatile("mma.sync.aligned.m16n8k16.row.col.f32.bf16.bf16.f32 {%0,%1,%2,%3}, {%4,%5,%6,%7}, {%8,%9}, {%0,%1,%2,%3};"
                 : "+f"(c[0]), "+f"(c[1]), "+f"(c[2]), "+f"(c[3])
                 : "r"(a0), "r"(a1), "r"(a2), "r"(a3), "r"(b0), "r"(b1));
}
__device__ __forceinline__ void cons_bar() { asm volatile("bar.sync 1, 256;" ::: "memory"); }

__device__ __forceinline__ float bf_round(float v) { return __bfloat162float(__float2bfloat16_rn(v)); }
__device__ __forceinline__ uint32_t pack_bf2(float lo, float hi) {
    __nv_bfloat162 t = __floats2bfloat162_rn(lo, hi);
    return *reinterpret_cast<uint32_t*>(&t);
}
__device__ __forceinline__ float bf_lo(uint32_t u) { return __uint_as_float(u << 16); }
__device__ __forceinline__ float bf_hi(uint32_t u) { return __uint_as_float(u & 0xffff0000u); }

__device__ __forceinline__ uint32_t tagw(float v, uint32_t tag) { return (__float_as_uint(v) & ~1u) | tag; }
__device__ __forceinline__ void st_tag1(float* p, float a, uint32_t tag) {
    asm volatile("st.relaxed.gpu.global.u32 [%0], %1;" ::"l"(p), "r"(tagw(a, tag)) : "memory");
}
__device__ __forceinline__ void st_tag2(float* p, float a, float b, uint32_t tag) {
    asm volatile("st.relaxed.gpu.global.v2.u32 [%0], {%1,%2};" ::"l"(p), "r"(tagw(a, tag)), "r"(tagw(b, tag)) : "memory");
}
__device__ __forceinline__ uint4 ld_rlx4(const float* p) {
    uint4 v;
    asm volatile("ld.relaxed.gpu.global.v4.u32 {%0,%1,%2,%3}, [%4];"
                 : "=r"(v.x), "=r"(v.y), "=r"(v.z), "=r"(v.w) : "l"(p) : "memory");
    return v;
}
__device__ __forceinline__ uint2 ld_rlx2(const float* p) {
    uint2 v;
    asm volatile("ld.relaxed.gpu.global.v2.u32 {%0,%1}, [%2];" : "=r"(v.x), "=r"(v.y) : "l"(p) : "memory");
    return v;
}
__device__ __forceinline__ uint32_t bad4(const uint4& v, uint32_t tag) {
    return ((v.x ^ tag) | (v.y ^ tag) | (v.z ^ tag) | (v.w ^ tag)) & 1u;
}

template <bool THIRD>
__device__ __forceinline__ void gemv_item(uint32_t addr, uint32_t a00, uint32_t a02, uint32_t a10, uint32_t a12,
                                          float (&acc)[3][4]) {
    uint32_t b[3][4];
    ldsm_x4_t(addr, b[0][0], b[0][1], b[0][2], b[0][3]);
    ldsm_x4_t(addr + 128, b[1][0], b[1][1], b[1][2], b[1][3]);
    if (THIRD) ldsm_x4_t(addr + 256, b[2][0], b[2][1], b[2][2], b[2][3]);
    mma16816(acc[0], a00, 0u, a02, 0u, b[0][0], b[0][1]);
    mma16816(acc[1], a00, 0u, a02, 0u, b[1][0], b[1][1]);
    if (THIRD) mma16816(acc[2], a00, 0u, a02, 0u, b[2][0], b[2][1]);
    mma16816(acc[0], a10, 0u, a12, 0u, b[0][2], b[0][3]);
    mma16816(acc[1], a10, 0u, a12, 0u, b[1][2], b[1][3]);
    if (THIRD) mma16816(acc[2], a10, 0u, a12, 0u, b[2][2], b[2][3]);
}

struct Cursor {
    uint32_t slot, phase;
    __device__ __forceinline__ void next() { if (++slot == NS) { slot = 0; phase ^= 1; } }
};

__global__ void __launch_bounds__(NTHR, 1)
fused_decode_kernel(const bf16* __restrict__ x, const bf16* __restrict__ kc, const bf16* __restrict__ vc,
                    const bf16* __restrict__ wq, const bf16* __restrict__ wo, const bf16* __restrict__ w1,
                    const bf16* __restrict__ w3, const bf16* __restrict__ w2, bf16* __restrict__ out) {
    extern __shared__ __align__(128) unsigned char smem[];
    const uint32_t sb = (uint32_t)__cvta_generic_to_shared(smem);
    const int tid = threadIdx.x, warp = tid >> 5, lane = tid & 31;
    const int cta = blockIdx.x;
    const bool is_att = cta < NATT;
    const int h = cta >> 2, qd = cta & 3;
    const uint32_t bar_full = sb + SM_BAR, bar_empty = bar_full + NS * 8;

    if (warp == NCW) {
        if (lane == 0) {
            TS(0);
#pragma unroll
            for (int s = 0; s < NS; s++) { mbar_init(bar_full + s * 8, 1); mbar_init(bar_empty + s * 8, NCW); }
            asm volatile("fence.mbarrier_init.release.cluster;" ::: "memory");
            asm volatile("fence.proxy.async.shared::cta;" ::: "memory");
        }
        __syncwarp();
        asm volatile("bar.arrive 2, %0;" ::"n"(NTHR) : "memory");
        uint64_t pol = 0;
        asm volatile("createpolicy.fractional.L2::evict_first.b64 %0, 1.0;" : "=l"(pol));
        const int n_items = is_att ? ITEMS_ATT : ITEMS_FFN;
        const int sg = cta / G, r = cta % G;
        uint32_t slot = 0, eph = 1;
        uint32_t lslot = 0, lph = 0;
        for (int i = 0; i < n_items; i++) {
            const char* src;
            int kind;
            if (is_att) {
                if (i < 5) {
                    src = (const char*)(wq + (size_t)(qd * 160 + i * 32) * (NH * DH) + h * DH);
                    kind = 1;
                } else if (i < 5 + 2 * NT * G) {
                    const int u = i - 5, j = u / (2 * NT), v = u % (2 * NT);
                    const int pair = sg * G + j, hb = (pair & 3) * NH + (pair >> 2);
                    const int tt = (v % NT) * G + r;
                    src = (const char*)((v >= NT ? vc : kc) + ((size_t)hb * SK + (SK - WIN) + tt * TK) * DH);
                    kind = 0;
                } else {
                    const int k = i - (5 + 2 * NT * G);
                    src = (const char*)(wo + (size_t)(h * DH + k * 32) * DM + qd * 160);
                    kind = 3;
                }
            } else {
                if (i < 80) {
                    src = (const char*)(((i & 2) ? w3 : w1) + (size_t)((i >> 2) * 32) * FF + qd * 384 + (i & 1) * 192);
                    kind = 2;
                } else {
                    const int k = i - 80;
                    src = (const char*)(w2 + (size_t)(qd * 384 + (k >> 2) * 32) * DM + (k & 3) * 160);
                    kind = 3;
                }
            }
            if (i >= DEPTH) {
                mbar_wait(bar_full + lslot * 8, lph);
                if (++lslot == NS) { lslot = 0; lph ^= 1; }
            }
            if (i >= NS) mbar_wait(bar_empty + slot * 8, eph);
            const uint32_t fb = bar_full + slot * 8, dst = sb + SM_RING + slot * SLOT;
            if (kind == 0) {
                if (lane == 0) { mbar_expect_tx(fb, TK * DH * 2); bulk_load(dst, src, TK * DH * 2, fb, pol); }
            } else {
                if (kind == 1) rows384<NH * DH * 2>(dst, src, lane, pol);
                else if (kind == 2) rows384<FF * 2>(dst, src, lane, pol);
                else rows320(dst, src, lane, pol);
                asm volatile("cp.async.mbarrier.arrive.shared::cta.b64 [%0];" ::"r"(fb) : "memory");
                __syncwarp();
                if (lane == 0) mbar_arrive(fb);
            }
            if (++slot == NS) { slot = 0; eph ^= 1; }
        }
        asm volatile("cp.async.wait_all;" ::: "memory");
        return;
    }

    const int g = lane >> 2, t = lane & 3;
    uint32_t epoch;
    asm volatile("ld.relaxed.gpu.global.u32 %0, [%1];" : "=r"(epoch) : "l"(&g_epoch) : "memory");

    if (warp < NB) {
        uint2 raw[5];
#pragma unroll
        for (int i = 0; i < 5; i++) raw[i] = __ldg(reinterpret_cast<const uint2*>(x + warp * DM) + i * 32 + lane);
        float v[20];
#pragma unroll
        for (int i = 0; i < 5; i++) {
            v[4 * i] = bf_lo(raw[i].x); v[4 * i + 1] = bf_hi(raw[i].x);
            v[4 * i + 2] = bf_lo(raw[i].y); v[4 * i + 3] = bf_hi(raw[i].y);
        }
        float s = 0.f;
#pragma unroll
        for (int i = 0; i < 20; i++) s += v[i];
#pragma unroll
        for (int o = 16; o; o >>= 1) s += __shfl_xor_sync(0xffffffffu, s, o);
        const float mean = s * (1.0f / DM);
        float q2 = 0.f;
#pragma unroll
        for (int i = 0; i < 20; i++) { const float d = v[i] - mean; q2 += d * d; }
#pragma unroll
        for (int o = 16; o; o >>= 1) q2 += __shfl_xor_sync(0xffffffffu, q2, o);
        const float mb = bf_round(mean);
        const float sd = bf_round(sqrtf(bf_round(bf_round(q2 * (1.0f / DM)) + 1e-5f)));
        uint2* dst = reinterpret_cast<uint2*>(smem + SM_XN + warp * XS * 2);
#pragma unroll
        for (int i = 0; i < 5; i++) {
            uint2 o;
            o.x = pack_bf2(bf_round(v[4 * i] - mb) / sd, bf_round(v[4 * i + 1] - mb) / sd);
            o.y = pack_bf2(bf_round(v[4 * i + 2] - mb) / sd, bf_round(v[4 * i + 3] - mb) / sd);
            dst[i * 32 + lane] = o;
        }
    } else if (tid < NB * 32 + 4) {
        reinterpret_cast<uint32_t*>(smem + SM_PW)[NK + (tid & 3)] = 0u;
    }
    const int hu = cta * 5 + warp;
    uint2 xres = make_uint2(0u, 0u);
    if (is_att && warp < 5) xres = __ldg(reinterpret_cast<const uint2*>(x) + hu);
    asm volatile("bar.sync 2, %0;" ::"n"(NTHR) : "memory");
    const uint32_t tag = (epoch + 1u) & 1u;

    Cursor cur{0u, 0u};
    const uint32_t* xnw = reinterpret_cast<const uint32_t*>(smem + SM_XN) + (g & 3) * (XS / 2) + t;
    const bool arow = g < NB;

    if (is_att) {
        {
            float acc[3][4] = {};
            for (int i = 0; i < 5; i++) {
                const int kw = (qd * 160 + i * 32) / 2;
                const uint32_t a00 = arow ? xnw[kw] : 0u, a02 = arow ? xnw[kw + 4] : 0u;
                const uint32_t a10 = arow ? xnw[kw + 8] : 0u, a12 = arow ? xnw[kw + 12] : 0u;
                mbar_wait(bar_full + cur.slot * 8, cur.phase);
                gemv_item<true>(sb + SM_RING + cur.slot * SLOT + lane * 400 + warp * 16, a00, a02, a10, a12, acc);
                __syncwarp();
                if (lane == 0) mbar_arrive(bar_empty + cur.slot * 8);
                cur.next();
            }
            if (arow) {
                float* dst = g_qpart + (cta * NB + g) * DH + warp * 8 + 2 * t;
#pragma unroll
                for (int s = 0; s < 3; s++) st_tag2(dst + s * 64, acc[s][0], acc[s][1], tag);
            }
        }
        if (tid == 0) TS(3);
        const int sg = cta / G, r = cta % G;
        for (int it = tid; it < G * 48; it += NCW * 32) {
            const int j = it / 48, d4 = it % 48;
            const int pair = sg * G + j;
            const float* src = g_qpart + ((pair >> 2) * 4 * NB + (pair & 3)) * DH + d4 * 4;
            uint4 v[4];
            unsigned spin = 0;
            while (true) {
                uint32_t bad = 0;
#pragma unroll
                for (int k = 0; k < 4; k++) v[k] = ld_rlx4(src + k * NB * DH);
#pragma unroll
                for (int k = 0; k < 4; k++) bad |= bad4(v[k], tag);
                if (!bad) break;
                if (++spin > SPIN_LIMIT) __trap();
            }
            const float q0 = (__uint_as_float(v[0].x) + __uint_as_float(v[1].x)) + (__uint_as_float(v[2].x) + __uint_as_float(v[3].x));
            const float q1 = (__uint_as_float(v[0].y) + __uint_as_float(v[1].y)) + (__uint_as_float(v[2].y) + __uint_as_float(v[3].y));
            const float q2 = (__uint_as_float(v[0].z) + __uint_as_float(v[1].z)) + (__uint_as_float(v[2].z) + __uint_as_float(v[3].z));
            const float q3 = (__uint_as_float(v[0].w) + __uint_as_float(v[1].w)) + (__uint_as_float(v[2].w) + __uint_as_float(v[3].w));
            reinterpret_cast<uint2*>(smem + SM_QS)[it] = make_uint2(pack_bf2(q0, q1), pack_bf2(q2, q3));
        }
        cons_bar();
        if (tid == 0) TS(4);

        const int kb = warp & 1, dq = warp >> 1;
        const bool diag = t == (g >> 1);
        const uint32_t k_off = (kb * 16 + ((lane >> 3) & 1) * 8 + (lane & 7)) * 384 + (((2 * dq + (lane >> 4)) ^ (lane & 7)) << 4);
        const uint32_t v_off = lane * 384 + ((warp ^ (lane & 7)) << 4);
        float* sc = reinterpret_cast<float*>(smem + SM_SC);
        uint32_t* pw = reinterpret_cast<uint32_t*>(smem + SM_PW);
        float* red = reinterpret_cast<float*>(smem + SM_RED);
        float* lsum = reinterpret_cast<float*>(smem + SM_LS);
        for (int j = 0; j < G; j++) {
            uint32_t qf[3][2];
            {
                const uint32_t* qw = reinterpret_cast<const uint32_t*>(smem + SM_QS) + j * (DH / 2) + t;
#pragma unroll
                for (int s = 0; s < 3; s++) {
                    qf[s][0] = qw[s * 32 + ((2 * dq) ^ g) * 4];
                    qf[s][1] = qw[s * 32 + ((2 * dq + 1) ^ g) * 4];
                }
            }
            for (int tt = 0; tt < NT; tt++) {
                mbar_wait(bar_full + cur.slot * 8, cur.phase);
                const uint32_t addr = sb + SM_RING + cur.slot * SLOT + k_off;
                uint32_t a[3][4];
#pragma unroll
                for (int s = 0; s < 3; s++) ldsm_x4(addr + s * 128, a[s][0], a[s][1], a[s][2], a[s][3]);
                float c[4] = {0.f, 0.f, 0.f, 0.f};
#pragma unroll
                for (int s = 0; s < 3; s++) mma16816(c, a[s][0], a[s][1], a[s][2], a[s][3], qf[s][0], qf[s][1]);
                __syncwarp();
                if (lane == 0) mbar_arrive(bar_empty + cur.slot * 8);
                cur.next();
                if (diag) {
                    float* d = sc + (tt * TK + kb * 16 + g) * 4 + dq;
                    d[0] = (g & 1) ? c[1] : c[0];
                    d[32] = (g & 1) ? c[3] : c[2];
                }
            }
            cons_bar();
            float m = -INFINITY;
#pragma unroll
            for (int k = lane; k < NK; k += 32) {
                const float4 s4 = reinterpret_cast<const float4*>(sc)[k];
                m = fmaxf(m, bf_round(bf_round((s4.x + s4.y) + (s4.z + s4.w)) * 0.07216878364870323f));
            }
#pragma unroll
            for (int o = 16; o; o >>= 1) m = fmaxf(m, __shfl_xor_sync(0xffffffffu, m, o));
            float l = 0.f;
#pragma unroll
            for (int k = tid; k < NK; k += NCW * 32) {
                const float4 s4 = reinterpret_cast<const float4*>(sc)[k];
                const float s = bf_round(bf_round((s4.x + s4.y) + (s4.z + s4.w)) * 0.07216878364870323f);
                const float p = __expf(s - m);
                l += p;
                const uint32_t pb = (uint32_t)__bfloat16_as_ushort(__float2bfloat16_rn(p));
                pw[(k & ~31) + (k & 7) * 4 + ((k >> 3) & 3)] = (k & 1) ? (pb << 16) : pb;
            }
#pragma unroll
            for (int o = 16; o; o >>= 1) l += __shfl_xor_sync(0xffffffffu, l, o);
            if (lane == 0) lsum[warp] = l;
            cons_bar();
            float acc[3][4] = {};
            for (int tt = 0; tt < NT; tt++) {
                const uint4 pa = *reinterpret_cast<const uint4*>(pw + (diag ? tt * TK + g * 4 : NK));
                mbar_wait(bar_full + cur.slot * 8, cur.phase);
                gemv_item<true>(sb + SM_RING + cur.slot * SLOT + v_off, pa.x, pa.y, pa.z, pa.w, acc);
                __syncwarp();
                if (lane == 0) mbar_arrive(bar_empty + cur.slot * 8);
                cur.next();
            }
            if (j == G - 1 && tid == 0) TS(5);
#pragma unroll
            for (int s = 0; s < 3; s++)
                *reinterpret_cast<float2*>(red + g * DH + s * 64 + ((warp ^ g) << 3) + 2 * t) = make_float2(acc[s][0], acc[s][1]);
            cons_bar();
            float* dst = g_opart + ((sg * G + j) * G + r) * OPS;
            if (tid < DH) {
                float o = 0.f;
#pragma unroll
                for (int k = 0; k < 8; k++) o += red[k * DH + tid];
                st_tag1(dst + tid, o, tag);
            } else if (tid < OPS) {
                float ls = 0.f;
#pragma unroll
                for (int k = 0; k < NCW; k++) ls += lsum[k];
                st_tag1(dst + tid, (tid & 1) ? ls : m, tag);
            }
        }
        if (tid == 0) TS(6);

        if (tid < NB * 48) {
            const int b = tid / 48, d4 = tid % 48;
            const float* src = g_opart + (h * NB + b) * G * OPS;
            uint4 v[G];
            uint2 ml[G];
            unsigned spin = 0;
            while (true) {
                uint32_t bad = 0;
#pragma unroll
                for (int k = 0; k < G; k++) { v[k] = ld_rlx4(src + k * OPS + d4 * 4); ml[k] = ld_rlx2(src + k * OPS + DH); }
#pragma unroll
                for (int k = 0; k < G; k++) bad |= bad4(v[k], tag) | (((ml[k].x ^ tag) | (ml[k].y ^ tag)) & 1u);
                if (!bad) break;
                if (++spin > SPIN_LIMIT) __trap();
            }
            float M = -INFINITY;
#pragma unroll
            for (int k = 0; k < G; k++) M = fmaxf(M, __uint_as_float(ml[k].x & ~1u));
            float L = 0.f, o0 = 0.f, o1 = 0.f, o2 = 0.f, o3 = 0.f;
#pragma unroll
            for (int k = 0; k < G; k++) {
                const float w = __expf(__uint_as_float(ml[k].x & ~1u) - M);
                L += w * __uint_as_float(ml[k].y);
                o0 += w * __uint_as_float(v[k].x); o1 += w * __uint_as_float(v[k].y);
                o2 += w * __uint_as_float(v[k].z); o3 += w * __uint_as_float(v[k].w);
            }
            const float inv = 1.0f / L;
            *reinterpret_cast<uint2*>(smem + SM_OS + (b * OS + d4 * 4) * 2) =
                make_uint2(pack_bf2(o0 * inv, o1 * inv), pack_bf2(o2 * inv, o3 * inv));
        }
        cons_bar();
        if (tid == 0) TS(7);

        {
            float acc[3][4] = {}, acc2[3][4] = {};
            const uint32_t* ow = reinterpret_cast<const uint32_t*>(smem + SM_OS) + (g & 3) * (OS / 2) + t;
#pragma unroll
            for (int i = 0; i < 6; i++) {
                const uint32_t a00 = arow ? ow[i * 16] : 0u, a02 = arow ? ow[i * 16 + 4] : 0u;
                const uint32_t a10 = arow ? ow[i * 16 + 8] : 0u, a12 = arow ? ow[i * 16 + 12] : 0u;
                mbar_wait(bar_full + cur.slot * 8, cur.phase);
                const uint32_t addr = sb + SM_RING + cur.slot * SLOT + lane * 336 + warp * 16;
                if (warp < 4) gemv_item<true>(addr, a00, a02, a10, a12, (i & 1) ? acc2 : acc);
                else gemv_item<false>(addr, a00, a02, a10, a12, (i & 1) ? acc2 : acc);
                cur.next();
            }
            if (arow) {
                float* dst = g_fin + ((g * 80 + qd * 20 + warp) * NSRC + h) * 8 + 2 * t;
                st_tag2(dst, acc[0][0] + acc2[0][0], acc[0][1] + acc2[0][1], tag);
                st_tag2(dst + 8 * NSRC * 8, acc[1][0] + acc2[1][0], acc[1][1] + acc2[1][1], tag);
                if (warp < 4) st_tag2(dst + 16 * NSRC * 8, acc[2][0] + acc2[2][0], acc[2][1] + acc2[2][1], tag);
            }
        }
        if (tid == 0) TS(8);

        if (warp < 5) {
            const float* src = g_fin + (hu >> 1) * (NSRC * 8) + (hu & 1) * 4;
            uint4 va, vf;
            unsigned spin = 0;
            while (true) {
                va = ld_rlx4(src + lane * 8);
                vf = ld_rlx4(src + (NH + (lane & 3)) * 8);
                if (!(bad4(va, tag) | bad4(vf, tag))) break;
                if (++spin > SPIN_LIMIT) __trap();
            }
            float a0 = __uint_as_float(va.x), a1 = __uint_as_float(va.y), a2 = __uint_as_float(va.z), a3 = __uint_as_float(va.w);
            float f0 = __uint_as_float(vf.x), f1 = __uint_as_float(vf.y), f2 = __uint_as_float(vf.z), f3 = __uint_as_float(vf.w);
            __syncwarp();
#pragma unroll
            for (int o = 16; o; o >>= 1) {
                a0 += __shfl_xor_sync(0xffffffffu, a0, o); a1 += __shfl_xor_sync(0xffffffffu, a1, o);
                a2 += __shfl_xor_sync(0xffffffffu, a2, o); a3 += __shfl_xor_sync(0xffffffffu, a3, o);
                if (o <= 2) {
                    f0 += __shfl_xor_sync(0xffffffffu, f0, o); f1 += __shfl_xor_sync(0xffffffffu, f1, o);
                    f2 += __shfl_xor_sync(0xffffffffu, f2, o); f3 += __shfl_xor_sync(0xffffffffu, f3, o);
                }
            }
            if (lane == 0) {
                uint2 o;
                o.x = pack_bf2(bf_round(bf_lo(xres.x) + bf_round(a0)) + bf_round(f0), bf_round(bf_hi(xres.x) + bf_round(a1)) + bf_round(f1));
                o.y = pack_bf2(bf_round(bf_lo(xres.y) + bf_round(a2)) + bf_round(f2), bf_round(bf_hi(xres.y) + bf_round(a3)) + bf_round(f3));
                reinterpret_cast<uint2*>(out)[hu] = o;
                if (hu == 0) asm volatile("st.relaxed.gpu.global.u32 [%0], %1;" ::"l"(&g_epoch), "r"(epoch + 1u) : "memory");
            }
            if (tid == 0) TS(9);
        }
    } else {
        float acc[4][3][4] = {};
        for (int rb = 0; rb < 20; rb++) {
            const int kw = rb * 16;
            const uint32_t a00 = arow ? xnw[kw] : 0u, a02 = arow ? xnw[kw + 4] : 0u;
            const uint32_t a10 = arow ? xnw[kw + 8] : 0u, a12 = arow ? xnw[kw + 12] : 0u;
#pragma unroll
            for (int k = 0; k < 4; k++) {
                mbar_wait(bar_full + cur.slot * 8, cur.phase);
                gemv_item<true>(sb + SM_RING + cur.slot * SLOT + lane * 400 + warp * 16, a00, a02, a10, a12, acc[k]);
                __syncwarp();
                if (lane == 0) mbar_arrive(bar_empty + cur.slot * 8);
                cur.next();
            }
        }
        uint32_t* hw = reinterpret_cast<uint32_t*>(smem + SM_RED);
        if (arow) {
#pragma unroll
            for (int k = 0; k < 2; k++)
#pragma unroll
                for (int s = 0; s < 3; s++) {
                    float hv[2];
#pragma unroll
                    for (int e = 0; e < 2; e++) {
                        const float gt = bf_round(acc[k][s][e]), up = bf_round(acc[2 + k][s][e]);
                        hv[e] = bf_round(gt / (1.0f + __expf(-gt))) * up;
                    }
                    hw[g * (HS / 2) + k * 96 + s * 32 + warp * 4 + t] = pack_bf2(hv[0], hv[1]);
                }
        }
        cons_bar();
        float acc2[4][3][4] = {};
        const uint32_t* hr = hw + (g & 3) * (HS / 2) + t;
        for (int rb = 0; rb < 12; rb++) {
            const uint32_t a00 = arow ? hr[rb * 16] : 0u, a02 = arow ? hr[rb * 16 + 4] : 0u;
            const uint32_t a10 = arow ? hr[rb * 16 + 8] : 0u, a12 = arow ? hr[rb * 16 + 12] : 0u;
#pragma unroll
            for (int k = 0; k < 4; k++) {
                mbar_wait(bar_full + cur.slot * 8, cur.phase);
                const uint32_t addr = sb + SM_RING + cur.slot * SLOT + lane * 336 + warp * 16;
                if (warp < 4) gemv_item<true>(addr, a00, a02, a10, a12, acc2[k]);
                else gemv_item<false>(addr, a00, a02, a10, a12, acc2[k]);
                __syncwarp();
                if (lane == 0) mbar_arrive(bar_empty + cur.slot * 8);
                cur.next();
            }
        }
        if (arow) {
#pragma unroll
            for (int k = 0; k < 4; k++) {
                float* dst = g_fin + ((g * 80 + k * 20 + warp) * NSRC + NH + qd) * 8 + 2 * t;
                st_tag2(dst, acc2[k][0][0], acc2[k][0][1], tag);
                st_tag2(dst + 8 * NSRC * 8, acc2[k][1][0], acc2[k][1][1], tag);
                if (warp < 4) st_tag2(dst + 16 * NSRC * 8, acc2[k][2][0], acc2[k][2][1], tag);
            }
        }
        if (tid == 0) TS(9);
    }
}

}

extern "C" void kernel_launch(void* const* d_in, const int* in_sizes, int n_in, void* d_out, int out_size) {
    (void)in_sizes; (void)n_in; (void)out_size;
    static bool configured = false;
    if (!configured) {
        cudaFuncSetAttribute(fused_decode_kernel, cudaFuncAttributeMaxDynamicSharedMemorySize, SM_TOTAL);
        configured = true;
    }
    const bf16* x = (const bf16*)d_in[0];
    const bf16* kc = (const bf16*)d_in[1];
    const bf16* vc = (const bf16*)d_in[2];
    const bf16* wq = (const bf16*)d_in[3];
    const bf16* wo = (const bf16*)d_in[4];
    const bf16* w1 = (const bf16*)d_in[6];
    const bf16* w3 = (const bf16*)d_in[7];
    const bf16* w2 = (const bf16*)d_in[8];
    fused_decode_kernel<<<NCTA, NTHR, SM_TOTAL>>>(x, kc, vc, wq, wo, w1, w3, w2, (bf16*)d_out);
}
```

```cpp
#include <cuda_runtime.h>
#include <cuda.h>
#include <cuda_bf16.h>
#include <stdint.h>

namespace {

typedef __nv_bfloat16 bf16;

constexpr int NB = 4, DM = 640, NH = 32, DH = 192, SK = 8192, WIN = 2048, FF = 1536;

#define P_G 16
#define P_DEPTH 4
#define P_DEPTH_FFN 4
#define P_PFMAP 1
#define P_PREW 1
#define P_CELL 1
#define P_LATE 1
#define P_NS 16

constexpr int G = P_G;
constexpr int TK = 32;
constexpr int NT = WIN / TK / G;
constexpr int NK = NT * TK;
constexpr int NS = P_NS;
constexpr int SLOT = 12288;
constexpr int DEPTH = P_DEPTH;
constexpr int DEPTH0 = DEPTH < P_DEPTH_FFN ? DEPTH : P_DEPTH_FFN;
static_assert(DEPTH0 <= 5, "DEPTH0");
constexpr int NATT = 128, NFFN = 4, NCTA = NATT + NFFN;
constexpr int NCW = 8;
constexpr int NXW = 3;
constexpr int NTHR = (NCW + 1 + NXW) * 32;
constexpr int NSRC = NH + NFFN;
constexpr int OPS = 200;
static_assert(G >= 4 && G <= 32, "G");

constexpr int SM_RING = 0;
constexpr int SM_XF = SM_RING + NS * SLOT;
constexpr int SM_QS = SM_XF + 20 * 256;
constexpr int SM_SC = SM_QS + G * DH * 2;
constexpr int SM_PF = SM_SC + NK * 16;
constexpr int SM_OF = SM_PF + NT * 64;
constexpr int SM_LS = SM_OF + 6 * 256;
constexpr int SM_ATT_END = SM_LS + 32;
constexpr int SM_HF = SM_XF + 40 * 256;
constexpr int SM_FFN_END = SM_HF + 24 * 256;
constexpr int SM_BAR = SM_ATT_END > SM_FFN_END ? SM_ATT_END : SM_FFN_END;
constexpr int B_QRDY = 2 * NS * 8, B_ORDY = B_QRDY + G * 8, B_TRIG = B_ORDY + 8, NBAR = 2 * NS + G + 7;
constexpr int SM_TS = SM_BAR + NBAR * 8;
constexpr int SM_TOTAL = SM_TS + 128;
static_assert(SM_TOTAL <= 232448, "smem");

constexpr int NKV = 2 * NT * G;
constexpr int ITEMS_ATT = 5 + NKV + 6;
constexpr int ITEMS_FFN = 80 + 48;

struct Maps { CUtensorMap k, v, wq, wo, w1, w3, w2; };

struct alignas(32) Sync { unsigned epoch, inits; };
__device__ Sync g_sync;
__device__ float g_qpart[NATT * NB * DH];
__device__ float g_opart[NATT * G * OPS];
__device__ float4 g_acc[NB * DM / 2 * P_CELL];
#define TS(i)
#define TS_DUMP(lo, hi)

constexpr unsigned SPIN_LIMIT = 1u << 24;

__device__ __forceinline__ void mbar_init(uint32_t bar, int cnt) {
    asm volatile("mbarrier.init.shared::cta.b64 [%0], %1;" ::"r"(bar), "r"(cnt) : "memory");
}
__device__ __forceinline__ void mbar_expect_tx(uint32_t bar, uint32_t bytes) {
    asm volatile("mbarrier.arrive.expect_tx.shared::cta.b64 _, [%0], %1;" ::"r"(bar), "r"(bytes) : "memory");
}
__device__ __forceinline__ void mbar_arrive(uint32_t bar) {
    asm volatile("mbarrier.arrive.shared::cta.b64 _, [%0];" ::"r"(bar) : "memory");
}
__device__ __forceinline__ void mbar_wait(uint32_t bar, uint32_t parity) {
    asm volatile("{\n.reg .pred p, q;\n.reg .u32 n;\nmov.u32 n, 0;\n"
                 "W: mbarrier.try_wait.parity.shared::cta.b64 p, [%0], %1;\n"
                 "@p bra D;\nadd.u32 n, n, 1;\nsetp.lt.u32 q, n, %2;\n@q bra W;\ntrap;\nD:\n}"
                 ::"r"(bar), "r"(parity), "n"(SPIN_LIMIT) : "memory");
}
__device__ __forceinline__ void tma3d(uint32_t dst, const CUtensorMap* map, int c1, int c2, uint32_t bar, uint64_t pol) {
    asm volatile("cp.async.bulk.tensor.3d.shared::cluster.global.mbarrier::complete_tx::bytes.L2::cache_hint "
                 "[%0], [%1, {%2, %3, %4}], [%5], %6;"
                 ::"r"(dst), "l"(map), "r"(0), "r"(c1), "r"(c2), "r"(bar), "l"(pol) : "memory");
}
__device__ __forceinline__ void ldsm_x4(uint32_t addr, uint32_t (&r)[4]) {
    asm volatile("ldmatrix.sync.aligned.m8n8.x4.shared.b16 {%0,%1,%2,%3}, [%4];"
                 : "=r"(r[0]), "=r"(r[1]), "=r"(r[2]), "=r"(r[3]) : "r"(addr) : "memory");
}
__device__ __forceinline__ void ldsm_x4_t(uint32_t addr, uint32_t (&r)[4]) {
    asm volatile("ldmatrix.sync.aligned.m8n8.x4.trans.shared.b16 {%0,%1,%2,%3}, [%4];"
                 : "=r"(r[0]), "=r"(r[1]), "=r"(r[2]), "=r"(r[3]) : "r"(addr) : "memory");
}
__device__ __forceinline__ void lds128(uint32_t addr, uint32_t (&r)[4]) {
    asm volatile("ld.shared.v4.u32 {%0,%1,%2,%3}, [%4];"
                 : "=r"(r[0]), "=r"(r[1]), "=r"(r[2]), "=r"(r[3]) : "r"(addr) : "memory");
}
__device__ __forceinline__ void mma16816(float (&c)[4], const uint32_t (&a)[4], uint32_t b0, uint32_t b1) {
    asm volatile("mma.sync.aligned.m16n8k16.row.col.f32.bf16.bf16.f32 {%0,%1,%2,%3}, {%4,%5,%6,%7}, {%8,%9}, {%0,%1,%2,%3};"
                 : "+f"(c[0]), "+f"(c[1]), "+f"(c[2]), "+f"(c[3])
                 : "r"(a[0]), "r"(a[1]), "r"(a[2]), "r"(a[3]), "r"(b0), "r"(b1));
}
__device__ __forceinline__ void cons_bar() { asm volatile("bar.sync 1, 256;" ::: "memory"); }

__device__ __forceinline__ float bf_round(float v) { return __bfloat162float(__float2bfloat16_rn(v)); }
__device__ __forceinline__ uint32_t pack_bf2(float lo, float hi) {
    __nv_bfloat162 t = __floats2bfloat162_rn(lo, hi);
    return *reinterpret_cast<uint32_t*>(&t);
}
__device__ __forceinline__ float bf_lo(uint32_t u) { return __uint_as_float(u << 16); }
__device__ __forceinline__ float bf_hi(uint32_t u) { return __uint_as_float(u & 0xffff0000u); }
__device__ __forceinline__ float shx(float v, int o) { return __shfl_xor_sync(0xffffffffu, v, o); }

__device__ __forceinline__ uint32_t frag_off(uint32_t k) {
    return ((k >> 1) & 3) * 16 + ((k >> 3) & 1) * 8 + ((k >> 4) & 1) * 4 + (k & 1) * 2;
}

__device__ __forceinline__ uint32_t tagw(float v, uint32_t tag) { return (__float_as_uint(v) & ~1u) | tag; }
__device__ __forceinline__ void st_tag1(float* p, float a, uint32_t tag) {
    asm volatile("st.relaxed.gpu.global.u32 [%0], %1;" ::"l"(p), "r"(tagw(a, tag)) : "memory");
}
__device__ __forceinline__ void st_tag2(float* p, float a, float b, uint32_t tag) {
    asm volatile("st.relaxed.gpu.global.v2.u32 [%0], {%1,%2};" ::"l"(p), "r"(tagw(a, tag)), "r"(tagw(b, tag)) : "memory");
}
__device__ __forceinline__ void st_fill4(float* p, uint32_t v) {
    asm volatile("st.relaxed.gpu.global.v4.u32 [%0], {%1,%1,%1,%1};" ::"l"(p), "r"(v) : "memory");
}
__device__ __forceinline__ void ld_need2(uint2& v, const float* p, uint32_t tag, uint32_t go) {
    asm volatile("{\n.reg .pred p;\nsetp.ne.u32 p, %3, 0;\n@p ld.relaxed.gpu.global.v2.u32 {%0,%1}, [%2];\n}"
                 : "+r"(v.x), "+r"(v.y) : "l"(p), "r"(((v.x ^ tag) | (v.y ^ tag)) & go) : "memory");
}
__device__ __forceinline__ uint32_t ld_rlx1(const float* p) {
    uint32_t v;
    asm volatile("ld.relaxed.gpu.global.u32 %0, [%1];" : "=r"(v) : "l"(p) : "memory");
    return v;
}
__device__ __forceinline__ uint2 ld_rlx2(const float* p) {
    uint2 v;
    asm volatile("ld.relaxed.gpu.global.v2.u32 {%0,%1}, [%2];" : "=r"(v.x), "=r"(v.y) : "l"(p) : "memory");
    return v;
}

template <int N>
__device__ __forceinline__ void add_out(const float4* acc, uint32_t* out, const float (&v)[N][2], uint32_t live,
                                        uint32_t live_last, uint32_t epoch) {
    float o[N][4];
#pragma unroll
    for (int i = 0; i < N; i++) {
        o[i][2] = 0.f;
        asm volatile("{\n.reg .pred p;\nsetp.ne.u32 p, %5, 0;\n"
                     "@p atom.relaxed.gpu.global.add.v4.f32 {%0,%1,%2,%3}, [%4], {%6,%7,%8,%9};\n}"
                     : "=f"(o[i][0]), "=f"(o[i][1]), "+f"(o[i][2]), "=f"(o[i][3])
                     : "l"(acc + i * 32 * P_CELL), "r"(i < N - 1 ? live : live_last), "f"(v[i][0]), "f"(v[i][1]), "f"(1.0f), "f"(0.0f)
                     : "memory");
    }
#pragma unroll
    for (int i = 0; i < N; i++)
        asm volatile("{\n.reg .pred p;\nsetp.eq.f32 p, %2, %3;\n@p st.global.u32 [%0], %1;\n}"
                     ::"l"(out + i * 32), "r"(pack_bf2(o[i][0] + v[i][0], o[i][1] + v[i][1])), "f"(o[i][2]), "f"((float)(NSRC - 1))
                     : "memory");
    if (acc == g_acc && o[0][2] == (float)(NSRC - 1))
        asm volatile("st.relaxed.gpu.global.u32 [%0], %1;" ::"l"(&g_sync.epoch), "r"(epoch + 1u) : "memory");
}

struct Ring {
    uint32_t full, addr, phase, first_full;
    __device__ __forceinline__ void wait() const { mbar_wait(full, phase); }
    __device__ __forceinline__ void release(int lane) {
        __syncwarp();
        if (lane == 0) mbar_arrive(full + NS * 8);
        full += 8; addr += SLOT;
        if (full == first_full + NS * 8) { full = first_full; addr -= NS * SLOT; phase ^= 1; }
    }
};

__device__ __forceinline__ void pin3(uint32_t (&v)[3]) {
    asm volatile("" : "+r"(v[0]), "+r"(v[1]), "+r"(v[2]));
}
__device__ __forceinline__ void gemv_loop(Ring& ring, int n, uint32_t a_addr, uint32_t a_step, uint32_t (&off)[3],
                                          float (&lo)[3][4], float (&hi)[3][4], int lane) {
    pin3(off);
#pragma unroll
    for (int s = 0; s < 3; s++)
#pragma unroll
        for (int e = 0; e < 4; e++) { lo[s][e] = 0.f; hi[s][e] = 0.f; }
#pragma unroll 1
    for (int it = 0; it < n; it++) {
        uint32_t a[4], b[3][4];
        lds128(a_addr, a);
        a_addr += a_step;
        ring.wait();
#pragma unroll
        for (int s = 0; s < 3; s++) ldsm_x4_t(ring.addr + off[s], b[s]);
#pragma unroll
        for (int s = 0; s < 3; s++) { mma16816(lo[s], a, b[s][0], b[s][1]); mma16816(hi[s], a, b[s][2], b[s][3]); }
        ring.release(lane);
    }
}

__global__ void __launch_bounds__(NTHR, 1)
fused_decode_kernel(const __grid_constant__ Maps maps, const bf16* __restrict__ x, bf16* __restrict__ out) {
    extern __shared__ __align__(1024) unsigned char smem[];
    const uint32_t sb = (uint32_t)__cvta_generic_to_shared(smem);
    const int tid = threadIdx.x, warp = tid >> 5, lane = tid & 31;
    const int cta = blockIdx.x;
    const bool is_att = cta < NATT;
    const int h = cta >> 2, qd = cta & 3;
    const int sg = cta / G, r = cta % G;
    const uint32_t bar_full = sb + SM_BAR;

    uint64_t pol;
    asm volatile("createpolicy.fractional.L2::evict_first.b64 %0, 1.0;" : "=l"(pol));
    if (tid == NCW * 32) {
        TS(0);
        const CUtensorMap* map = is_att ? &maps.wq : &maps.w1;
        const int c1 = is_att ? h * 3 : qd * 6, c2 = is_att ? qd * 160 : 0, step = is_att ? 32 : 16;
#pragma unroll 1
        for (int i = 0; i < DEPTH0; i++) {
            mbar_init(bar_full + i * 8, 1);
            mbar_expect_tx(bar_full + i * 8, 12288);
            tma3d(sb + SM_RING + i * SLOT, map, c1, c2 + i * step, bar_full + i * 8, pol);
        }
        TS(1);
    }
    if (warp == NCW) {
        if (lane == 0) {
#pragma unroll
            for (int i = DEPTH0; i < NBAR; i++) mbar_init(bar_full + i * 8, i < NS ? 1 : i < 2 * NS ? NCW : i <= 2 * NS + G ? NXW : 1);
            asm volatile("fence.mbarrier_init.release.cluster;" ::: "memory");
        }
        __syncwarp();
        asm volatile("bar.arrive 2, %0;" ::"n"(NTHR) : "memory");
        if (lane == 0) {
            const int n_items = is_att ? ITEMS_ATT : ITEMS_FFN;
            const int depth = is_att ? DEPTH : P_DEPTH_FFN;
            asm volatile("prefetch.tensormap [%0];" ::"l"(is_att ? &maps.k : &maps.w3) : "memory");
            asm volatile("prefetch.tensormap [%0];" ::"l"(is_att ? &maps.v : &maps.w2) : "memory");
            asm volatile("prefetch.tensormap [%0];" ::"l"(&maps.wo) : "memory");
#pragma unroll 1
            for (int i = DEPTH0; i < n_items; i++) {
                const CUtensorMap* map;
                int c1, c2;
                uint32_t bytes = 12288;
                if (is_att) {
                    const uint32_t u = i - 5;
                    if (u < NKV) {
                        const int pair = sg * G + u / (2 * NT);
                        map = (u & NT) ? &maps.v : &maps.k;
                        c1 = 0;
                        c2 = ((pair & 3) * NH + (pair >> 2)) * SK + (SK - WIN) + ((u % NT) * G + r) * TK;
                    } else if (i < 5) {
                        map = &maps.wq; c1 = h * 3; c2 = qd * 160 + i * 32;
                    } else {
                        map = &maps.wo; c1 = qd * 5; c2 = h * DH + (u - NKV) * 32; bytes = 10240;
                    }
                } else {
                    if (i < 80) {
                        map = i < 40 ? &maps.w1 : &maps.w3; c1 = qd * 6; c2 = (i < 40 ? i : i - 40) * 16;
                    } else {
                        map = &maps.w2; c1 = i < 104 ? 0 : 5; c2 = qd * 384 + (i < 104 ? i - 80 : i - 104) * 16; bytes = 10240;
                    }
                }
                const uint32_t slot = i % NS;
                if (i >= depth) mbar_wait(bar_full + ((i - depth) % NS) * 8, ((i - depth) / NS) & 1);
                if (i >= NS) mbar_wait(bar_full + (NS + slot) * 8, (i / NS - 1) & 1);
                mbar_expect_tx(bar_full + slot * 8, bytes);
                tma3d(sb + SM_RING + slot * SLOT, map, c1, c2, bar_full + slot * 8, pol);
            }
        }
        return;
    }

    const int g = lane >> 2, t = lane & 3;
    uint32_t epoch;
    asm volatile("ld.relaxed.gpu.global.u32 %0, [%1];" : "=r"(epoch) : "l"(&g_sync.epoch) : "memory");

    if (warp > NCW) {
        const uint32_t tag = (epoch + 1u) & 1u;
        const int e = tid - (NCW + 1) * 32;
        if (is_att) {
            const uint32_t nt = tag ^ 1u;
            st_fill4(g_qpart + cta * (NB * DH) + e * 4, nt);
            st_fill4(g_qpart + cta * (NB * DH) + e * 4 + 384, nt);
            if (e < OPS / 4) {
#pragma unroll 1
                for (int j = 0; j < G; j++) st_fill4(g_opart + ((sg * G + j) * G + r) * OPS + e * 4, nt);
            }
        }
        if (!is_att) {
#pragma unroll 1
            for (int c = qd * 320 + e; c < qd * 320 + 320; c += NXW * 32) {
                const uint32_t xw = __ldg(reinterpret_cast<const uint32_t*>(x) + c);
                asm volatile("st.relaxed.gpu.global.v4.f32 [%0], {%1,%2,%3,%3};"
                             ::"l"(g_acc + c * P_CELL), "f"(bf_lo(xw)), "f"(bf_hi(xw)), "f"(0.f) : "memory");
                if (P_CELL > 1) asm volatile("st.relaxed.gpu.global.v4.f32 [%0], {%1,%1,%1,%1};" ::"l"(g_acc + c * P_CELL + 1), "f"(0.f) : "memory");
            }
            __syncwarp();
            if (lane == 0) asm volatile("red.release.gpu.global.add.u32 [%0], 1;" ::"l"(&g_sync.inits) : "memory");
        }
        asm volatile("bar.sync 2, %0;" ::"n"(NTHR) : "memory");
        if (is_att) {
        mbar_wait(bar_full + B_TRIG + 40, 0);
        if (e == 0) TS(10);
#pragma unroll 1
        for (int j = 0; j < G; j++) {
            const int pair = sg * G + j;
            const float* src = g_qpart + ((pair >> 2) * 4 * NB + (pair & 3)) * DH + e * 2;
            uint2 v0, v1, v2, v3;
            unsigned spin = 0;
            while (true) {
                asm volatile("ld.relaxed.gpu.global.v2.u32 {%0,%1}, [%8];\n"
                             "ld.relaxed.gpu.global.v2.u32 {%2,%3}, [%8+3072];\n"
                             "ld.relaxed.gpu.global.v2.u32 {%4,%5}, [%8+6144];\n"
                             "ld.relaxed.gpu.global.v2.u32 {%6,%7}, [%8+9216];"
                             : "=r"(v0.x), "=r"(v0.y), "=r"(v1.x), "=r"(v1.y), "=r"(v2.x), "=r"(v2.y), "=r"(v3.x), "=r"(v3.y)
                             : "l"(src) : "memory");
                const uint32_t all = v0.x & v0.y & v1.x & v1.y & v2.x & v2.y & v3.x & v3.y;
                const uint32_t any = v0.x | v0.y | v1.x | v1.y | v2.x | v2.y | v3.x | v3.y;
                if ((tag ? all : ~any) & 1u) break;
                if (++spin > SPIN_LIMIT) __trap();
            }
            reinterpret_cast<uint32_t*>(smem + SM_QS)[j * (DH / 2) + e] = pack_bf2(
                (__uint_as_float(v0.x) + __uint_as_float(v1.x)) + (__uint_as_float(v2.x) + __uint_as_float(v3.x)),
                (__uint_as_float(v0.y) + __uint_as_float(v1.y)) + (__uint_as_float(v2.y) + __uint_as_float(v3.y)));
            __syncwarp();
            if (lane == 0) mbar_arrive(bar_full + B_QRDY + j * 8);
        }
        }
        if (e == 0) {
            unsigned spin = 0, n;
            do {
                asm volatile("ld.acquire.gpu.global.u32 %0, [%1];" : "=r"(n) : "l"(&g_sync.inits) : "memory");
                if (++spin > SPIN_LIMIT) __trap();
            } while (n != (epoch + 1u) * (NFFN * NXW));
        }
#pragma unroll 1
        for (int b = 0; b < (is_att ? NB : 0); b++) {
            const float* src = g_opart + (h * NB + b) * (G * OPS);
            const float* mlp = src + (lane % G) * OPS + DH;
            src += e * 2;
            uint32_t go = h * NB + b != sg * G + G - 1;
            bool have_w = false;
            float wk[G];
            uint2 v[G], ml = make_uint2(~tag, ~tag);
#pragma unroll
            for (int k = 0; k < G; k++) v[k] = ml;
            mbar_wait(bar_full + B_TRIG + b * 8, 0);
            unsigned spin = 0;
            while (true) {
                ld_need2(ml, mlp, tag, 1u);
#pragma unroll
                for (int k = 0; k < G; k++) ld_need2(v[k], src + k * OPS, tag, go);
                if (!have_w) {
                    if (__all_sync(0xffffffffu, (((ml.x ^ tag) | (ml.y ^ tag)) & 1u) == 0u)) {
                        const float mk = __uint_as_float(ml.x & ~1u);
                        float M = mk;
#pragma unroll
                        for (int o = G / 2; o; o >>= 1) M = fmaxf(M, shx(M, o));
                        float w = __expf(mk - M);
                        float L = w * __uint_as_float(ml.y);
#pragma unroll
                        for (int o = G / 2; o; o >>= 1) L += shx(L, o);
                        w = __fdividef(w, L);
#pragma unroll
                        for (int k = 0; k < G; k++) wk[k] = __shfl_sync(0xffffffffu, w, k);
                        have_w = true;
                        if (!go) mbar_wait(bar_full + B_TRIG + 32, 0);
                        go = 1u;
                    }
                }
                uint32_t bad = 0;
#pragma unroll
                for (int k = 0; k < G; k++) bad |= (v[k].x ^ tag) | (v[k].y ^ tag);
                if (have_w && !(bad & 1u)) break;
                if (++spin > SPIN_LIMIT) __trap();
            }
            float o0 = 0.f, o1 = 0.f, o2 = 0.f, o3 = 0.f;
#pragma unroll
            for (int k = 0; k < G; k += 2) {
                o0 += wk[k] * __uint_as_float(v[k].x);
                o1 += wk[k] * __uint_as_float(v[k].y);
                o2 += wk[k + 1] * __uint_as_float(v[k + 1].x);
                o3 += wk[k + 1] * __uint_as_float(v[k + 1].y);
            }
            o0 += o2; o1 += o3;
            *reinterpret_cast<uint32_t*>(smem + SM_OF + (e >> 4) * 256 + b * 64 + frag_off((e * 2) & 31)) = pack_bf2(o0, o1);
            __syncwarp();
        }
        __syncwarp();
        if (lane == 0) mbar_arrive(bar_full + B_ORDY);
        return;
    }

    if (warp < NB) {
        uint2 raw[5];
#pragma unroll
        for (int i = 0; i < 5; i++) raw[i] = __ldg(reinterpret_cast<const uint2*>(x + warp * DM) + i * 32 + lane);
        float s = 0.f;
#pragma unroll
        for (int i = 0; i < 5; i++) s += (bf_lo(raw[i].x) + bf_hi(raw[i].x)) + (bf_lo(raw[i].y) + bf_hi(raw[i].y));
#pragma unroll
        for (int o = 16; o; o >>= 1) s += shx(s, o);
        const float mean = s * (1.0f / DM);
        float q2 = 0.f;
#pragma unroll
        for (int i = 0; i < 5; i++) {
            const float d0 = bf_lo(raw[i].x) - mean, d1 = bf_hi(raw[i].x) - mean;
            const float d2 = bf_lo(raw[i].y) - mean, d3 = bf_hi(raw[i].y) - mean;
            q2 += (d0 * d0 + d1 * d1) + (d2 * d2 + d3 * d3);
        }
#pragma unroll
        for (int o = 16; o; o >>= 1) q2 += shx(q2, o);
        const float mb = bf_round(mean);
        const float rs = __frcp_rn(bf_round(__fsqrt_rn(bf_round(bf_round(q2 * (1.0f / DM)) + 1e-5f))));
        const uint32_t k = (lane * 4) & 31;
        unsigned char* dst = smem + SM_XF + warp * 64 +
            (is_att ? (lane >> 3) * 256 + frag_off(k) : (lane >> 2) * 256 + frag_off(k & 15));
        const uint32_t step = is_att ? 1024 : 2048;
#pragma unroll
        for (int i = 0; i < 5; i++) {
            const uint32_t d0 = pack_bf2(bf_lo(raw[i].x) - mb, bf_hi(raw[i].x) - mb);
            const uint32_t d1 = pack_bf2(bf_lo(raw[i].y) - mb, bf_hi(raw[i].y) - mb);
            *reinterpret_cast<uint32_t*>(dst + i * step) = pack_bf2(bf_lo(d0) * rs, bf_hi(d0) * rs);
            *reinterpret_cast<uint32_t*>(dst + i * step + 16) = pack_bf2(bf_lo(d1) * rs, bf_hi(d1) * rs);
        }
    }
    asm volatile("bar.sync 2, %0;" ::"n"(NTHR) : "memory");
    const uint32_t tag = (epoch + 1u) & 1u;
    if (tid == 0) TS(3);

    Ring ring{bar_full, sb + SM_RING, 0u, bar_full};
    float lo[3][4], hi[3][4];
    uint32_t off[3];
    const uint32_t a_lane = (g & 3) * 64 + t * 16;

    if (is_att) {
        float* sc = reinterpret_cast<float*>(smem + SM_SC);
        float* lsum = reinterpret_cast<float*>(smem + SM_LS);
#pragma unroll 1
        for (int j = -1; j < G; j++) {
            const bool kv = j >= 0;
            const int pair = sg * G + j;
            if (kv) {
                const int kb = warp & 1, dq = warp >> 1;
                const uint32_t key = kb * 16 + (lane & 15);
                uint32_t qf[3][2];
                mbar_wait(bar_full + B_QRDY + j * 8, 0);
                if (j == 0 && tid == 0) TS(6);
                const uint32_t* qw = reinterpret_cast<const uint32_t*>(smem + SM_QS) + j * (DH / 2) + dq * 8 + t;
#pragma unroll
                for (int s = 0; s < 3; s++) {
                    qf[s][0] = qw[s * 32];
                    qf[s][1] = qw[s * 32 + 4];
                    off[s] = key * 384 + s * 128 + (((2 * dq + (lane >> 4)) ^ ((3 * key + s) & 7)) << 4);
                }
                pin3(off);
                float* d = sc + (kb * 16 + g) * 4 + dq;
#pragma unroll 1
                for (int tt = 0; tt < NT; tt++) {
                    uint32_t a[3][4];
                    ring.wait();
#pragma unroll
                    for (int s = 0; s < 3; s++) ldsm_x4(ring.addr + off[s], a[s]);
                    float c[4] = {0.f, 0.f, 0.f, 0.f};
#pragma unroll
                    for (int s = 0; s < 3; s++) mma16816(c, a[s], qf[s][0], qf[s][1]);
                    ring.release(lane);
                    if (t == 0) { d[0] = c[0]; d[32] = c[2]; }
                    d += TK * 4;
                }
            }
            const bool trig = tid == 0 && j >= 1 && ((pair - 1) >> 2) == h;
            if (trig && (j == G - 1 || !P_LATE)) mbar_arrive(bar_full + B_TRIG + ((pair - 1) & 3) * 8);
            uint32_t a_addr, a_step, rows;
            int n;
            float* dst;
            if (kv) {
                cons_bar();
                float m = -INFINITY;
#pragma unroll 2
                for (int k = lane; k < NK; k += 32) {
                    const float4 s4 = reinterpret_cast<const float4*>(sc)[k];
                    m = fmaxf(m, (s4.x + s4.y) + (s4.z + s4.w));
                }
#pragma unroll
                for (int o = 16; o; o >>= 1) m = fmaxf(m, shx(m, o));
                m = bf_round(bf_round(m) * 0.07216878364870323f);
                float l = 0.f;
#pragma unroll 1
                for (int k = tid; k < NK; k += NCW * 32) {
                    const float4 s4 = reinterpret_cast<const float4*>(sc)[k];
                    const float s = bf_round(bf_round((s4.x + s4.y) + (s4.z + s4.w)) * 0.07216878364870323f);
                    const float p = __expf(s - m);
                    l += p;
                    *reinterpret_cast<bf16*>(smem + SM_PF + (k >> 5) * 64 + frag_off(lane)) = __float2bfloat16_rn(p);
                }
#pragma unroll
                for (int o = 16; o; o >>= 1) l += shx(l, o);
                if (lane == 0) lsum[warp] = l;
                cons_bar();
                dst = g_opart + (pair * G + r) * OPS;
                if (tid < 8) {
                    const float4 l0 = reinterpret_cast<const float4*>(lsum)[0], l1 = reinterpret_cast<const float4*>(lsum)[1];
                    st_tag1(dst + DH + tid, (tid & 1) ? ((l0.x + l0.y) + (l0.z + l0.w)) + ((l1.x + l1.y) + (l1.z + l1.w)) : m, tag);
                }
                if (trig && j == G - 1) mbar_arrive(bar_full + B_TRIG + 24);
                dst += warp * 8;
                a_addr = sb + SM_PF + t * 16; a_step = 64; n = NT; rows = 1;
            } else {
                dst = g_qpart + (cta * NB + g) * DH + warp * 8;
                a_addr = sb + SM_XF + qd * 5 * 256 + a_lane; a_step = 256; n = 5; rows = NB;
            }
#pragma unroll
            for (int s = 0; s < 3; s++) off[s] = lane * 384 + s * 128 + ((warp ^ ((3 * lane + s) & 7)) << 4);
            gemv_loop(ring, n, a_addr, a_step, off, lo, hi, lane);
            if (trig && (j == G - 1 || P_LATE)) mbar_arrive(bar_full + B_TRIG + (j == G - 1 ? 32 : ((pair - 1) & 3) * 8));
            if (j == G - 1 && tid == 0) TS(5);
            if (g < rows) {
#pragma unroll
                for (int s = 0; s < 3; s++) st_tag2(dst + 2 * t + s * 64, lo[s][0] + hi[s][2], lo[s][1] + hi[s][3], tag);
            }
            if (j >= 0 && j < G - 1) continue;
            if (tid == 0 && j < 0) { mbar_arrive(bar_full + B_TRIG + 40); TS(4); }

            {
                const uint32_t done = bar_full + B_TRIG + 40;
                uint32_t b[6][3][4];
#pragma unroll
                for (int s = 0; s < 3; s++) {
                    const uint32_t w64 = lane * 320 + (warp + 8 * s) * 16;
                    off[s] = sb + SM_RING + (w64 ^ (((w64 >> 7) & 3) << 4));
#pragma unroll
                    for (int e = 0; e < 4; e++) { lo[s][e] = 0.f; hi[s][e] = 0.f; }
                }
                const int cell = g * 320 + (qd * 20 + warp) * 4 + t;
                const float4* accp = g_acc + cell * P_CELL;
                uint32_t* outp = reinterpret_cast<uint32_t*>(out) + cell;
                uint32_t live = kv && g < NB, live3 = live && warp < 4, a_addr = sb + SM_OF + a_lane;
                pin3(off);
                asm volatile("" : "+l"(accp), "+l"(outp), "+r"(live), "+r"(live3), "+r"(a_addr));
#pragma unroll
                for (int i = 0; i < 6; i++) {
                    constexpr int I0 = 5 + NKV;
                    if (i == 5) {
                        mbar_wait(kv ? bar_full + B_ORDY : done, 0);
                        if (kv && tid == 0) TS(7);
#pragma unroll
                        for (int k = 0; k < 5; k++) {
                            uint32_t a[4];
                            lds128(a_addr + k * 256, a);
#pragma unroll
                            for (int s = 0; s < 3; s++)
                                if (s < 2 || warp < 4) { mma16816(lo[s], a, b[k][s][0], b[k][s][1]); mma16816(hi[s], a, b[k][s][2], b[k][s][3]); }
                        }
                    }
                    mbar_wait(kv ? bar_full + ((I0 + i) % NS) * 8 : done, kv ? ((I0 + i) / NS) & 1 : 0);
#pragma unroll
                    for (int s = 0; s < 3; s++) ldsm_x4_t(off[s] + ((I0 + i) % NS) * SLOT, b[i][s]);
                }
                uint32_t a[4];
                lds128(a_addr + 5 * 256, a);
#pragma unroll
                for (int s = 0; s < 3; s++) { mma16816(lo[s], a, b[5][s][0], b[5][s][1]); mma16816(hi[s], a, b[5][s][2], b[5][s][3]); }
                if (kv && tid == 0) TS(8);
                float v[3][2];
#pragma unroll
                for (int s = 0; s < 3; s++) { v[s][0] = lo[s][0] + hi[s][2]; v[s][1] = lo[s][1] + hi[s][3]; }
                add_out<3>(accp, outp, v, live, live3, epoch);
            }
        }
        if (tid == 0) { TS(9); TS_DUMP(3, 16); }
    } else {
        float gate[6][2];
#pragma unroll 1
        for (int ps = 0; ps < 4; ps++) {
            const uint32_t row = lane & 15, parts = ps < 2 ? 6 : 5;
#pragma unroll
            for (int s = 0; s < 3; s++) {
                const uint32_t r128 = row * parts + min(2 * s + (lane >> 4), parts - 1);
                off[s] = r128 * 128 + ((warp ^ (r128 & 7)) << 4);
            }
            gemv_loop(ring, ps < 2 ? 40 : 24, sb + (ps < 2 ? SM_XF : SM_HF) + a_lane, 256, off, lo, hi, lane);
            if (ps == 0) {
#pragma unroll
                for (int s = 0; s < 3; s++) {
                    gate[2 * s][0] = lo[s][0]; gate[2 * s][1] = lo[s][1];
                    gate[2 * s + 1][0] = hi[s][0]; gate[2 * s + 1][1] = hi[s][1];
                }
            } else if (ps == 1) {
#pragma unroll
                for (int p = 0; p < 6; p++) {
                    float hv[2];
#pragma unroll
                    for (int e = 0; e < 2; e++) {
                        const float gt = bf_round(gate[p][e]);
                        hv[e] = bf_round(__fdividef(gt, 1.0f + __expf(-gt))) * bf_round((p & 1) ? hi[p >> 1][e] : lo[p >> 1][e]);
                    }
                    if (g < NB)
                        *reinterpret_cast<uint32_t*>(smem + SM_HF + (p * 4 + (warp >> 1)) * 256 + g * 64 + t * 16 + (warp & 1) * 8) =
                            pack_bf2(hv[0], hv[1]);
                }
                cons_bar();
            } else {
                mbar_wait(bar_full + B_ORDY, 0);
                const int cell = g * 320 + ((ps - 2) * 40 + warp) * 4 + t;
                float v[5][2];
#pragma unroll
                for (int p = 0; p < 5; p++) {
                    v[p][0] = (p & 1) ? hi[p >> 1][0] : lo[p >> 1][0];
                    v[p][1] = (p & 1) ? hi[p >> 1][1] : lo[p >> 1][1];
                }
                add_out<5>(g_acc + cell * P_CELL, reinterpret_cast<uint32_t*>(out) + cell, v, g < NB, g < NB, epoch);
            }
        }
        if (tid == 0) { TS(9); TS_DUMP(3, 10); }
    }
}

typedef CUresult (*EncodeFn)(CUtensorMap*, CUtensorMapDataType, cuuint32_t, void*, const cuuint64_t*, const cuuint64_t*,
                             const cuuint32_t*, const cuuint32_t*, CUtensorMapInterleave, CUtensorMapSwizzle,
                             CUtensorMapL2promotion, CUtensorMapFloatOOBfill);

void make_map(EncodeFn enc, CUtensorMap* m, const void* p, uint64_t rows, uint64_t cols, uint32_t inner, uint32_t parts,
              uint32_t box_rows) {
    const cuuint64_t dims[3] = {inner, cols / inner, rows};
    const cuuint64_t strides[2] = {inner * 2ull, cols * 2ull};
    const cuuint32_t box[3] = {inner, parts, box_rows};
    const cuuint32_t es[3] = {1, 1, 1};
    enc(m, CU_TENSOR_MAP_DATA_TYPE_BFLOAT16, 3, const_cast<void*>(p), dims, strides, box, es, CU_TENSOR_MAP_INTERLEAVE_NONE,
        inner == 64 ? CU_TENSOR_MAP_SWIZZLE_128B : CU_TENSOR_MAP_SWIZZLE_64B, CU_TENSOR_MAP_L2_PROMOTION_NONE,
        CU_TENSOR_MAP_FLOAT_OOB_FILL_NONE);
}

}

extern "C" void kernel_launch(void* const* d_in, const int* in_sizes, int n_in, void* d_out, int out_size) {
    (void)in_sizes; (void)n_in; (void)out_size;
    static EncodeFn enc = nullptr;
    if (!enc) {
        void* fn = nullptr;
        cudaDriverEntryPointQueryResult qr;
        cudaGetDriverEntryPoint("cuTensorMapEncodeTiled", &fn, cudaEnableDefault, &qr);
        enc = (EncodeFn)fn;
        cudaFuncSetAttribute(fused_decode_kernel, cudaFuncAttributeMaxDynamicSharedMemorySize, SM_TOTAL);
    }
    Maps maps;
    make_map(enc, &maps.k, d_in[1], (uint64_t)NB * NH * SK, DH, 64, 3, TK);
    make_map(enc, &maps.v, d_in[2], (uint64_t)NB * NH * SK, DH, 64, 3, TK);
    make_map(enc, &maps.wq, d_in[3], DM, NH * DH, 64, 3, 32);
    make_map(enc, &maps.wo, d_in[4], NH * DH, DM, 32, 5, 32);
    make_map(enc, &maps.w1, d_in[6], DM, FF, 64, 6, 16);
    make_map(enc, &maps.w3, d_in[7], DM, FF, 64, 6, 16);
    make_map(enc, &maps.w2, d_in[8], FF, DM, 64, 5, 16);
    fused_decode_kernel<<<NCTA, NTHR, SM_TOTAL>>>(maps, (const bf16*)d_in[0], (bf16*)d_out);
}
```

```cpp
#include <cuda_runtime.h>
#include <cuda.h>
#include <cuda_bf16.h>
#include <stdint.h>

namespace {

typedef __nv_bfloat16 bf16;

constexpr int NB = 4, DM = 640, NH = 32, DH = 192, SK = 8192, WIN = 2048, FF = 1536;

#define P_G 16
#define P_DEPTH 4
#define P_DEPTH_FFN 4
#define P_PFMAP 1
#define P_GAIN 8
#define P_BIAS 16
#define P_SLEEP 500
#define P_DMIN P_DEPTH
#define P_DMAX 6
#define P_EARLY 0
#define P_QDELAY 800
#define P_DWO 3
#define P_WOFROM 0
#define P_NS 16

constexpr int G = P_G;
constexpr int TK = 32;
constexpr int NT = WIN / TK / G;
constexpr int NK = NT * TK;
constexpr int NS = P_NS;
constexpr int SLOT = 12288;
constexpr int DEPTH = P_DEPTH;
constexpr int DEPTH0 = DEPTH < P_DEPTH_FFN ? DEPTH : P_DEPTH_FFN;
static_assert(DEPTH0 <= 5, "DEPTH0");
constexpr int NATT = 128, NFFN = 4, NCTA = NATT + NFFN;
constexpr int NCW = 8;
constexpr int NXW = 6;
constexpr int NTHR = (NCW + 1 + NXW + 1) * 32;
constexpr int NSRC = NH + NFFN;
constexpr int VS = 256;
constexpr int OPS = VS + 32;
static_assert(G >= 4 && G <= 32, "G");

constexpr int SM_RING = 0;
constexpr int SM_XF = SM_RING + NS * SLOT;
constexpr int SM_QS = SM_XF + 20 * 256;
constexpr int SM_SC = SM_QS + G * DH * 2;
constexpr int SM_PF = SM_SC + NK * 16;
constexpr int SM_OF = SM_PF + NT * 64;
constexpr int SM_LS = SM_OF + 6 * 256;
constexpr int SM_ATT_END = SM_LS + 32;
constexpr int SM_HF = SM_XF + 40 * 256;
constexpr int SM_FFN_END = SM_HF + 24 * 256;
constexpr int SM_BAR = SM_ATT_END > SM_FFN_END ? SM_ATT_END : SM_FFN_END;
constexpr int B_QRDY = 2 * NS * 8, B_ORDY = B_QRDY + G * 8, B_TRIG = B_ORDY + 8, NBAR = 2 * NS + G + 8;
constexpr int SM_PACE = SM_BAR + NBAR * 8;
constexpr int SM_TS = SM_PACE + 8;
constexpr int SM_TOTAL = SM_TS + 256;
static_assert(SM_TOTAL <= 232448, "smem");

constexpr int NKV = 2 * NT * G;
constexpr int ITEMS_ATT = 5 + NKV + 6;
constexpr int ITEMS_FFN = 80 + 48;

struct Maps { CUtensorMap k, v, wq, wo, w1, w3, w2; };

struct alignas(32) Sync { unsigned epoch, inits, prog[2]; };
__device__ Sync g_sync;
__device__ __align__(128) float g_qpart[NATT * NB * VS];
__device__ __align__(128) float g_opart[NATT * G * OPS];
__device__ float4 g_acc[NB * DM / 2];
#define TS(i)
#define TS_DUMP(lo, hi)

constexpr unsigned SPIN_LIMIT = 1u << 24;

__device__ __forceinline__ void mbar_init(uint32_t bar, int cnt) {
    asm volatile("mbarrier.init.shared::cta.b64 [%0], %1;" ::"r"(bar), "r"(cnt) : "memory");
}
__device__ __forceinline__ void mbar_expect_tx(uint32_t bar, uint32_t bytes) {
    asm volatile("mbarrier.arrive.expect_tx.shared::cta.b64 _, [%0], %1;" ::"r"(bar), "r"(bytes) : "memory");
}
__device__ __forceinline__ void mbar_arrive(uint32_t bar) {
    asm volatile("mbarrier.arrive.shared::cta.b64 _, [%0];" ::"r"(bar) : "memory");
}
__device__ __forceinline__ void mbar_wait(uint32_t bar, uint32_t parity) {
    asm volatile("{\n.reg .pred p, q;\n.reg .u32 n;\nmov.u32 n, 0;\n"
                 "W: mbarrier.try_wait.parity.shared::cta.b64 p, [%0], %1;\n"
                 "@p bra D;\nadd.u32 n, n, 1;\nsetp.lt.u32 q, n, %2;\n@q bra W;\ntrap;\nD:\n}"
                 ::"r"(bar), "r"(parity), "n"(SPIN_LIMIT) : "memory");
}
__device__ __forceinline__ void tma3d(uint32_t dst, const CUtensorMap* map, int c1, int c2, uint32_t bar, uint64_t pol) {
    asm volatile("cp.async.bulk.tensor.3d.shared::cluster.global.mbarrier::complete_tx::bytes.L2::cache_hint "
                 "[%0], [%1, {%2, %3, %4}], [%5], %6;"
                 ::"r"(dst), "l"(map), "r"(0), "r"(c1), "r"(c2), "r"(bar), "l"(pol) : "memory");
}
__device__ __forceinline__ void ldsm_x4(uint32_t addr, uint32_t (&r)[4]) {
    asm volatile("ldmatrix.sync.aligned.m8n8.x4.shared.b16 {%0,%1,%2,%3}, [%4];"
                 : "=r"(r[0]), "=r"(r[1]), "=r"(r[2]), "=r"(r[3]) : "r"(addr) : "memory");
}
__device__ __forceinline__ void ldsm_x4_t(uint32_t addr, uint32_t (&r)[4]) {
    asm volatile("ldmatrix.sync.aligned.m8n8.x4.trans.shared.b16 {%0,%1,%2,%3}, [%4];"
                 : "=r"(r[0]), "=r"(r[1]), "=r"(r[2]), "=r"(r[3]) : "r"(addr) : "memory");
}
__device__ __forceinline__ void lds128(uint32_t addr, uint32_t (&r)[4]) {
    asm volatile("ld.shared.v4.u32 {%0,%1,%2,%3}, [%4];"
                 : "=r"(r[0]), "=r"(r[1]), "=r"(r[2]), "=r"(r[3]) : "r"(addr) : "memory");
}
__device__ __forceinline__ void mma16816(float (&c)[4], const uint32_t (&a)[4], uint32_t b0, uint32_t b1) {
    asm volatile("mma.sync.aligned.m16n8k16.row.col.f32.bf16.bf16.f32 {%0,%1,%2,%3}, {%4,%5,%6,%7}, {%8,%9}, {%0,%1,%2,%3};"
                 : "+f"(c[0]), "+f"(c[1]), "+f"(c[2]), "+f"(c[3])
                 : "r"(a[0]), "r"(a[1]), "r"(a[2]), "r"(a[3]), "r"(b0), "r"(b1));
}
__device__ __forceinline__ void cons_bar() { asm volatile("bar.sync 1, 256;" ::: "memory"); }

__device__ __forceinline__ float bf_round(float v) { return __bfloat162float(__float2bfloat16_rn(v)); }
__device__ __forceinline__ uint32_t pack_bf2(float lo, float hi) {
    __nv_bfloat162 t = __floats2bfloat162_rn(lo, hi);
    return *reinterpret_cast<uint32_t*>(&t);
}
__device__ __forceinline__ float bf_lo(uint32_t u) { return __uint_as_float(u << 16); }
__device__ __forceinline__ float bf_hi(uint32_t u) { return __uint_as_float(u & 0xffff0000u); }
__device__ __forceinline__ float shx(float v, int o) { return __shfl_xor_sync(0xffffffffu, v, o); }

__device__ __forceinline__ uint32_t frag_off(uint32_t k) {
    return ((k >> 1) & 3) * 16 + ((k >> 3) & 1) * 8 + ((k >> 4) & 1) * 4 + (k & 1) * 2;
}

__device__ __forceinline__ void st_tag2(float* p, float a, float b, uint32_t tag) {
    asm volatile("{\n.reg .b64 w;\n.reg .b32 x;\nlop3.b32 x, %1, 0xfffffffe, %3, 0xea;\nmov.b64 w, {x, %2};\n"
                 "st.relaxed.gpu.global.b64 [%0], w;\n}"
                 ::"l"(p), "r"(__float_as_uint(a)), "r"(__float_as_uint(b)), "r"(tag) : "memory");
}
__device__ __forceinline__ void st_fill4(float* p, uint32_t v) {
    asm volatile("{\n.reg .b64 w;\nmov.b64 w, {%1, %1};\nst.relaxed.gpu.global.v2.b64 [%0], {w, w};\n}" ::"l"(p), "r"(v) : "memory");
}
__device__ __forceinline__ uint32_t bad4(const uint4& v, uint32_t tag) {
    uint32_t r;
    asm("lop3.b32 %0, %1, %2, %3, 0x7e;" : "=r"(r) : "r"(v.x), "r"(v.z), "r"(tag));
    return r;
}
__device__ __forceinline__ void ld_need2(uint2& v, const float* p, uint32_t bad) {
    asm volatile("{\n.reg .pred p;\n.reg .b64 w;\n.reg .b32 n;\nand.b32 n, %3, 1;\nsetp.ne.u32 p, n, 0;\nmov.b64 w, {%0,%1};\n"
                 "@p ld.relaxed.gpu.global.b64 w, [%2];\nmov.b64 {%0,%1}, w;\n}"
                 : "+r"(v.x), "+r"(v.y) : "l"(p), "r"(bad) : "memory");
}
__device__ __forceinline__ void ld_need4(uint4& v, const float* p, uint32_t bad) {
    asm volatile("{\n.reg .pred p;\n.reg .b64 w0, w1;\n.reg .b32 n;\nand.b32 n, %5, 1;\nsetp.ne.u32 p, n, 0;\n"
                 "mov.b64 w0, {%0,%1};\nmov.b64 w1, {%2,%3};\n"
                 "@p ld.relaxed.gpu.global.v2.b64 {w0, w1}, [%4];\nmov.b64 {%0,%1}, w0;\nmov.b64 {%2,%3}, w1;\n}"
                 : "+r"(v.x), "+r"(v.y), "+r"(v.z), "+r"(v.w) : "l"(p), "r"(bad) : "memory");
}
__device__ __forceinline__ uint32_t quad_reduce(float a0, float a1, float a2, float a3, int t) {
    const bool up = t & 2;
    float x = (up ? a2 : a0) + shx(up ? a0 : a2, 2), y = (up ? a3 : a1) + shx(up ? a1 : a3, 2);
    x += shx(x, 1);
    y += shx(y, 1);
    return pack_bf2(x, y);
}

template <int N>
__device__ __forceinline__ void add_out(const float4* acc, uint32_t* out, const float (&v)[N][2], uint32_t live,
                                        uint32_t live_last, uint32_t epoch) {
    float o[N][4];
#pragma unroll
    for (int i = 0; i < N; i++) {
        o[i][2] = 0.f;
        asm volatile("{\n.reg .pred p;\nsetp.ne.u32 p, %5, 0;\n"
                     "@p atom.relaxed.gpu.global.add.v4.f32 {%0,%1,%2,%3}, [%4], {%6,%7,%8,%9};\n}"
                     : "=f"(o[i][0]), "=f"(o[i][1]), "+f"(o[i][2]), "=f"(o[i][3])
                     : "l"(acc + i * 32), "r"(i < N - 1 ? live : live_last), "f"(v[i][0]), "f"(v[i][1]), "f"(1.0f), "f"(0.0f)
                     : "memory");
    }
#pragma unroll
    for (int i = 0; i < N; i++)
        asm volatile("{\n.reg .pred p;\nsetp.eq.f32 p, %2, %3;\n@p st.global.u32 [%0], %1;\n}"
                     ::"l"(out + i * 32), "r"(pack_bf2(o[i][0] + v[i][0], o[i][1] + v[i][1])), "f"(o[i][2]), "f"((float)(NSRC - 1))
                     : "memory");
    if (acc == g_acc && o[0][2] == (float)(NSRC - 1))
        asm volatile("st.relaxed.gpu.global.u32 [%0], %1;" ::"l"(&g_sync.epoch), "r"(epoch + 1u) : "memory");
}

__device__ __forceinline__ int pair_of(int sg, uint32_t j) { return sg * G + (j % (G / 4)) * 4 + j / (G / 4); }

struct Ring {
    uint32_t full, addr, phase, first_full;
    __device__ __forceinline__ void wait() const { mbar_wait(full, phase); }
    __device__ __forceinline__ void release(int lane) {
        __syncwarp();
        if (lane == 0) mbar_arrive(full + NS * 8);
        full += 8; addr += SLOT;
        if (full == first_full + NS * 8) { full = first_full; addr -= NS * SLOT; phase ^= 1; }
    }
};

__device__ __forceinline__ void pin3(uint32_t (&v)[3]) {
    asm volatile("" : "+r"(v[0]), "+r"(v[1]), "+r"(v[2]));
}
__device__ __forceinline__ void gemv_loop(Ring& ring, int n, uint32_t a_addr, uint32_t a_step, uint32_t (&off)[3],
                                          float (&lo)[3][4], float (&hi)[3][4], int lane) {
    pin3(off);
#pragma unroll
    for (int s = 0; s < 3; s++)
#pragma unroll
        for (int e = 0; e < 4; e++) { lo[s][e] = 0.f; hi[s][e] = 0.f; }
#pragma unroll 1
    for (int it = 0; it < n; it++) {
        uint32_t a[4], b[3][4];
        lds128(a_addr, a);
        a_addr += a_step;
        ring.wait();
#pragma unroll
        for (int s = 0; s < 3; s++) ldsm_x4_t(ring.addr + off[s], b[s]);
#pragma unroll
        for (int s = 0; s < 3; s++) { mma16816(lo[s], a, b[s][0], b[s][1]); mma16816(hi[s], a, b[s][2], b[s][3]); }
        ring.release(lane);
    }
}

__global__ void __launch_bounds__(NTHR, 1)
fused_decode_kernel(const __grid_constant__ Maps maps, const bf16* __restrict__ x, bf16* __restrict__ out) {
    extern __shared__ __align__(1024) unsigned char smem[];
    const uint32_t sb = (uint32_t)__cvta_generic_to_shared(smem);
    const int tid = threadIdx.x, warp = tid >> 5, lane = tid & 31;
    const int cta = blockIdx.x;
    const bool is_att = cta < NATT;
    const int h = cta >> 2, qd = cta & 3;
    const int sg = cta / G, r = cta % G;
    const uint32_t bar_full = sb + SM_BAR;

    uint64_t pol;
    asm volatile("createpolicy.fractional.L2::evict_first.b64 %0, 1.0;" : "=l"(pol));
    if (tid == NCW * 32) {
        TS(0);
        const CUtensorMap* map = is_att ? &maps.wq : &maps.w1;
        const int c1 = is_att ? h * 3 : qd * 6, c2 = is_att ? qd * 160 : 0, step = is_att ? 32 : 16;
#pragma unroll 1
        for (int i = 0; i < DEPTH0; i++) {
            mbar_init(bar_full + i * 8, 1);
            mbar_expect_tx(bar_full + i * 8, 12288);
            tma3d(sb + SM_RING + i * SLOT, map, c1, c2 + i * step, bar_full + i * 8, pol);
        }
        TS(1);
    }
    if (warp == NCW) {
        volatile int* pace = reinterpret_cast<volatile int*>(smem + SM_PACE);
        if (lane == 0) {
            pace[0] = 0;
            pace[1] = is_att ? DEPTH : P_DEPTH_FFN;
#pragma unroll
            for (int i = DEPTH0; i < NBAR; i++)
                mbar_init(bar_full + i * 8, i < NS ? 1 : i < 2 * NS ? NCW : i < 2 * NS + G ? NXW : i == 2 * NS + G && is_att ? 1 + NB * NXW : 1);
            asm volatile("fence.mbarrier_init.release.cluster;" ::: "memory");
        }
        __syncwarp();
        asm volatile("bar.arrive 2, %0;" ::"n"(NTHR) : "memory");
        if (lane == 0) {
            const int n_items = is_att ? ITEMS_ATT : ITEMS_FFN;

            asm volatile("prefetch.tensormap [%0];" ::"l"(is_att ? &maps.k : &maps.w3) : "memory");
            asm volatile("prefetch.tensormap [%0];" ::"l"(is_att ? &maps.v : &maps.w2) : "memory");
            asm volatile("prefetch.tensormap [%0];" ::"l"(&maps.wo) : "memory");
#pragma unroll 1
            for (int i = DEPTH0; i < n_items; i++) {
                const CUtensorMap* map;
                int c1, c2;
                uint32_t bytes = 12288;
                if (is_att) {
                    const uint32_t u = i - 5;
                    if (u < NKV) {
                        const int pair = pair_of(sg, u / (2 * NT));
                        map = (u & NT) ? &maps.v : &maps.k;
                        c1 = 0;
                        c2 = ((pair & 3) * NH + (pair >> 2)) * SK + (SK - WIN) + ((u % NT) * G + r) * TK;
                    } else if (i < 5) {
                        map = &maps.wq; c1 = h * 3; c2 = qd * 160 + i * 32;
                    } else {
                        map = &maps.wo; c1 = qd * 5; c2 = h * DH + (u - NKV) * 32; bytes = 10240;
                    }
                } else {
                    if (i < 80) {
                        map = i < 40 ? &maps.w1 : &maps.w3; c1 = qd * 6; c2 = (i < 40 ? i : i - 40) * 16;
                    } else {
                        map = &maps.w2; c1 = i < 104 ? 0 : 5; c2 = qd * 384 + (i < 104 ? i - 80 : i - 104) * 16; bytes = 10240;
                    }
                }
                const int depth = (is_att && i >= 5 + NKV + P_WOFROM) ? P_DWO : pace[1];
                const uint32_t slot = (uint32_t)i % NS, landed = i - depth;
                if (i >= NS) mbar_wait(bar_full + (NS + slot) * 8, ((uint32_t)i / NS - 1) & 1);
                mbar_expect_tx(bar_full + slot * 8, bytes);
                uint32_t dst = sb + SM_RING + slot * SLOT, fb = bar_full + slot * 8;
                asm volatile("" : "+r"(dst), "+r"(fb), "+l"(map), "+r"(c1), "+r"(c2));
                if (i >= depth) mbar_wait(bar_full + (landed % NS) * 8, (landed / NS) & 1);
                tma3d(dst, map, c1, c2, fb, pol);
                pace[0] = landed + 1;
            }
        }
        return;
    }

    const int g = lane >> 2, t = lane & 3;
    uint32_t epoch;
    asm volatile("ld.relaxed.gpu.global.u32 %0, [%1];" : "=r"(epoch) : "l"(&g_sync.epoch) : "memory");

    if (warp == NCW + 1 + NXW) {
        asm volatile("bar.sync 2, %0;" ::"n"(NTHR) : "memory");
        if (lane == 0 && is_att && P_GAIN) {
            volatile int* pace = reinterpret_cast<volatile int*>(smem + SM_PACE);
            if (cta == 0) asm volatile("st.relaxed.gpu.global.u32 [%0], %1;" ::"l"(&g_sync.prog[epoch & 1u]), "r"(0u) : "memory");
            unsigned* prog = &g_sync.prog[~epoch & 1u];
            int reported = 0;
#pragma unroll 1
            for (int it = 0; it < 4096; it++) {
                const int landed = pace[0];
                if (landed >= NKV + 5 - P_DMAX) break;
                int sum;
                asm volatile("atom.relaxed.gpu.global.add.u32 %0, [%1], %2;" : "=r"(sum) : "l"(prog), "r"(landed - reported) : "memory");
                reported = landed;
                const int lag16 = sum / (NATT / 16) - landed * 16 + P_BIAS;
                pace[1] = min(max(DEPTH + ((lag16 * P_GAIN + 128) >> 8), P_DMIN), P_DMAX);
                __nanosleep(P_SLEEP);
            }
        }
        return;
    }
    if (warp > NCW) {
        uint32_t tag = (epoch + 1u) & 1u;
        asm volatile("" : "+r"(tag));
        const int e = tid - (NCW + 1) * 32;
        if (is_att) {
            st_fill4(g_qpart + (cta * NB + e / 48) * VS + (e % 48) / 6 * 32 + (e % 6) * 4, tag ^ 1u);
            if (e < 50) {
#pragma unroll 1
                for (int j = 0; j < G; j++) st_fill4(g_opart + ((sg * G + j) * G + r) * OPS + e / 6 * 32 + (e % 6) * 4, tag ^ 1u);
            }
        } else {
#pragma unroll 1
            for (int c = qd * 320 + e; c < qd * 320 + 320; c += NXW * 32) {
                const uint32_t xw = __ldg(reinterpret_cast<const uint32_t*>(x) + c);
                asm volatile("st.relaxed.gpu.global.v4.f32 [%0], {%1,%2,%3,%3};"
                             ::"l"(g_acc + c), "f"(bf_lo(xw)), "f"(bf_hi(xw)), "f"(0.f) : "memory");
            }
            __syncwarp();
            if (lane == 0) asm volatile("red.release.gpu.global.add.u32 [%0], 1;" ::"l"(&g_sync.inits) : "memory");
        }
        asm volatile("bar.sync 2, %0;" ::"n"(NTHR) : "memory");
        const uint32_t xw = (e >> 2) / 6, xr = (e >> 2) % 6, voff = xw * 32 + xr * 4;
        const uint32_t col = (xr >> 1) * 64 + xw * 8 + (xr & 1) * 4 + (t & 2);
        if (is_att) {
            mbar_wait(bar_full + B_TRIG + 40, 0);
            if (e == 0) TS(10);
            __nanosleep(P_QDELAY);
#pragma unroll 1
            for (int j = 0; j < G; j++) {
                const int pair = pair_of(sg, j);
                const float* src = g_qpart + (((pair >> 2) * 4 + t) * NB + (pair & 3)) * VS + voff;
                uint4 v = make_uint4(~tag, ~tag, ~tag, ~tag);
                unsigned spin = 0;
                while (bad4(v, tag) & 1u) {
                    ld_need4(v, src, 1u);
                    if (++spin > SPIN_LIMIT) __trap();
                }
                const uint32_t qq = quad_reduce(__uint_as_float(v.x), __uint_as_float(v.y), __uint_as_float(v.z), __uint_as_float(v.w), t);
                if (!(t & 1)) *reinterpret_cast<uint32_t*>(smem + SM_QS + (j * DH + col) * 2) = qq;
                __syncwarp();
                if (lane == 0) mbar_arrive(bar_full + B_QRDY + j * 8);
                if (e == 0 && j == 0) TS(12);
            }
        }
        if (e == 0) {
            unsigned spin = 0, n;
            do {
                asm volatile("ld.acquire.gpu.global.u32 %0, [%1];" : "=r"(n) : "l"(&g_sync.inits) : "memory");
                if (++spin > SPIN_LIMIT) __trap();
            } while (n != (epoch + 1u) * (NFFN * NXW));
            mbar_arrive(bar_full + B_ORDY);
        }
#pragma unroll 1
        for (int b = 0; b < (is_att ? NB : 0); b++) {
            constexpr int KP = G / 4;
            const float* src = g_opart + (h * NB + b) * (G * OPS);
            const float* mlp = src + (lane % G) * OPS + VS;
            src += t * KP * OPS + voff;
            const bool last = h * NB + b == sg * G + G - 1;
            uint32_t of_addr = sb + SM_OF + (col >> 5) * 256 + b * 64 + frag_off(col & 31);
            uint4 v[KP];
            uint2 ml = make_uint2(0u, 0u);
            uint32_t bad[KP];
            mbar_wait(bar_full + B_TRIG + b * 8, 0);
            ld_need2(ml, mlp, 1u);
#pragma unroll
            for (int k = 0; k < KP; k++) { v[k] = make_uint4(0u, 0u, 0u, 0u); ld_need4(v[k], src + k * OPS, 1u); }
            if (last) mbar_wait(bar_full + B_TRIG + 32, 0);
            unsigned spin = 0;
            while ((ml.x ^ tag) & 1u) {
                ld_need2(ml, mlp, 1u);
                if (++spin > SPIN_LIMIT) __trap();
            }
            const float mk = __uint_as_float(ml.x & ~1u);
            float M = mk;
#pragma unroll
            for (int o = G / 2; o; o >>= 1) M = fmaxf(M, shx(M, o));
            float w = __expf(mk - M);
            float L = w * __uint_as_float(ml.y);
#pragma unroll
            for (int o = G / 2; o; o >>= 1) L += shx(L, o);
            w = __fdividef(w, L);
            float wk[KP];
#pragma unroll
            for (int k = 0; k < KP; k++) { wk[k] = __shfl_sync(0xffffffffu, w, t * KP + k); bad[k] = bad4(v[k], tag); }
            if (e == 0 && b == 3) TS(11);
            uint32_t ordy = bar_full + B_ORDY;
            asm volatile("" : "+r"(of_addr), "+l"(src), "+r"(ordy));
            if (last) mbar_wait(bar_full + B_TRIG + 48, 0);
            while (true) {
                uint32_t any = 0;
                float o0 = 0.f, o1 = 0.f, o2 = 0.f, o3 = 0.f;
#pragma unroll
                for (int k = 0; k < KP; k++) ld_need4(v[k], src + k * OPS, bad[k]);
#pragma unroll
                for (int k = 0; k < KP; k++) {
                    bad[k] = bad4(v[k], tag);
                    asm("or.b32 %0, %0, %1;" : "+r"(any) : "r"(bad[k]));
                    o0 += wk[k] * __uint_as_float(v[k].x);
                    o1 += wk[k] * __uint_as_float(v[k].y);
                    o2 += wk[k] * __uint_as_float(v[k].z);
                    o3 += wk[k] * __uint_as_float(v[k].w);
                }
                const uint32_t oo = quad_reduce(o0, o1, o2, o3, t);
                asm volatile("st.shared.u32 [%0], %1;" ::"r"(of_addr), "r"(oo) : "memory");
                if (!__any_sync(0xffffffffu, any & 1u)) break;
                if (++spin > SPIN_LIMIT) __trap();
            }
            __syncwarp();
            if (lane == 0) mbar_arrive(ordy);
        }
        return;
    }

    if (warp < NB) {
        uint2 raw[5];
#pragma unroll
        for (int i = 0; i < 5; i++) raw[i] = __ldg(reinterpret_cast<const uint2*>(x + warp * DM) + i * 32 + lane);
        float s = 0.f;
#pragma unroll
        for (int i = 0; i < 5; i++) s += (bf_lo(raw[i].x) + bf_hi(raw[i].x)) + (bf_lo(raw[i].y) + bf_hi(raw[i].y));
#pragma unroll
        for (int o = 16; o; o >>= 1) s += shx(s, o);
        const float mean = s * (1.0f / DM);
        float q2 = 0.f;
#pragma unroll
        for (int i = 0; i < 5; i++) {
            const float d0 = bf_lo(raw[i].x) - mean, d1 = bf_hi(raw[i].x) - mean;
            const float d2 = bf_lo(raw[i].y) - mean, d3 = bf_hi(raw[i].y) - mean;
            q2 += (d0 * d0 + d1 * d1) + (d2 * d2 + d3 * d3);
        }
#pragma unroll
        for (int o = 16; o; o >>= 1) q2 += shx(q2, o);
        const float mb = bf_round(mean);
        const float rs = __frcp_rn(bf_round(__fsqrt_rn(bf_round(bf_round(q2 * (1.0f / DM)) + 1e-5f))));
        const uint32_t k = (lane * 4) & 31;
        unsigned char* dst = smem + SM_XF + warp * 64 +
            (is_att ? (lane >> 3) * 256 + frag_off(k) : (lane >> 2) * 256 + frag_off(k & 15));
        const uint32_t step = is_att ? 1024 : 2048;
#pragma unroll
        for (int i = 0; i < 5; i++) {
            const uint32_t d0 = pack_bf2(bf_lo(raw[i].x) - mb, bf_hi(raw[i].x) - mb);
            const uint32_t d1 = pack_bf2(bf_lo(raw[i].y) - mb, bf_hi(raw[i].y) - mb);
            *reinterpret_cast<uint32_t*>(dst + i * step) = pack_bf2(bf_lo(d0) * rs, bf_hi(d0) * rs);
            *reinterpret_cast<uint32_t*>(dst + i * step + 16) = pack_bf2(bf_lo(d1) * rs, bf_hi(d1) * rs);
        }
    }
    asm volatile("bar.sync 2, %0;" ::"n"(NTHR) : "memory");
    uint32_t tag = (epoch + 1u) & 1u;
    asm volatile("" : "+r"(tag));
    if (tid == 0) TS(3);

    Ring ring{bar_full, sb + SM_RING, 0u, bar_full};
    float lo[3][4], hi[3][4];
    uint32_t off[3];
    const uint32_t a_lane = (g & 3) * 64 + t * 16;

    if (is_att) {
        float* sc = reinterpret_cast<float*>(smem + SM_SC);
        float* lsum = reinterpret_cast<float*>(smem + SM_LS);
#pragma unroll 1
        for (int j = -1; j < G; j++) {
            const bool kv = j >= 0;
            const int pair = pair_of(sg, j), prev = pair_of(sg, j - 1);
            const bool trig_last = tid == 0 && j == G - 1 && (pair >> 2) == h;
            if (trig_last) mbar_arrive(bar_full + B_TRIG + 24);
            if (kv) {
                const int kb = warp & 1, dq = warp >> 1;
                const uint32_t key = kb * 16 + (lane & 15);
                uint32_t qf[3][2];
                mbar_wait(bar_full + B_QRDY + j * 8, 0);
                if (j == 0 && tid == 0) TS(6);
                const uint32_t* qw = reinterpret_cast<const uint32_t*>(smem + SM_QS) + j * (DH / 2) + dq * 8 + t;
#pragma unroll
                for (int s = 0; s < 3; s++) {
                    qf[s][0] = qw[s * 32];
                    qf[s][1] = qw[s * 32 + 4];
                    off[s] = key * 384 + s * 128 + (((2 * dq + (lane >> 4)) ^ ((3 * key + s) & 7)) << 4);
                }
                pin3(off);
                float* d = sc + (kb * 16 + g) * 4 + dq;
#pragma unroll 1
                for (int tt = 0; tt < NT; tt++) {
                    uint32_t a[3][4];
                    ring.wait();
#pragma unroll
                    for (int s = 0; s < 3; s++) ldsm_x4(ring.addr + off[s], a[s]);
                    float c[4] = {0.f, 0.f, 0.f, 0.f};
#pragma unroll
                    for (int s = 0; s < 3; s++) mma16816(c, a[s], qf[s][0], qf[s][1]);
                    ring.release(lane);
                    if (t == 0) { d[0] = c[0]; d[32] = c[2]; }
                    d += TK * 4;
                }
            }
            const bool trig = tid == 0 && j >= 1 && (prev >> 2) == h;
            if (trig && j == G - 1) mbar_arrive(bar_full + B_TRIG + (prev & 3) * 8);
            uint32_t a_addr, a_step, rows;
            int n;
            float* dst;
            if (kv) {
                cons_bar();
                float m = -INFINITY;
#pragma unroll 2
                for (int k = lane; k < NK; k += 32) {
                    const float4 s4 = reinterpret_cast<const float4*>(sc)[k];
                    m = fmaxf(m, (s4.x + s4.y) + (s4.z + s4.w));
                }
#pragma unroll
                for (int o = 16; o; o >>= 1) m = fmaxf(m, shx(m, o));
                m = bf_round(bf_round(m) * 0.07216878364870323f);
                float l = 0.f;
#pragma unroll 1
                for (int k = tid; k < NK; k += NCW * 32) {
                    const float4 s4 = reinterpret_cast<const float4*>(sc)[k];
                    const float s = bf_round(bf_round((s4.x + s4.y) + (s4.z + s4.w)) * 0.07216878364870323f);
                    const float p = __expf(s - m);
                    l += p;
                    *reinterpret_cast<bf16*>(smem + SM_PF + (k >> 5) * 64 + frag_off(lane)) = __float2bfloat16_rn(p);
                }
#pragma unroll
                for (int o = 16; o; o >>= 1) l += shx(l, o);
                if (lane == 0) lsum[warp] = l;
                cons_bar();
                dst = g_opart + (pair * G + r) * OPS;
                if (tid < 4) {
                    const float4 l0 = reinterpret_cast<const float4*>(lsum)[0], l1 = reinterpret_cast<const float4*>(lsum)[1];
                    st_tag2(dst + VS + tid * 2, m, ((l0.x + l0.y) + (l0.z + l0.w)) + ((l1.x + l1.y) + (l1.z + l1.w)), tag);
                }
                if (trig_last) mbar_arrive(bar_full + B_TRIG + 32);
                if (trig_last && P_EARLY) mbar_arrive(bar_full + B_TRIG + 48);
                dst += warp * 32;
                a_addr = sb + SM_PF + t * 16; a_step = 64; n = NT; rows = 1;
            } else {
                dst = g_qpart + (cta * NB + g) * VS + warp * 32;
                a_addr = sb + SM_XF + qd * 5 * 256 + a_lane; a_step = 256; n = 5; rows = NB;
            }
#pragma unroll
            for (int s = 0; s < 3; s++) off[s] = lane * 384 + s * 128 + ((warp ^ ((3 * lane + s) & 7)) << 4);
            gemv_loop(ring, n, a_addr, a_step, off, lo, hi, lane);
            if (j == G - 1 ? trig_last && !P_EARLY : trig) mbar_arrive(bar_full + B_TRIG + (j == G - 1 ? 48 : (prev & 3) * 8));
            if (j == G - 1 && tid == 0) TS(5);
            if (g < rows) {
#pragma unroll
                for (int s = 0; s < 3; s++) st_tag2(dst + 2 * t + s * 8, lo[s][0] + hi[s][2], lo[s][1] + hi[s][3], tag);
            }
            if (j >= 0 && j < G - 1) continue;
            if (tid == 0 && j < 0) { mbar_arrive(bar_full + B_TRIG + 40); TS(4); }

#pragma unroll 1
            for (int pass = 0; pass <= (int)kv; pass++) {
                constexpr int I0 = 5 + NKV;
                uint32_t b[6][3][4];
#pragma unroll
                for (int s = 0; s < 3; s++) {
                    const uint32_t w64 = lane * 320 + (warp + 8 * s) * 16;
                    off[s] = sb + SM_RING + (w64 ^ (((w64 >> 7) & 3) << 4));
#pragma unroll
                    for (int e = 0; e < 4; e++) { lo[s][e] = 0.f; hi[s][e] = 0.f; }
                }
                const int cell = g * 320 + (qd * 20 + warp) * 4 + t;
                const float4* accp = g_acc + cell;
                uint32_t* outp = reinterpret_cast<uint32_t*>(out) + cell;
                uint32_t live = pass && g < NB, live3 = live && warp < 4, a_addr = sb + SM_OF + a_lane;
                const uint32_t done = bar_full + B_TRIG + 40;
                uint32_t ordy = pass ? bar_full + B_ORDY : done, last = pass ? bar_full + ((I0 + 5) % NS) * 8 : done;
                pin3(off);
                asm volatile("" : "+l"(accp), "+l"(outp), "+r"(live), "+r"(live3), "+r"(a_addr), "+r"(ordy), "+r"(last));
#pragma unroll
                for (int i = 0; i < 6; i++) {
                    if (i == 5) {
                        mbar_wait(ordy, 0);
                        if (pass && tid == 0) TS(7);
#pragma unroll
                        for (int k = 0; k < 5; k++) {
                            uint32_t a[4];
                            lds128(a_addr + k * 256, a);
#pragma unroll
                            for (int s = 0; s < 3; s++)
                                if (s < 2 || warp < 4) { mma16816(lo[s], a, b[k][s][0], b[k][s][1]); mma16816(hi[s], a, b[k][s][2], b[k][s][3]); }
                        }
                    }
                    mbar_wait(i == 5 ? last : pass ? bar_full + ((I0 + i) % NS) * 8 : done, pass ? ((I0 + i) / NS) & 1 : 0);
#pragma unroll
                    for (int s = 0; s < 3; s++) ldsm_x4_t(off[s] + ((I0 + i) % NS) * SLOT, b[i][s]);
                }
                uint32_t a[4];
                lds128(a_addr + 5 * 256, a);
#pragma unroll
                for (int s = 0; s < 3; s++) { mma16816(lo[s], a, b[5][s][0], b[5][s][1]); mma16816(hi[s], a, b[5][s][2], b[5][s][3]); }
                if (pass && tid == 0) TS(8);
                float v[3][2];
#pragma unroll
                for (int s = 0; s < 3; s++) { v[s][0] = lo[s][0] + hi[s][2]; v[s][1] = lo[s][1] + hi[s][3]; }
                add_out<3>(accp, outp, v, live, live3, epoch);
            }
        }
        if (tid == 0) { TS(9); TS_DUMP(3, 32); }
    } else {
        float gate[6][2];
#pragma unroll 1
        for (int ps = 0; ps < 4; ps++) {
            const uint32_t row = lane & 15, parts = ps < 2 ? 6 : 5;
#pragma unroll
            for (int s = 0; s < 3; s++) {
                const uint32_t r128 = row * parts + min(2 * s + (lane >> 4), parts - 1);
                off[s] = r128 * 128 + ((warp ^ (r128 & 7)) << 4);
            }
            gemv_loop(ring, ps < 2 ? 40 : 24, sb + (ps < 2 ? SM_XF : SM_HF) + a_lane, 256, off, lo, hi, lane);
            if (ps == 0) {
#pragma unroll
                for (int s = 0; s < 3; s++) {
                    gate[2 * s][0] = lo[s][0]; gate[2 * s][1] = lo[s][1];
                    gate[2 * s + 1][0] = hi[s][0]; gate[2 * s + 1][1] = hi[s][1];
                }
            } else if (ps == 1) {
#pragma unroll
                for (int p = 0; p < 6; p++) {
                    float hv[2];
#pragma unroll
                    for (int e = 0; e < 2; e++) {
                        const float gt = bf_round(gate[p][e]);
                        hv[e] = bf_round(__fdividef(gt, 1.0f + __expf(-gt))) * bf_round((p & 1) ? hi[p >> 1][e] : lo[p >> 1][e]);
                    }
                    if (g < NB)
                        *reinterpret_cast<uint32_t*>(smem + SM_HF + (p * 4 + (warp >> 1)) * 256 + g * 64 + t * 16 + (warp & 1) * 8) =
                            pack_bf2(hv[0], hv[1]);
                }
                cons_bar();
            } else {
                mbar_wait(bar_full + B_ORDY, 0);
                const int cell = g * 320 + ((ps - 2) * 40 + warp) * 4 + t;
                float v[5][2];
#pragma unroll
                for (int p = 0; p < 5; p++) {
                    v[p][0] = (p & 1) ? hi[p >> 1][0] : lo[p >> 1][0];
                    v[p][1] = (p & 1) ? hi[p >> 1][1] : lo[p >> 1][1];
                }
                add_out<5>(g_acc + cell, reinterpret_cast<uint32_t*>(out) + cell, v, g < NB, g < NB, epoch);
            }
        }
        if (tid == 0) { TS(9); TS_DUMP(3, 10); }
    }
}

typedef CUresult (*EncodeFn)(CUtensorMap*, CUtensorMapDataType, cuuint32_t, void*, const cuuint64_t*, const cuuint64_t*,
                             const cuuint32_t*, const cuuint32_t*, CUtensorMapInterleave, CUtensorMapSwizzle,
                             CUtensorMapL2promotion, CUtensorMapFloatOOBfill);

void make_map(EncodeFn enc, CUtensorMap* m, const void* p, uint64_t rows, uint64_t cols, uint32_t inner, uint32_t parts,
              uint32_t box_rows) {
    const cuuint64_t dims[3] = {inner, cols / inner, rows};
    const cuuint64_t strides[2] = {inner * 2ull, cols * 2ull};
    const cuuint32_t box[3] = {inner, parts, box_rows};
    const cuuint32_t es[3] = {1, 1, 1};
    enc(m, CU_TENSOR_MAP_DATA_TYPE_BFLOAT16, 3, const_cast<void*>(p), dims, strides, box, es, CU_TENSOR_MAP_INTERLEAVE_NONE,
        inner == 64 ? CU_TENSOR_MAP_SWIZZLE_128B : CU_TENSOR_MAP_SWIZZLE_64B, CU_TENSOR_MAP_L2_PROMOTION_NONE,
        CU_TENSOR_MAP_FLOAT_OOB_FILL_NONE);
}

}

extern "C" void kernel_launch(void* const* d_in, const int* in_sizes, int n_in, void* d_out, int out_size) {
    (void)in_sizes; (void)n_in; (void)out_size;
    static EncodeFn enc = nullptr;
    if (!enc) {
        void* fn = nullptr;
        cudaDriverEntryPointQueryResult qr;
        cudaGetDriverEntryPoint("cuTensorMapEncodeTiled", &fn, cudaEnableDefault, &qr);
        enc = (EncodeFn)fn;
        cudaFuncSetAttribute(fused_decode_kernel, cudaFuncAttributeMaxDynamicSharedMemorySize, SM_TOTAL);
    }
    Maps maps;
    make_map(enc, &maps.k, d_in[1], (uint64_t)NB * NH * SK, DH, 64, 3, TK);
    make_map(enc, &maps.v, d_in[2], (uint64_t)NB * NH * SK, DH, 64, 3, TK);
    make_map(enc, &maps.wq, d_in[3], DM, NH * DH, 64, 3, 32);
    make_map(enc, &maps.wo, d_in[4], NH * DH, DM, 32, 5, 32);
    make_map(enc, &maps.w1, d_in[6], DM, FF, 64, 6, 16);
    make_map(enc, &maps.w3, d_in[7], DM, FF, 64, 6, 16);
    make_map(enc, &maps.w2, d_in[8], FF, DM, 64, 5, 16);
    fused_decode_kernel<<<NCTA, NTHR, SM_TOTAL>>>(maps, (const bf16*)d_in[0], (bf16*)d_out);
}
```

```cpp
#include <cuda_runtime.h>
#include <cuda.h>
#include <cuda_bf16.h>
#include <stdint.h>

namespace {

typedef __nv_bfloat16 bf16;

constexpr int NB = 4, DM = 640, NH = 32, DH = 192, SK = 8192, WIN = 2048, FF = 1536;

#define P_G 16
#define P_DEPTH 4
#define P_DEPTH_FFN 4
#define P_PFMAP 1
#define P_GAIN 8
#define P_BIAS 16
#define P_SLEEP 500
#define P_DMIN P_DEPTH
#define P_DMAX 6
#define P_EARLY 0
#define P_QDELAY 800
#define P_DWO 0x333333
#define P_WOPACE 1
#define P_PRE 3
#define P_PF 0
#define P_DINIT DEPTH
#define P_NS 16

constexpr int G = P_G;
constexpr int TK = 32;
constexpr int NT = WIN / TK / G;
constexpr int NS = P_NS;
constexpr int SLOT = 12288;
constexpr int DEPTH = P_DEPTH;
#define P_D0 5
constexpr int DEPTH0 = P_D0;
static_assert(DEPTH0 <= 5, "DEPTH0");
constexpr int NATT = 128, NFFN = 4, NCTA = NATT + NFFN;
constexpr int NCW = 8;
constexpr int NXW = 6;
constexpr int NTHR = (NCW + 1 + NXW + 1) * 32;
constexpr int NSRC = NH + NFFN;
constexpr int VS = 256;
constexpr int OPS = VS + 32;
static_assert(G >= 4 && G <= 16, "G");

constexpr int SM_RING = 0;
constexpr int SM_XF = SM_RING + NS * SLOT;
constexpr int SM_QS = SM_XF + 20 * 256;
constexpr int SM_PF = SM_QS + G * DH * 2;
constexpr int SM_OF = SM_PF + NT * 64;
constexpr int SM_LS = SM_OF + 6 * 256;
constexpr int SM_ATT_END = SM_LS + 64;
constexpr int SM_HF = SM_XF + 40 * 256;
constexpr int SM_FFN_END = SM_HF + 24 * 256;
constexpr int SM_BAR = SM_ATT_END > SM_FFN_END ? SM_ATT_END : SM_FFN_END;
constexpr int B_QRDY = 2 * NS * 8, B_ORDY = B_QRDY + G * 8, B_TRIG = B_ORDY + 8, NBAR = 2 * NS + G + 8;
constexpr int SM_PACE = SM_BAR + NBAR * 8;
constexpr int SM_TS = SM_PACE + 8;
constexpr int SM_TOTAL = SM_TS + 256;
static_assert(SM_TOTAL <= 232448, "smem");

constexpr int NKV = 2 * NT * G;
constexpr int ITEMS_ATT = 5 + NKV + 6;
constexpr int ITEMS_FFN = 80 + 48;

struct Maps { CUtensorMap k, v, wq, wo, w1, w3, w2; };

struct alignas(32) Sync { unsigned epoch, inits, prog[2]; };
__device__ Sync g_sync;
__device__ __align__(128) float g_qpart[NATT * NB * VS];
__device__ __align__(128) float g_opart[NATT * G * OPS];
__device__ float4 g_acc[NB * DM / 2];
#define TS(i)
#define TS_DUMP(lo, hi)

constexpr unsigned SPIN_LIMIT = 1u << 24;

__device__ __forceinline__ void mbar_init(uint32_t bar, int cnt) {
    asm volatile("mbarrier.init.shared::cta.b64 [%0], %1;" ::"r"(bar), "r"(cnt) : "memory");
}
__device__ __forceinline__ void mbar_expect_tx(uint32_t bar, uint32_t bytes) {
    asm volatile("mbarrier.arrive.expect_tx.shared::cta.b64 _, [%0], %1;" ::"r"(bar), "r"(bytes) : "memory");
}
__device__ __forceinline__ void mbar_arrive(uint32_t bar) {
    asm volatile("mbarrier.arrive.shared::cta.b64 _, [%0];" ::"r"(bar) : "memory");
}
__device__ __forceinline__ void mbar_wait(uint32_t bar, uint32_t parity) {
    asm volatile("{\n.reg .pred p, q;\n.reg .u32 n;\nmov.u32 n, 0;\n"
                 "W: mbarrier.try_wait.parity.shared::cta.b64 p, [%0], %1;\n"
                 "@p bra D;\nadd.u32 n, n, 1;\nsetp.lt.u32 q, n, %2;\n@q bra W;\ntrap;\nD:\n}"
                 ::"r"(bar), "r"(parity), "n"(SPIN_LIMIT) : "memory");
}
__device__ __forceinline__ void tma3d(uint32_t dst, const CUtensorMap* map, int c1, int c2, uint32_t bar, uint64_t pol) {
    asm volatile("cp.async.bulk.tensor.3d.shared::cluster.global.mbarrier::complete_tx::bytes.L2::cache_hint "
                 "[%0], [%1, {%2, %3, %4}], [%5], %6;"
                 ::"r"(dst), "l"(map), "r"(0), "r"(c1), "r"(c2), "r"(bar), "l"(pol) : "memory");
}
__device__ __forceinline__ void ldsm_x4(uint32_t addr, uint32_t (&r)[4]) {
    asm volatile("ldmatrix.sync.aligned.m8n8.x4.shared.b16 {%0,%1,%2,%3}, [%4];"
                 : "=r"(r[0]), "=r"(r[1]), "=r"(r[2]), "=r"(r[3]) : "r"(addr) : "memory");
}
__device__ __forceinline__ void ldsm_x4_t(uint32_t addr, uint32_t (&r)[4]) {
    asm volatile("ldmatrix.sync.aligned.m8n8.x4.trans.shared.b16 {%0,%1,%2,%3}, [%4];"
                 : "=r"(r[0]), "=r"(r[1]), "=r"(r[2]), "=r"(r[3]) : "r"(addr) : "memory");
}
__device__ __forceinline__ void lds128(uint32_t addr, uint32_t (&r)[4]) {
    asm volatile("ld.shared.v4.u32 {%0,%1,%2,%3}, [%4];"
                 : "=r"(r[0]), "=r"(r[1]), "=r"(r[2]), "=r"(r[3]) : "r"(addr) : "memory");
}
__device__ __forceinline__ void mma16816(float (&c)[4], const uint32_t (&a)[4], uint32_t b0, uint32_t b1) {
    asm volatile("mma.sync.aligned.m16n8k16.row.col.f32.bf16.bf16.f32 {%0,%1,%2,%3}, {%4,%5,%6,%7}, {%8,%9}, {%0,%1,%2,%3};"
                 : "+f"(c[0]), "+f"(c[1]), "+f"(c[2]), "+f"(c[3])
                 : "r"(a[0]), "r"(a[1]), "r"(a[2]), "r"(a[3]), "r"(b0), "r"(b1));
}
__device__ __forceinline__ void cons_bar() { asm volatile("bar.sync 1, 256;" ::: "memory"); }

__device__ __forceinline__ float bf_round(float v) { return __bfloat162float(__float2bfloat16_rn(v)); }
__device__ __forceinline__ uint32_t pack_bf2(float lo, float hi) {
    __nv_bfloat162 t = __floats2bfloat162_rn(lo, hi);
    return *reinterpret_cast<uint32_t*>(&t);
}
__device__ __forceinline__ float bf_lo(uint32_t u) { return __uint_as_float(u << 16); }
__device__ __forceinline__ float bf_hi(uint32_t u) { return __uint_as_float(u & 0xffff0000u); }
__device__ __forceinline__ float shx(float v, int o) { return __shfl_xor_sync(0xffffffffu, v, o); }

__device__ __forceinline__ uint32_t frag_off(uint32_t k) {
    return ((k >> 1) & 3) * 16 + ((k >> 3) & 1) * 8 + ((k >> 4) & 1) * 4 + (k & 1) * 2;
}

__device__ __forceinline__ void st_tag2(float* p, float a, float b, uint32_t tag) {
    asm volatile("{\n.reg .b64 w;\n.reg .b32 x;\nlop3.b32 x, %1, 0xfffffffe, %3, 0xea;\nmov.b64 w, {x, %2};\n"
                 "st.relaxed.gpu.global.b64 [%0], w;\n}"
                 ::"l"(p), "r"(__float_as_uint(a)), "r"(__float_as_uint(b)), "r"(tag) : "memory");
}
__device__ __forceinline__ void st_fill4(float* p, uint32_t v) {
    asm volatile("{\n.reg .b64 w;\nmov.b64 w, {%1, %1};\nst.relaxed.gpu.global.v2.b64 [%0], {w, w};\n}" ::"l"(p), "r"(v) : "memory");
}
__device__ __forceinline__ uint32_t bad4(const uint4& v, uint32_t tag) {
    uint32_t r;
    asm("lop3.b32 %0, %1, %2, %3, 0x7e;" : "=r"(r) : "r"(v.x), "r"(v.z), "r"(tag));
    return r;
}
__device__ __forceinline__ void ld_need2(uint2& v, const float* p, uint32_t bad) {
    asm volatile("{\n.reg .pred p;\n.reg .b64 w;\n.reg .b32 n;\nand.b32 n, %3, 1;\nsetp.ne.u32 p, n, 0;\nmov.b64 w, {%0,%1};\n"
                 "@p ld.relaxed.gpu.global.b64 w, [%2];\nmov.b64 {%0,%1}, w;\n}"
                 : "+r"(v.x), "+r"(v.y) : "l"(p), "r"(bad) : "memory");
}
__device__ __forceinline__ void ld_need4(uint4& v, const float* p, uint32_t bad) {
    asm volatile("{\n.reg .pred p;\n.reg .b64 w0, w1;\n.reg .b32 n;\nand.b32 n, %5, 1;\nsetp.ne.u32 p, n, 0;\n"
                 "mov.b64 w0, {%0,%1};\nmov.b64 w1, {%2,%3};\n"
                 "@p ld.relaxed.gpu.global.v2.b64 {w0, w1}, [%4];\nmov.b64 {%0,%1}, w0;\nmov.b64 {%2,%3}, w1;\n}"
                 : "+r"(v.x), "+r"(v.y), "+r"(v.z), "+r"(v.w) : "l"(p), "r"(bad) : "memory");
}
__device__ __forceinline__ uint32_t quad_reduce(float a0, float a1, float a2, float a3, int t) {
    const bool up = t & 2;
    float x = (up ? a2 : a0) + shx(up ? a0 : a2, 2), y = (up ? a3 : a1) + shx(up ? a1 : a3, 2);
    x += shx(x, 1);
    y += shx(y, 1);
    return pack_bf2(x, y);
}

template <int N>
__device__ __forceinline__ void add_out(const float4* acc, uint32_t* out, const float (&v)[N][2], uint32_t live,
                                        uint32_t live_last, uint32_t epoch) {
    float o[N][4];
#pragma unroll
    for (int i = 0; i < N; i++) {
        o[i][2] = 0.f;
        asm volatile("{\n.reg .pred p;\nsetp.ne.u32 p, %5, 0;\n"
                     "@p atom.relaxed.gpu.global.add.v4.f32 {%0,%1,%2,%3}, [%4], {%6,%7,%8,%9};\n}"
                     : "=f"(o[i][0]), "=f"(o[i][1]), "+f"(o[i][2]), "=f"(o[i][3])
                     : "l"(acc + i * 32), "r"(i < N - 1 ? live : live_last), "f"(v[i][0]), "f"(v[i][1]), "f"(1.0f), "f"(0.0f)
                     : "memory");
    }
#pragma unroll
    for (int i = 0; i < N; i++)
        asm volatile("{\n.reg .pred p;\nsetp.eq.f32 p, %2, %3;\n@p st.global.u32 [%0], %1;\n}"
                     ::"l"(out + i * 32), "r"(pack_bf2(o[i][0] + v[i][0], o[i][1] + v[i][1])), "f"(o[i][2]), "f"((float)(NSRC - 1))
                     : "memory");
    if (acc == g_acc && o[0][2] == (float)(NSRC - 1))
        asm volatile("st.relaxed.gpu.global.u32 [%0], %1;" ::"l"(&g_sync.epoch), "r"(epoch + 1u) : "memory");
}

__device__ __forceinline__ int pair_of(int sg, uint32_t j) { return sg * G + (j % (G / 4)) * 4 + j / (G / 4); }

struct Ring {
    uint32_t full, addr, phase, first_full;
    __device__ __forceinline__ void wait() const { mbar_wait(full, phase); }
    __device__ __forceinline__ void skip(int n) {
        full += n * 8; addr += n * SLOT;
        if (full >= first_full + NS * 8) { full -= NS * 8; addr -= NS * SLOT; phase ^= 1; }
    }
    __device__ __forceinline__ void release(int lane) {
        __syncwarp();
        if (lane == 0) mbar_arrive(full + NS * 8);
        full += 8; addr += SLOT;
        if (full == first_full + NS * 8) { full = first_full; addr -= NS * SLOT; phase ^= 1; }
    }
};

__device__ __forceinline__ void pin3(uint32_t (&v)[3]) {
    asm volatile("" : "+r"(v[0]), "+r"(v[1]), "+r"(v[2]));
}
__device__ __forceinline__ void gemv_loop(Ring& ring, int n, uint32_t a_addr, uint32_t a_step, uint32_t (&off)[3],
                                          float (&lo)[3][4], float (&hi)[3][4], int lane) {
    pin3(off);
#pragma unroll
    for (int s = 0; s < 3; s++)
#pragma unroll
        for (int e = 0; e < 4; e++) { lo[s][e] = 0.f; hi[s][e] = 0.f; }
#pragma unroll 1
    for (int it = 0; it < n; it++) {
        uint32_t a[4], b[3][4];
        lds128(a_addr, a);
        a_addr += a_step;
        ring.wait();
#pragma unroll
        for (int s = 0; s < 3; s++) ldsm_x4_t(ring.addr + off[s], b[s]);
#pragma unroll
        for (int s = 0; s < 3; s++) { mma16816(lo[s], a, b[s][0], b[s][1]); mma16816(hi[s], a, b[s][2], b[s][3]); }
        ring.release(lane);
    }
}

__global__ void __launch_bounds__(NTHR, 1)
fused_decode_kernel(const char* __restrict__ kwin, const bf16* __restrict__ x, bf16* __restrict__ out,
                    const __grid_constant__ Maps maps) {
    extern __shared__ __align__(1024) unsigned char smem[];
    const uint32_t sb = (uint32_t)__cvta_generic_to_shared(smem);
    const int tid = threadIdx.x, warp = tid >> 5, lane = tid & 31;
    const unsigned cta = blockIdx.x;
    const bool is_att = cta < NATT;
    const int h = cta >> 2, qd = cta & 3;
    const int sg = cta / G, r = cta % G;
    const uint32_t bar_full = sb + SM_BAR;

    uint64_t pol;
    asm volatile("createpolicy.fractional.L2::evict_first.b64 %0, 1.0;" : "=l"(pol));
    if (tid == NCW * 32) {
        TS(0);
        const CUtensorMap* map = is_att ? &maps.wq : &maps.w1;
        const int c1 = is_att ? h * 3 : qd * 6, c2 = is_att ? qd * 160 : 0, step = is_att ? 32 : 16;
#pragma unroll 1
        for (int i = 0; i < DEPTH0; i++) {
            mbar_init(bar_full + i * 8, 1);
            mbar_expect_tx(bar_full + i * 8, 12288);
            tma3d(sb + SM_RING + i * SLOT, map, c1, c2 + i * step, bar_full + i * 8, pol);
        }
        TS(1);
    }
    if (warp == NCW) {
        volatile int* pace = reinterpret_cast<volatile int*>(smem + SM_PACE);
        if (lane == 0) {
            pace[0] = 0;
            pace[1] = is_att ? P_DINIT : P_DEPTH_FFN;
#pragma unroll
            for (int i = DEPTH0; i < NBAR; i++)
                mbar_init(bar_full + i * 8, i < NS ? 1 : i < 2 * NS ? NCW : i < 2 * NS + G ? NXW : i == 2 * NS + G && is_att ? 1 + NB * NXW : 1);
            asm volatile("fence.mbarrier_init.release.cluster;" ::: "memory");
        }
        __syncwarp();
        asm volatile("bar.arrive 2, %0;" ::"n"(NTHR) : "memory");
        if (lane == 0) {
            const int n_items = is_att ? ITEMS_ATT : ITEMS_FFN;

            asm volatile("prefetch.tensormap [%0];" ::"l"(is_att ? &maps.k : &maps.w3) : "memory");
            asm volatile("prefetch.tensormap [%0];" ::"l"(is_att ? &maps.v : &maps.w2) : "memory");
            asm volatile("prefetch.tensormap [%0];" ::"l"(&maps.wo) : "memory");
#pragma unroll 1
            for (int i = DEPTH0; i < n_items; i++) {
                const CUtensorMap* map;
                int c1, c2;
                uint32_t bytes = 12288;
                if (is_att) {
                    const uint32_t u = i - 5;
                    if (u < NKV) {
                        const int pair = pair_of(sg, u / (2 * NT));
                        map = (u & NT) ? &maps.v : &maps.k;
                        c1 = 0;
                        c2 = ((pair & 3) * NH + (pair >> 2)) * SK + (SK - WIN) + ((u % NT) * G + r) * TK;
                    } else if (i < 5) {
                        map = &maps.wq; c1 = h * 3; c2 = qd * 160 + i * 32;
                    } else {
                        map = &maps.wo; c1 = qd * 5; c2 = h * DH + (u - NKV) * 32; bytes = 10240;
                    }
                } else {
                    if (i < 80) {
                        map = i < 40 ? &maps.w1 : &maps.w3; c1 = qd * 6; c2 = (i < 40 ? i : i - 40) * 16;
                    } else {
                        map = &maps.w2; c1 = i < 104 ? 0 : 5; c2 = qd * 384 + (i < 104 ? i - 80 : i - 104) * 16; bytes = 10240;
                    }
                }
                const int depth = (is_att && i >= 5 + NKV) ? ((P_DWO >> (4 * (i - 5 - NKV))) & 15) + (P_WOPACE ? pace[1] - DEPTH : 0) : pace[1];
                const uint32_t slot = (uint32_t)i % NS, landed = i - depth;
                if (i >= NS) mbar_wait(bar_full + (NS + slot) * 8, ((uint32_t)i / NS - 1) & 1);
                mbar_expect_tx(bar_full + slot * 8, bytes);
                uint32_t dst = sb + SM_RING + slot * SLOT, fb = bar_full + slot * 8;
                asm volatile("" : "+r"(dst), "+r"(fb), "+l"(map), "+r"(c1), "+r"(c2));
                if (i == 4) TS(22);
                if (i >= depth) mbar_wait(bar_full + (landed % NS) * 8, (landed / NS) & 1);
                tma3d(dst, map, c1, c2, fb, pol);
                if (i == 4) TS(23);
                if (i == 5) TS(30);
                if (i == 8) TS(31);
                pace[0] = landed + 1;
            }
        }
        return;
    }

    const int g = lane >> 2, t = lane & 3;
    uint32_t epoch;
    asm volatile("ld.relaxed.gpu.global.u32 %0, [%1];" : "=r"(epoch) : "l"(&g_sync.epoch) : "memory");

    if (warp == NCW + 1 + NXW) {
        asm volatile("bar.sync 2, %0;" ::"n"(NTHR) : "memory");
        if (lane == 0 && is_att && P_GAIN) {
            volatile int* pace = reinterpret_cast<volatile int*>(smem + SM_PACE);
            if (cta == 0) asm volatile("st.relaxed.gpu.global.u32 [%0], %1;" ::"l"(&g_sync.prog[epoch & 1u]), "r"(0u) : "memory");
            unsigned* prog = &g_sync.prog[~epoch & 1u];
            int reported = 0;
#pragma unroll 1
            for (int it = 0; it < 4096; it++) {
                const int landed = pace[0];
                if (landed >= NKV + 5 - P_DMAX) break;
                int sum;
                asm volatile("atom.relaxed.gpu.global.add.u32 %0, [%1], %2;" : "=r"(sum) : "l"(prog), "r"(landed - reported) : "memory");
                reported = landed;
                const int lag16 = sum / (NATT / 16) - landed * 16 + P_BIAS;
                pace[1] = min(max(DEPTH + ((lag16 * P_GAIN + 128) >> 8), P_DMIN), P_DMAX);
                __nanosleep(P_SLEEP);
            }
        }
        return;
    }
    if (warp > NCW) {
        uint32_t tag = (epoch + 1u) & 1u;
        asm volatile("" : "+r"(tag));
        const int e = tid - (NCW + 1) * 32;
        if (is_att) {
            st_fill4(g_qpart + (cta * NB + e / 48) * VS + (e % 48) / 6 * 32 + (e % 6) * 4, tag ^ 1u);
            if (e < 50) {
#pragma unroll 1
                for (int j = 0; j < G; j++) st_fill4(g_opart + ((sg * G + j) * G + r) * OPS + e / 6 * 32 + (e % 6) * 4, tag ^ 1u);
            }
        } else {
#pragma unroll 1
            for (int c = qd * 320 + e; c < qd * 320 + 320; c += NXW * 32) {
                const uint32_t xw = __ldg(reinterpret_cast<const uint32_t*>(x) + c);
                asm volatile("st.relaxed.gpu.global.v4.f32 [%0], {%1,%2,%3,%3};"
                             ::"l"(g_acc + c), "f"(bf_lo(xw)), "f"(bf_hi(xw)), "f"(0.f) : "memory");
            }
            __syncwarp();
            if (lane == 0) asm volatile("red.release.gpu.global.add.u32 [%0], 1;" ::"l"(&g_sync.inits) : "memory");
        }
        asm volatile("bar.sync 2, %0;" ::"n"(NTHR) : "memory");
        const uint32_t xw = (e >> 2) / 6, xr = (e >> 2) % 6, voff = xw * 32 + xr * 4;
        const uint32_t col = (xr >> 1) * 64 + xw * 8 + (xr & 1) * 4 + (t & 2);
        if (is_att) {
            mbar_wait(bar_full + B_TRIG + 40, 0);
            if (e == 0) TS(10);
            __nanosleep(P_QDELAY);
#pragma unroll 1
            for (int j = 0; j < G; j++) {
                const int pair = pair_of(sg, j);
                const float* src = g_qpart + (((pair >> 2) * 4 + t) * NB + (pair & 3)) * VS + voff;
                uint4 v = make_uint4(~tag, ~tag, ~tag, ~tag);
                unsigned spin = 0;
                while (bad4(v, tag) & 1u) {
                    ld_need4(v, src, 1u);
                    if (++spin > SPIN_LIMIT) __trap();
                }
                const uint32_t qq = quad_reduce(__uint_as_float(v.x), __uint_as_float(v.y), __uint_as_float(v.z), __uint_as_float(v.w), t);
                if (!(t & 1)) *reinterpret_cast<uint32_t*>(smem + SM_QS + j * (DH * 2) + ((col & 7) >> 1) * 96 + (col >> 3) * 4) = qq;
                __syncwarp();
                if (lane == 0) mbar_arrive(bar_full + B_QRDY + j * 8);
                if (e == 0 && j == 0) TS(12);
            }
        }
        if (e == 0) {
            unsigned spin = 0, n;
            do {
                asm volatile("ld.acquire.gpu.global.u32 %0, [%1];" : "=r"(n) : "l"(&g_sync.inits) : "memory");
                if (++spin > SPIN_LIMIT) __trap();
            } while (n != (epoch + 1u) * (NFFN * NXW));
            mbar_arrive(bar_full + B_ORDY);
        }
#pragma unroll 1
        for (int b = 0; b < (is_att ? NB : 0); b++) {
            constexpr int KP = G / 4;
            const float* src = g_opart + (h * NB + b) * (G * OPS);
            const float* mlp = src + (lane % G) * OPS + VS;
            src += t * KP * OPS + voff;
            const bool last = h * NB + b == sg * G + G - 1;
            uint32_t of_addr = sb + SM_OF + (col >> 5) * 256 + b * 64 + frag_off(col & 31);
            uint4 v[KP];
            uint2 ml = make_uint2(0u, 0u);
            uint32_t bad[KP];
            mbar_wait(bar_full + B_TRIG + b * 8, 0);
            ld_need2(ml, mlp, 1u);
#pragma unroll
            for (int k = 0; k < KP; k++) { v[k] = make_uint4(0u, 0u, 0u, 0u); ld_need4(v[k], src + k * OPS, 1u); }
            if (last) mbar_wait(bar_full + B_TRIG + 32, 0);
            unsigned spin = 0;
            while ((ml.x ^ tag) & 1u) {
                ld_need2(ml, mlp, 1u);
                if (++spin > SPIN_LIMIT) __trap();
            }
            const float mk = __uint_as_float(ml.x & ~1u);
            float M = mk;
#pragma unroll
            for (int o = G / 2; o; o >>= 1) M = fmaxf(M, shx(M, o));
            float w = __expf(mk - M);
            float L = w * __uint_as_float(ml.y);
#pragma unroll
            for (int o = G / 2; o; o >>= 1) L += shx(L, o);
            w = __fdividef(w, L);
            float wk[KP];
#pragma unroll
            for (int k = 0; k < KP; k++) { wk[k] = __shfl_sync(0xffffffffu, w, t * KP + k); bad[k] = bad4(v[k], tag); }
            if (e == 0 && b == 3) TS(11);
            uint32_t ordy = bar_full + B_ORDY;
            asm volatile("" : "+r"(of_addr), "+l"(src), "+r"(ordy));
            if (last) mbar_wait(bar_full + B_TRIG + 48, 0);
            while (true) {
                uint32_t any = 0;
                float o0 = 0.f, o1 = 0.f, o2 = 0.f, o3 = 0.f;
#pragma unroll
                for (int k = 0; k < KP; k++) ld_need4(v[k], src + k * OPS, bad[k]);
#pragma unroll
                for (int k = 0; k < KP; k++) {
                    bad[k] = bad4(v[k], tag);
                    asm("or.b32 %0, %0, %1;" : "+r"(any) : "r"(bad[k]));
                    o0 += wk[k] * __uint_as_float(v[k].x);
                    o1 += wk[k] * __uint_as_float(v[k].y);
                    o2 += wk[k] * __uint_as_float(v[k].z);
                    o3 += wk[k] * __uint_as_float(v[k].w);
                }
                const uint32_t oo = quad_reduce(o0, o1, o2, o3, t);
                asm volatile("st.shared.u32 [%0], %1;" ::"r"(of_addr), "r"(oo) : "memory");
                if (!__any_sync(0xffffffffu, any & 1u)) break;
                if (++spin > SPIN_LIMIT) __trap();
            }
            __syncwarp();
            if (lane == 0) mbar_arrive(ordy);
        }
        return;
    }

    if (warp < NB) {
        uint2 raw[5];
#pragma unroll
        for (int i = 0; i < 5; i++) raw[i] = __ldg(reinterpret_cast<const uint2*>(x + warp * DM) + i * 32 + lane);
        float s = 0.f;
#pragma unroll
        for (int i = 0; i < 5; i++) s += (bf_lo(raw[i].x) + bf_hi(raw[i].x)) + (bf_lo(raw[i].y) + bf_hi(raw[i].y));
#pragma unroll
        for (int o = 16; o; o >>= 1) s += shx(s, o);
        const float mean = s * (1.0f / DM);
        float q2 = 0.f;
#pragma unroll
        for (int i = 0; i < 5; i++) {
            const float d0 = bf_lo(raw[i].x) - mean, d1 = bf_hi(raw[i].x) - mean;
            const float d2 = bf_lo(raw[i].y) - mean, d3 = bf_hi(raw[i].y) - mean;
            q2 += (d0 * d0 + d1 * d1) + (d2 * d2 + d3 * d3);
        }
#pragma unroll
        for (int o = 16; o; o >>= 1) q2 += shx(q2, o);
        const float mb = bf_round(mean);
        const float rs = __frcp_rn(bf_round(__fsqrt_rn(bf_round(bf_round(q2 * (1.0f / DM)) + 1e-5f))));
        const uint32_t k = (lane * 4) & 31;
        unsigned char* dst = smem + SM_XF + warp * 64 +
            (is_att ? (lane >> 3) * 256 + frag_off(k) : (lane >> 2) * 256 + frag_off(k & 15));
        const uint32_t step = is_att ? 1024 : 2048;
#pragma unroll
        for (int i = 0; i < 5; i++) {
            const uint32_t d0 = pack_bf2(bf_lo(raw[i].x) - mb, bf_hi(raw[i].x) - mb);
            const uint32_t d1 = pack_bf2(bf_lo(raw[i].y) - mb, bf_hi(raw[i].y) - mb);
            *reinterpret_cast<uint32_t*>(dst + i * step) = pack_bf2(bf_lo(d0) * rs, bf_hi(d0) * rs);
            *reinterpret_cast<uint32_t*>(dst + i * step + 16) = pack_bf2(bf_lo(d1) * rs, bf_hi(d1) * rs);
        }
    }
    asm volatile("bar.sync 2, %0;" ::"n"(NTHR) : "memory");
    uint32_t tag = (epoch + 1u) & 1u;
    asm volatile("" : "+r"(tag));
    if (tid == 0) TS(3);

    Ring ring{bar_full, sb + SM_RING, 0u, bar_full};
    float lo[3][4], hi[3][4];
    uint32_t off[3];
    const uint32_t a_lane = (g & 3) * 64 + t * 16;

    if (is_att) {
        float* lsum = reinterpret_cast<float*>(smem + SM_LS);
#pragma unroll 1
        for (int j = -1; j < G; j++) {
            const bool kv = j >= 0;
            const int pair = pair_of(sg, j), prev = pair_of(sg, j - 1);
            const bool trig_last = tid == 0 && j == G - 1 && (pair >> 2) == h;
            if (trig_last) mbar_arrive(bar_full + B_TRIG + 24);
            const bool trig = tid == 0 && j >= 1 && (prev >> 2) == h;
            uint32_t a_addr, a_step, rows;
            int n;
            float* dst;
            if (kv) {
                uint32_t qf[6][4];
                mbar_wait(bar_full + B_QRDY + j * 8, 0);
                if (j == 0 && tid == 0) TS(6);
#pragma unroll
                for (int i = 0; i < 6; i++) lds128(sb + SM_QS + j * (DH * 2) + t * 96 + i * 16, qf[i]);
                const uint32_t key = (warp & 1) * 16 + (lane & 15);
                float sv[NT / 4], m = -INFINITY;
#pragma unroll
                for (int rr = 0; rr < NT / 4; rr++) {
                    const uint32_t item = 5 + j * (2 * NT) + rr * 4 + (warp >> 1), slot = item % NS;
#pragma unroll
                    for (int s = 0; s < 3; s++)
                        off[s] = sb + SM_RING + slot * SLOT + key * 384 + s * 128 + (((lane >> 4) ^ ((3 * key + s) & 7)) << 4);
                    pin3(off);
                    mbar_wait(bar_full + slot * 8, (item / NS) & 1);
                    float c[3][4] = {};
#pragma unroll
                    for (int dq = 0; dq < 4; dq++)
#pragma unroll
                        for (int s = 0; s < 3; s++) {
                            uint32_t a[4];
                            ldsm_x4(off[s] ^ (dq << 5), a);
                            mma16816(c[s], a, qf[s * 2 + (dq >> 1)][(dq & 1) * 2], qf[s * 2 + (dq >> 1)][(dq & 1) * 2 + 1]);
                        }
                    __syncwarp();
                    if (lane == 0)
                        asm volatile("mbarrier.arrive.shared::cta.b64 _, [%0], %1;" ::"r"(bar_full + (NS + slot) * 8), "n"(NCW / 2) : "memory");
                    const float raw = (t & 1) ? (c[0][2] + c[1][2]) + c[2][2] : (c[0][0] + c[1][0]) + c[2][0];
                    sv[rr] = bf_round(bf_round(raw) * 0.07216878364870323f);
                    m = fmaxf(m, sv[rr]);
                }
                ring.skip(NT);
                if (tid == 0 && j == G - 1) TS(14);
                if (trig && j == G - 1) mbar_arrive(bar_full + B_TRIG + (prev & 3) * 8);
                m = fmaxf(m, shx(m, 1));
#pragma unroll
                for (int o = 4; o < 32; o <<= 1) m = fmaxf(m, shx(m, o));
                if (lane == 0) lsum[8 + warp] = m;
                cons_bar();
                {
                    const float4 m0 = reinterpret_cast<const float4*>(lsum)[2], m1 = reinterpret_cast<const float4*>(lsum)[3];
                    m = fmaxf(fmaxf(fmaxf(m0.x, m0.y), fmaxf(m0.z, m0.w)), fmaxf(fmaxf(m1.x, m1.y), fmaxf(m1.z, m1.w)));
                }
                float l = 0.f;
#pragma unroll
                for (int rr = 0; rr < NT / 4; rr++) {
                    const float p = __expf(sv[rr] - m);
                    l += p;
                    *reinterpret_cast<bf16*>(smem + SM_PF + (rr * 4 + (warp >> 1)) * 64 + frag_off((warp & 1) * 16 + (t & 1) * 8 + g)) =
                        __float2bfloat16_rn(p);
                }
                l += shx(l, 1);
#pragma unroll
                for (int o = 4; o < 32; o <<= 1) l += shx(l, o);
                if (lane == 0) lsum[warp] = l;
                cons_bar();
                dst = g_opart + (pair * G + r) * OPS;
                if (tid < 4) {
                    const float4 l0 = reinterpret_cast<const float4*>(lsum)[0], l1 = reinterpret_cast<const float4*>(lsum)[1];
                    st_tag2(dst + VS + tid * 2, m, ((l0.x + l0.y) + (l0.z + l0.w)) + ((l1.x + l1.y) + (l1.z + l1.w)), tag);
                }
                if (tid == 0 && j == G - 1) TS(13);
                if (trig_last) mbar_arrive(bar_full + B_TRIG + 32);
                if (trig_last && P_EARLY) mbar_arrive(bar_full + B_TRIG + 48);
                dst += warp * 32;
                a_addr = sb + SM_PF + t * 16; a_step = 64; n = NT; rows = 1;
            } else {
                dst = g_qpart + (cta * NB + g) * VS + warp * 32;
                a_addr = sb + SM_XF + qd * 5 * 256 + a_lane; a_step = 256; n = 5; rows = NB;
            }
#pragma unroll
            for (int s = 0; s < 3; s++) off[s] = lane * 384 + s * 128 + ((warp ^ ((3 * lane + s) & 7)) << 4);
            gemv_loop(ring, n, a_addr, a_step, off, lo, hi, lane);
            if (j == G - 1 ? trig_last && !P_EARLY : trig) mbar_arrive(bar_full + B_TRIG + (j == G - 1 ? 48 : (prev & 3) * 8));
            if (j == G - 1 && tid == 0) TS(5);
            if (g < rows) {
#pragma unroll
                for (int s = 0; s < 3; s++) st_tag2(dst + 2 * t + s * 8, lo[s][0] + hi[s][2], lo[s][1] + hi[s][3], tag);
            }
            if (j >= 0 && j < G - 1) continue;
            if (tid == 0 && j < 0) { mbar_arrive(bar_full + B_TRIG + 40); TS(4); }

#pragma unroll 1
            for (int pass = 0; pass <= (int)kv; pass++) {
                constexpr int I0 = 5 + NKV;
                uint32_t b[6][3][4];
#pragma unroll
                for (int s = 0; s < 3; s++) {
                    const uint32_t w64 = lane * 320 + (warp + 8 * s) * 16;
                    off[s] = sb + SM_RING + (w64 ^ (((w64 >> 7) & 3) << 4));
#pragma unroll
                    for (int e = 0; e < 4; e++) { lo[s][e] = 0.f; hi[s][e] = 0.f; }
                }
                const int cell = g * 320 + (qd * 20 + warp) * 4 + t;
                const float4* accp = g_acc + cell;
                uint32_t* outp = reinterpret_cast<uint32_t*>(out) + cell;
                uint32_t live = pass && g < NB, live3 = live && warp < 4, a_addr = sb + SM_OF + a_lane;
                const uint32_t done = bar_full + B_TRIG + 40;
                uint32_t ordy = pass ? bar_full + B_ORDY : done, fb[6];
#pragma unroll
                for (int i = 0; i < 6; i++) fb[i] = pass ? bar_full + ((I0 + i) % NS) * 8 : done;
                pin3(off);
                asm volatile("" : "+l"(accp), "+l"(outp), "+r"(live), "+r"(live3), "+r"(a_addr), "+r"(ordy), "+r"(fb[3]), "+r"(fb[4]), "+r"(fb[5]));
                uint32_t a[6][4];
#pragma unroll
                for (int i = 0; i < 6; i++) {
                    if (i == P_PRE) {
                        mbar_wait(ordy, 0);
                        if (pass && tid == 0) TS(7);
#pragma unroll
                        for (int k = 0; k < 6; k++) lds128(a_addr + k * 256, a[k]);
                    }
                    mbar_wait(fb[i], pass ? ((I0 + i) / NS) & 1 : 0);
#pragma unroll
                    for (int s = 0; s < 3; s++) ldsm_x4_t(off[s] + ((I0 + i) % NS) * SLOT, b[i][s]);
#pragma unroll
                    for (int k = 0; k < 6; k++)
                        if (i >= P_PRE && (i == P_PRE ? k < i : k == i - 1) || (i == 5 && k == 5)) {
#pragma unroll
                            for (int s = 0; s < 3; s++)
                                if (s < 2 || warp < 4) { mma16816(lo[s], a[k], b[k][s][0], b[k][s][1]); mma16816(hi[s], a[k], b[k][s][2], b[k][s][3]); }
                        }
                }
                if (pass && tid == 0) TS(8);
                float v[3][2];
#pragma unroll
                for (int s = 0; s < 3; s++) { v[s][0] = lo[s][0] + hi[s][2]; v[s][1] = lo[s][1] + hi[s][3]; }
                add_out<3>(accp, outp, v, live, live3, epoch);
            }
        }
        if (tid == 0) { TS(9); TS_DUMP(3, 32); }
    } else {
        float gate[6][2];
#pragma unroll 1
        for (int ps = 0; ps < 4; ps++) {
            const uint32_t row = lane & 15, parts = ps < 2 ? 6 : 5;
#pragma unroll
            for (int s = 0; s < 3; s++) {
                const uint32_t r128 = row * parts + min(2 * s + (lane >> 4), parts - 1);
                off[s] = r128 * 128 + ((warp ^ (r128 & 7)) << 4);
            }
            gemv_loop(ring, ps < 2 ? 40 : 24, sb + (ps < 2 ? SM_XF : SM_HF) + a_lane, 256, off, lo, hi, lane);
            if (ps == 0) {
#pragma unroll
                for (int s = 0; s < 3; s++) {
                    gate[2 * s][0] = lo[s][0]; gate[2 * s][1] = lo[s][1];
                    gate[2 * s + 1][0] = hi[s][0]; gate[2 * s + 1][1] = hi[s][1];
                }
            } else if (ps == 1) {
#pragma unroll
                for (int p = 0; p < 6; p++) {
                    float hv[2];
#pragma unroll
                    for (int e = 0; e < 2; e++) {
                        const float gt = bf_round(gate[p][e]);
                        hv[e] = bf_round(__fdividef(gt, 1.0f + __expf(-gt))) * bf_round((p & 1) ? hi[p >> 1][e] : lo[p >> 1][e]);
                    }
                    if (g < NB)
                        *reinterpret_cast<uint32_t*>(smem + SM_HF + (p * 4 + (warp >> 1)) * 256 + g * 64 + t * 16 + (warp & 1) * 8) =
                            pack_bf2(hv[0], hv[1]);
                }
                cons_bar();
            } else {
                mbar_wait(bar_full + B_ORDY, 0);
                const int cell = g * 320 + ((ps - 2) * 40 + warp) * 4 + t;
                float v[5][2];
#pragma unroll
                for (int p = 0; p < 5; p++) {
                    v[p][0] = (p & 1) ? hi[p >> 1][0] : lo[p >> 1][0];
                    v[p][1] = (p & 1) ? hi[p >> 1][1] : lo[p >> 1][1];
                }
                add_out<5>(g_acc + cell, reinterpret_cast<uint32_t*>(out) + cell, v, g < NB, g < NB, epoch);
            }
        }
        if (tid == 0) { TS(9); TS_DUMP(3, 10); }
    }
}

typedef CUresult (*EncodeFn)(CUtensorMap*, CUtensorMapDataType, cuuint32_t, void*, const cuuint64_t*, const cuuint64_t*,
                             const cuuint32_t*, const cuuint32_t*, CUtensorMapInterleave, CUtensorMapSwizzle,
                             CUtensorMapL2promotion, CUtensorMapFloatOOBfill);

void make_map(EncodeFn enc, CUtensorMap* m, const void* p, uint64_t rows, uint64_t cols, uint32_t inner, uint32_t parts,
              uint32_t box_rows) {
    const cuuint64_t dims[3] = {inner, cols / inner, rows};
    const cuuint64_t strides[2] = {inner * 2ull, cols * 2ull};
    const cuuint32_t box[3] = {inner, parts, box_rows};
    const cuuint32_t es[3] = {1, 1, 1};
    enc(m, CU_TENSOR_MAP_DATA_TYPE_BFLOAT16, 3, const_cast<void*>(p), dims, strides, box, es, CU_TENSOR_MAP_INTERLEAVE_NONE,
        inner == 64 ? CU_TENSOR_MAP_SWIZZLE_128B : CU_TENSOR_MAP_SWIZZLE_64B, CU_TENSOR_MAP_L2_PROMOTION_NONE,
        CU_TENSOR_MAP_FLOAT_OOB_FILL_NONE);
}

}

extern "C" void kernel_launch(void* const* d_in, const int* in_sizes, int n_in, void* d_out, int out_size) {
    (void)in_sizes; (void)n_in; (void)out_size;
    static EncodeFn enc = nullptr;
    if (!enc) {
        void* fn = nullptr;
        cudaDriverEntryPointQueryResult qr;
        cudaGetDriverEntryPoint("cuTensorMapEncodeTiled", &fn, cudaEnableDefault, &qr);
        enc = (EncodeFn)fn;
        cudaFuncSetAttribute(fused_decode_kernel, cudaFuncAttributeMaxDynamicSharedMemorySize, SM_TOTAL);
    }
    Maps maps;
    make_map(enc, &maps.k, d_in[1], (uint64_t)NB * NH * SK, DH, 64, 3, TK);
    make_map(enc, &maps.v, d_in[2], (uint64_t)NB * NH * SK, DH, 64, 3, TK);
    make_map(enc, &maps.wq, d_in[3], DM, NH * DH, 64, 3, 32);
    make_map(enc, &maps.wo, d_in[4], NH * DH, DM, 32, 5, 32);
    make_map(enc, &maps.w1, d_in[6], DM, FF, 64, 6, 16);
    make_map(enc, &maps.w3, d_in[7], DM, FF, 64, 6, 16);
    make_map(enc, &maps.w2, d_in[8], FF, DM, 64, 5, 16);
    fused_decode_kernel<<<NCTA, NTHR, SM_TOTAL>>>((const char*)d_in[1] + (size_t)(SK - WIN) * DH * 2, (const bf16*)d_in[0],
                                                  (bf16*)d_out, maps);
}
```

```cpp
#include <cuda_runtime.h>
#include <cuda.h>
#include <cuda_bf16.h>
#include <stdint.h>

namespace {

typedef __nv_bfloat16 bf16;

constexpr int NB = 4, DM = 640, NH = 32, DH = 192, SK = 8192, WIN = 2048, FF = 1536;

#define P_G 16
#define P_DEPTH 4
#define P_DEPTH_FFN 4
#define P_GAIN 8
#define P_BIAS 16
#define P_SLEEP 500
#define P_DMIN P_DEPTH
#define P_DMAX 6
#define P_SETTLE 3000
#define P_QDELAY 1600
#define P_DWO 0x333333
#define P_WOPACE 1
#define P_PRE 3
#define P_WSETTLE 2000
#define P_NSL 20
#define P_DRY (G - 1)
#define P_NS 16

constexpr int G = P_G;
constexpr int TK = 32;
constexpr int NT = WIN / TK / G;
constexpr int NS = P_NS;
constexpr int SLOT = 12288;
constexpr int DEPTH = P_DEPTH;
#define P_D0 5
constexpr int DEPTH0 = P_D0;
static_assert(DEPTH0 <= 5, "DEPTH0");
constexpr int NATT = 128, NFFN = 4, NCTA = NATT + NFFN;
constexpr int NCW = 8;
constexpr int NXW = 3;
constexpr int W_PROD = NCW, W_WGT = NCW + 1 + NXW, W_PACE = W_WGT + 1;
constexpr int NTHR = (W_PACE + 1) * 32;
constexpr int NSRC = NH + NFFN;
constexpr int VS = 256;
static_assert(G == 8 || G == 16, "G");

constexpr int SM_RING = 0;
constexpr int SM_XF = SM_RING + NS * SLOT;
constexpr int SM_QS = SM_XF + 20 * 256;
constexpr int SM_PF = SM_QS + G * DH * 2;
constexpr int SM_OF = SM_PF + 2 * NT * 64;
constexpr int SM_LS = SM_OF + 6 * 256;
constexpr int SM_ATT_END = SM_LS + 80;
constexpr int SM_HF = SM_XF + 40 * 256;
constexpr int SM_FFN_END = SM_HF + 24 * 256;
constexpr int SM_BAR = SM_ATT_END > SM_FFN_END ? SM_ATT_END : SM_FFN_END;
constexpr int B_QRDY = 2 * NS * 8, B_ORDY = B_QRDY + G * 8, B_OTRIG = B_ORDY + 8, B_QTRIG = B_OTRIG + 32,
              B_WTRIG = B_QTRIG + 8, B_WRDY = B_WTRIG + 16, NBAR = 2 * NS + G + 10;
constexpr int SM_PACE = SM_BAR + NBAR * 8;
constexpr int SM_TS = SM_PACE + 8;
constexpr int SM_TOTAL = SM_TS + 256;
static_assert(SM_TOTAL <= 232448, "smem");

constexpr int NKV = 2 * NT * G;
constexpr int ITEMS_ATT = 5 + NKV + 6;
constexpr int ITEMS_FFN = 80 + 48;

struct Maps { CUtensorMap k, v, wq, wo, w1, w3, w2; };

struct alignas(32) Sync { unsigned epoch, inits, prog[2]; };
__device__ Sync g_sync;
__device__ __align__(128) float g_qpart[NATT * NB * VS];
__device__ __align__(128) float g_ml[NATT * G * 32];
__device__ __align__(128) float4 g_oacc[NATT * 64];
__device__ __align__(128) float4 g_acc[NB * DM / 2];
#define TS(i)
#define TS_DUMP(lo, hi)

constexpr unsigned SPIN_LIMIT = 1u << 24;

__device__ __forceinline__ void mbar_init(uint32_t bar, int cnt) {
    asm volatile("mbarrier.init.shared::cta.b64 [%0], %1;" ::"r"(bar), "r"(cnt) : "memory");
}
__device__ __forceinline__ void mbar_expect_tx(uint32_t bar, uint32_t bytes) {
    asm volatile("mbarrier.arrive.expect_tx.shared::cta.b64 _, [%0], %1;" ::"r"(bar), "r"(bytes) : "memory");
}
__device__ __forceinline__ void mbar_arrive(uint32_t bar) {
    asm volatile("mbarrier.arrive.shared::cta.b64 _, [%0];" ::"r"(bar) : "memory");
}
__device__ __forceinline__ void mbar_wait(uint32_t bar, uint32_t parity) {
    asm volatile("{\n.reg .pred p, q;\n.reg .u32 n;\nmov.u32 n, 0;\n"
                 "W: mbarrier.try_wait.parity.shared::cta.b64 p, [%0], %1;\n"
                 "@p bra D;\nadd.u32 n, n, 1;\nsetp.lt.u32 q, n, %2;\n@q bra W;\ntrap;\nD:\n}"
                 ::"r"(bar), "r"(parity), "n"(SPIN_LIMIT) : "memory");
}
__device__ __forceinline__ void tma3d(uint32_t dst, const CUtensorMap* map, int c1, int c2, uint32_t bar, uint64_t pol) {
    asm volatile("cp.async.bulk.tensor.3d.shared::cluster.global.mbarrier::complete_tx::bytes.L2::cache_hint "
                 "[%0], [%1, {%2, %3, %4}], [%5], %6;"
                 ::"r"(dst), "l"(map), "r"(0), "r"(c1), "r"(c2), "r"(bar), "l"(pol) : "memory");
}
__device__ __forceinline__ void ldsm_x4(uint32_t addr, uint32_t (&r)[4]) {
    asm volatile("ldmatrix.sync.aligned.m8n8.x4.shared.b16 {%0,%1,%2,%3}, [%4];"
                 : "=r"(r[0]), "=r"(r[1]), "=r"(r[2]), "=r"(r[3]) : "r"(addr) : "memory");
}
__device__ __forceinline__ void ldsm_x4_t(uint32_t addr, uint32_t (&r)[4]) {
    asm volatile("ldmatrix.sync.aligned.m8n8.x4.trans.shared.b16 {%0,%1,%2,%3}, [%4];"
                 : "=r"(r[0]), "=r"(r[1]), "=r"(r[2]), "=r"(r[3]) : "r"(addr) : "memory");
}
__device__ __forceinline__ void lds128(uint32_t addr, uint32_t (&r)[4]) {
    asm volatile("ld.shared.v4.u32 {%0,%1,%2,%3}, [%4];"
                 : "=r"(r[0]), "=r"(r[1]), "=r"(r[2]), "=r"(r[3]) : "r"(addr) : "memory");
}
__device__ __forceinline__ void mma16816(float (&c)[4], const uint32_t (&a)[4], uint32_t b0, uint32_t b1) {
    asm volatile("mma.sync.aligned.m16n8k16.row.col.f32.bf16.bf16.f32 {%0,%1,%2,%3}, {%4,%5,%6,%7}, {%8,%9}, {%0,%1,%2,%3};"
                 : "+f"(c[0]), "+f"(c[1]), "+f"(c[2]), "+f"(c[3])
                 : "r"(a[0]), "r"(a[1]), "r"(a[2]), "r"(a[3]), "r"(b0), "r"(b1));
}
__device__ __forceinline__ void cons_bar() { asm volatile("bar.sync 1, 256;" ::: "memory"); }

__device__ __forceinline__ float bf_round(float v) { return __bfloat162float(__float2bfloat16_rn(v)); }
__device__ __forceinline__ uint32_t pack_bf2(float lo, float hi) {
    __nv_bfloat162 t = __floats2bfloat162_rn(lo, hi);
    return *reinterpret_cast<uint32_t*>(&t);
}
__device__ __forceinline__ float bf_lo(uint32_t u) { return __uint_as_float(u << 16); }
__device__ __forceinline__ float bf_hi(uint32_t u) { return __uint_as_float(u & 0xffff0000u); }
__device__ __forceinline__ float shx(float v, int o) { return __shfl_xor_sync(0xffffffffu, v, o); }

__device__ __forceinline__ uint32_t frag_off(uint32_t k) {
    return ((k >> 1) & 3) * 16 + ((k >> 3) & 1) * 8 + ((k >> 4) & 1) * 4 + (k & 1) * 2;
}

__device__ __forceinline__ void st_tag2(float* p, float a, float b, uint32_t tag) {
    asm volatile("{\n.reg .b64 w;\n.reg .b32 x;\nlop3.b32 x, %1, 0xfffffffe, %3, 0xea;\nmov.b64 w, {x, %2};\n"
                 "st.relaxed.gpu.global.b64 [%0], w;\n}"
                 ::"l"(p), "r"(__float_as_uint(a)), "r"(__float_as_uint(b)), "r"(tag) : "memory");
}
__device__ __forceinline__ void st_fill4(float* p, uint32_t v) {
    asm volatile("{\n.reg .b64 w;\nmov.b64 w, {%1, %1};\nst.relaxed.gpu.global.v2.b64 [%0], {w, w};\n}" ::"l"(p), "r"(v) : "memory");
}
__device__ __forceinline__ uint2 ld_word(const float* p) {
    uint2 v;
    asm volatile("{\n.reg .b64 w;\nld.relaxed.gpu.global.b64 w, [%2];\nmov.b64 {%0,%1}, w;\n}" : "=r"(v.x), "=r"(v.y) : "l"(p) : "memory");
    return v;
}
__device__ __forceinline__ uint4 ld_word2(const float* p) {
    uint4 v;
    asm volatile("{\n.reg .b64 w0, w1;\nld.relaxed.gpu.global.v2.b64 {w0, w1}, [%4];\nmov.b64 {%0,%1}, w0;\nmov.b64 {%2,%3}, w1;\n}"
                 : "=r"(v.x), "=r"(v.y), "=r"(v.z), "=r"(v.w) : "l"(p) : "memory");
    return v;
}

template <int N>
__device__ __forceinline__ void add_out(const float4* acc, uint32_t* out, const float (&v)[N][2], uint32_t live,
                                        uint32_t live_last, uint32_t epoch) {
    float o[N][4];
#pragma unroll
    for (int i = 0; i < N; i++) {
        o[i][2] = 0.f;
        asm volatile("{\n.reg .pred p;\nsetp.ne.u32 p, %5, 0;\n"
                     "@p atom.relaxed.gpu.global.add.v4.f32 {%0,%1,%2,%3}, [%4], {%6,%7,%8,%9};\n}"
                     : "=f"(o[i][0]), "=f"(o[i][1]), "+f"(o[i][2]), "=f"(o[i][3])
                     : "l"(acc + i * 32), "r"(i < N - 1 ? live : live_last), "f"(v[i][0]), "f"(v[i][1]), "f"(1.0f), "f"(0.0f)
                     : "memory");
    }
#pragma unroll
    for (int i = 0; i < N; i++)
        asm volatile("{\n.reg .pred p;\nsetp.eq.f32 p, %2, %3;\n@p st.global.u32 [%0], %1;\n}"
                     ::"l"(out + i * 32), "r"(pack_bf2(o[i][0] + v[i][0], o[i][1] + v[i][1])), "f"(o[i][2]), "f"((float)(NSRC - 1))
                     : "memory");
    if (acc == g_acc && o[0][2] == (float)(NSRC - 1))
        asm volatile("st.relaxed.gpu.global.u32 [%0], %1;" ::"l"(&g_sync.epoch), "r"(epoch + 1u) : "memory");
}

__device__ __forceinline__ int pair_of(int sg, uint32_t j) { return sg * G + (j % (G / 4)) * 4 + j / (G / 4); }

__device__ __forceinline__ void settle(int cycles) {
    const uint32_t t0 = (uint32_t)clock();
    while ((uint32_t)clock() - t0 < (uint32_t)cycles) __nanosleep(P_NSL);
}

struct Ring {
    uint32_t full, addr, phase, first_full;
    __device__ __forceinline__ void wait() const { mbar_wait(full, phase); }
    __device__ __forceinline__ void skip(int n) {
        full += n * 8; addr += n * SLOT;
        if (full >= first_full + NS * 8) { full -= NS * 8; addr -= NS * SLOT; phase ^= 1; }
    }
    __device__ __forceinline__ void release(int lane) {
        __syncwarp();
        if (lane == 0) mbar_arrive(full + NS * 8);
        full += 8; addr += SLOT;
        if (full == first_full + NS * 8) { full = first_full; addr -= NS * SLOT; phase ^= 1; }
    }
};

__device__ __forceinline__ void pin3(uint32_t (&v)[3]) {
    asm volatile("" : "+r"(v[0]), "+r"(v[1]), "+r"(v[2]));
}
__device__ __forceinline__ void gemv_loop(Ring& ring, int n, uint32_t a_addr, uint32_t a_step, uint32_t (&off)[3],
                                          float (&lo)[3][4], float (&hi)[3][4], int lane) {
    pin3(off);
#pragma unroll
    for (int s = 0; s < 3; s++)
#pragma unroll
        for (int e = 0; e < 4; e++) { lo[s][e] = 0.f; hi[s][e] = 0.f; }
#pragma unroll 1
    for (int it = 0; it < n; it++) {
        uint32_t a[4], b[3][4];
        lds128(a_addr, a);
        a_addr += a_step;
        ring.wait();
#pragma unroll
        for (int s = 0; s < 3; s++) ldsm_x4_t(ring.addr + off[s], b[s]);
#pragma unroll
        for (int s = 0; s < 3; s++) { mma16816(lo[s], a, b[s][0], b[s][1]); mma16816(hi[s], a, b[s][2], b[s][3]); }
        ring.release(lane);
    }
}

__global__ void __launch_bounds__(NTHR, 1)
fused_decode_kernel(const __grid_constant__ Maps maps, const bf16* __restrict__ x, bf16* __restrict__ out) {
    extern __shared__ __align__(1024) unsigned char smem[];
    const uint32_t sb = (uint32_t)__cvta_generic_to_shared(smem);
    const int tid = threadIdx.x, warp = tid >> 5, lane = tid & 31;
    const unsigned cta = blockIdx.x;
    const bool is_att = cta < NATT;
    const int h = cta >> 2, qd = cta & 3;
    const int sg = cta / G, r = cta % G;
    const uint32_t bar_full = sb + SM_BAR;

    uint64_t pol;
    asm volatile("createpolicy.fractional.L2::evict_first.b64 %0, 1.0;" : "=l"(pol));
    if (tid == NCW * 32) {
        TS(0);
        const CUtensorMap* map = is_att ? &maps.wq : &maps.w1;
        const int c1 = is_att ? h * 3 : qd * 6, c2 = is_att ? qd * 160 : 0, step = is_att ? 32 : 16;
#pragma unroll 1
        for (int i = 0; i < DEPTH0; i++) {
            mbar_init(bar_full + i * 8, 1);
            mbar_expect_tx(bar_full + i * 8, 12288);
            tma3d(sb + SM_RING + i * SLOT, map, c1, c2 + i * step, bar_full + i * 8, pol);
        }
        TS(1);
    }
    if (warp == NCW) {
        volatile int* pace = reinterpret_cast<volatile int*>(smem + SM_PACE);
        if (lane == 0) {
            pace[0] = 0;
            pace[1] = is_att ? DEPTH : P_DEPTH_FFN;
#pragma unroll
            for (int i = DEPTH0; i < NBAR; i++)
                mbar_init(bar_full + i * 8, i < NS ? 1 : i < 2 * NS ? NCW : i < 2 * NS + G ? NXW : i == 2 * NS + G && is_att ? 2 * NB : 1);
            asm volatile("fence.mbarrier_init.release.cluster;" ::: "memory");
        }
        __syncwarp();
        asm volatile("bar.arrive 2, %0;" ::"n"(NTHR) : "memory");
        if (lane == 0) {
            const int n_items = is_att ? ITEMS_ATT : ITEMS_FFN;

            asm volatile("prefetch.tensormap [%0];" ::"l"(is_att ? &maps.k : &maps.w3) : "memory");
            asm volatile("prefetch.tensormap [%0];" ::"l"(is_att ? &maps.v : &maps.w2) : "memory");
            asm volatile("prefetch.tensormap [%0];" ::"l"(&maps.wo) : "memory");
#pragma unroll 1
            for (int i = DEPTH0; i < n_items; i++) {
                const CUtensorMap* map;
                int c1, c2;
                uint32_t bytes = 12288;
                if (is_att) {
                    const uint32_t u = i - 5;
                    if (u < NKV) {
                        const uint32_t blk = u / NT;
                        const bool isv = blk == 2 * G - 1 || (blk && !(blk & 1));
                        const int pair = pair_of(sg, isv ? (blk - 1) / 2 : (blk + 1) / 2);
                        map = isv ? &maps.v : &maps.k;
                        c1 = 0;
                        c2 = ((pair & 3) * NH + (pair >> 2)) * SK + (SK - WIN) + ((u % NT) * G + r) * TK;
                    } else if (i < 5) {
                        map = &maps.wq; c1 = h * 3; c2 = qd * 160 + i * 32;
                    } else {
                        map = &maps.wo; c1 = qd * 5; c2 = h * DH + (u - NKV) * 32; bytes = 10240;
                    }
                } else {
                    if (i < 80) {
                        map = i < 40 ? &maps.w1 : &maps.w3; c1 = qd * 6; c2 = (i < 40 ? i : i - 40) * 16;
                    } else {
                        map = &maps.w2; c1 = i < 104 ? 0 : 5; c2 = qd * 384 + (i < 104 ? i - 80 : i - 104) * 16; bytes = 10240;
                    }
                }
                const int depth = (is_att && i >= 5 + NKV) ? ((P_DWO >> (4 * (i - 5 - NKV))) & 15) + (P_WOPACE ? pace[1] - DEPTH : 0) : pace[1];
                const uint32_t slot = (uint32_t)i % NS, landed = i - depth;
                if (i >= NS) mbar_wait(bar_full + (NS + slot) * 8, ((uint32_t)i / NS - 1) & 1);
                mbar_expect_tx(bar_full + slot * 8, bytes);
                uint32_t dst = sb + SM_RING + slot * SLOT, fb = bar_full + slot * 8;
                asm volatile("" : "+r"(dst), "+r"(fb), "+l"(map), "+r"(c1), "+r"(c2));
                if (i == 4) TS(22);
                if (i >= depth) mbar_wait(bar_full + (landed % NS) * 8, (landed / NS) & 1);
                tma3d(dst, map, c1, c2, fb, pol);
                if (i == 4) TS(23);
                if (i == 5) TS(30);
                if (i == 8) TS(31);
                pace[0] = landed + 1;
            }
        }
        return;
    }

    const int g = lane >> 2, t = lane & 3;
    uint32_t epoch;
    asm volatile("ld.relaxed.gpu.global.u32 %0, [%1];" : "=r"(epoch) : "l"(&g_sync.epoch) : "memory");

    if (warp == W_PACE) {
        asm volatile("bar.sync 2, %0;" ::"n"(NTHR) : "memory");
        if (lane == 0 && is_att && P_GAIN) {
            volatile int* pace = reinterpret_cast<volatile int*>(smem + SM_PACE);
            if (cta == 0) asm volatile("st.relaxed.gpu.global.u32 [%0], %1;" ::"l"(&g_sync.prog[epoch & 1u]), "r"(0u) : "memory");
            unsigned* prog = &g_sync.prog[~epoch & 1u];
            int reported = 0;
#pragma unroll 1
            for (int it = 0; it < 4096; it++) {
                const int landed = pace[0];
                if (landed >= NKV + 5 - P_DMAX) break;
                int sum;
                asm volatile("atom.relaxed.gpu.global.add.u32 %0, [%1], %2;" : "=r"(sum) : "l"(prog), "r"(landed - reported) : "memory");
                reported = landed;
                const int lag16 = sum / (NATT / 16) - landed * 16 + P_BIAS;
                pace[1] = min(max(DEPTH + ((lag16 * P_GAIN + 128) >> 8), P_DMIN), P_DMAX);
                __nanosleep(P_SLEEP);
            }
        }
        return;
    }
    if (warp == W_WGT) {
        const uint32_t tag = (epoch + 1u) & 1u;
        if (is_att && lane < 2 * G) st_fill4(g_ml + ((sg * G + (lane >> 1)) * G + r) * 32 + (lane & 1) * 4, tag ^ 1u);
        asm volatile("bar.sync 2, %0;" ::"n"(NTHR) : "memory");
        if (lane == 0) asm volatile("red.release.gpu.global.add.u32 [%0], 1;" ::"l"(&g_sync.inits) : "memory");
        __syncwarp();
#pragma unroll 1
        for (int j = 0; j < G; j++) {
            if (is_att) mbar_wait(bar_full + B_WTRIG + (j & 1) * 8, (j >> 1) & 1);
            settle(P_WSETTLE);
            unsigned spin = 0;
            if (j == 0) {
                unsigned n;
                do {
                    asm volatile("ld.acquire.gpu.global.u32 %0, [%1];" : "=r"(n) : "l"(&g_sync.inits) : "memory");
                    if (++spin > SPIN_LIMIT) __trap();
                } while (n != (epoch + 1u) * NCTA);
                if (!is_att) {
                    if (lane == 0) mbar_arrive(bar_full + B_ORDY);
                    return;
                }
            }
            const float* src = g_ml + (pair_of(sg, j) * G + lane % G) * 32;
            uint2 ml;
            do {
                ml = ld_word(src);
                if (++spin > SPIN_LIMIT) __trap();
            } while ((ml.x ^ tag) & 1u);
            const float mk = __uint_as_float(ml.x & ~1u);
            float M = mk;
#pragma unroll
            for (int o = G / 2; o; o >>= 1) M = fmaxf(M, shx(M, o));
            const float w = __expf(mk - M);
            float L = w * __uint_as_float(ml.y);
#pragma unroll
            for (int o = G / 2; o; o >>= 1) L += shx(L, o);
            if (lane == r) {
                reinterpret_cast<float*>(smem + SM_LS)[16 + (j & 1)] = __fdividef(w, L);
                mbar_arrive(bar_full + B_WRDY + (j & 1) * 8);
                if (j == G - 1) TS(11);
            }
        }
        return;
    }
    if (warp > W_PROD) {
        const uint32_t tag = (epoch + 1u) & 1u;
        const int e = tid - (W_PROD + 1) * 32;
        if (is_att) {
#pragma unroll
            for (int i = 0; i < 2; i++)
                st_fill4(g_qpart + (cta * NB + i * 2 + e / 48) * VS + (e % 48) / 6 * 32 + (e % 6) * 4, tag ^ 1u);
            if (e < 64) st_fill4(reinterpret_cast<float*>(g_oacc + cta * 64 + e), 0u);
        } else {
#pragma unroll 1
            for (int c = qd * 320 + e; c < qd * 320 + 320; c += NXW * 32) {
                const uint32_t xw = __ldg(reinterpret_cast<const uint32_t*>(x) + c);
                asm volatile("st.relaxed.gpu.global.v4.f32 [%0], {%1,%2,%3,%3};"
                             ::"l"(g_acc + c), "f"(bf_lo(xw)), "f"(bf_hi(xw)), "f"(0.f) : "memory");
            }
        }
        asm volatile("bar.sync 2, %0;" ::"n"(NTHR) : "memory");
        if (!is_att) return;
        {
            const uint32_t xw = (e >> 1) / 6, xr = (e >> 1) % 6, up = e & 1;
            const uint32_t col = (xr >> 1) * 64 + xw * 8 + (xr & 1) * 4 + up * 2;
            mbar_wait(bar_full + B_QTRIG, 0);
            if (e == 0) TS(10);
            settle(P_QDELAY);
#pragma unroll 1
            for (int j = 0; j < G; j++) {
                const int pair = pair_of(sg, j);
                const float* src = g_qpart + (((pair >> 2) * 4 + up * 2) * NB + (pair & 3)) * VS + xw * 32 + xr * 4;
                uint4 u, v;
                unsigned spin = 0;
                do {
                    u = ld_word2(src);
                    v = ld_word2(src + NB * VS);
                    if (++spin > SPIN_LIMIT) __trap();
                } while (((u.x ^ tag) | (u.z ^ tag) | (v.x ^ tag) | (v.z ^ tag)) & 1u);
                const float a0 = __uint_as_float(u.x) + __uint_as_float(v.x), a1 = __uint_as_float(u.y) + __uint_as_float(v.y);
                const float a2 = __uint_as_float(u.z) + __uint_as_float(v.z), a3 = __uint_as_float(u.w) + __uint_as_float(v.w);
                *reinterpret_cast<uint32_t*>(smem + SM_QS + j * (DH * 2) + ((col & 7) >> 1) * 96 + (col >> 3) * 4) =
                    pack_bf2((up ? a2 : a0) + shx(up ? a0 : a2, 1), (up ? a3 : a1) + shx(up ? a1 : a3, 1));
                __syncwarp();
                if (lane == 0) mbar_arrive(bar_full + B_QRDY + j * 8);
                if (e == 0 && j == 0) TS(12);
            }
        }
        if (e >= 64) return;
#pragma unroll 1
        for (int b = 0; b < NB; b++) {
            const float4* src = g_oacc + (h * NB + b) * 64 + e;
            uint32_t dst = sb + SM_OF + (e >> 5) * 256 + b * 64 + frag_off(lane), ordy = bar_full + B_ORDY;
            asm volatile("" : "+r"(dst), "+l"(src), "+r"(ordy));
            mbar_wait(bar_full + B_OTRIG + b * 8, 0);
            if (h * NB + b != sg * G + G - 1) settle(P_SETTLE);
            unsigned spin = 0;
            float o0, o1, o2, n;
            do {
                asm volatile("atom.relaxed.gpu.global.add.v4.f32 {%0,%1,%2,%3}, [%4], {%5,%5,%5,%5};"
                             : "=f"(o0), "=f"(o1), "=f"(o2), "=f"(n) : "l"(src), "f"(0.f) : "memory");
                asm volatile("st.shared.u16 [%0], %1;\nst.shared.u16 [%0+512], %2;\nst.shared.u16 [%0+1024], %3;"
                             ::"r"(dst), "h"(__bfloat16_as_ushort(__float2bfloat16_rn(o0))),
                               "h"(__bfloat16_as_ushort(__float2bfloat16_rn(o1))), "h"(__bfloat16_as_ushort(__float2bfloat16_rn(o2))) : "memory");
                if (++spin > SPIN_LIMIT) __trap();
            } while (n != (float)G);
            __syncwarp();
            if (lane == 0) mbar_arrive(ordy);
        }
        return;
    }

    if (warp < NB) {
        uint2 raw[5];
#pragma unroll
        for (int i = 0; i < 5; i++) raw[i] = __ldg(reinterpret_cast<const uint2*>(x + warp * DM) + i * 32 + lane);
        float s = 0.f;
#pragma unroll
        for (int i = 0; i < 5; i++) s += (bf_lo(raw[i].x) + bf_hi(raw[i].x)) + (bf_lo(raw[i].y) + bf_hi(raw[i].y));
#pragma unroll
        for (int o = 16; o; o >>= 1) s += shx(s, o);
        const float mean = s * (1.0f / DM);
        float q2 = 0.f;
#pragma unroll
        for (int i = 0; i < 5; i++) {
            const float d0 = bf_lo(raw[i].x) - mean, d1 = bf_hi(raw[i].x) - mean;
            const float d2 = bf_lo(raw[i].y) - mean, d3 = bf_hi(raw[i].y) - mean;
            q2 += (d0 * d0 + d1 * d1) + (d2 * d2 + d3 * d3);
        }
#pragma unroll
        for (int o = 16; o; o >>= 1) q2 += shx(q2, o);
        const float mb = bf_round(mean);
        const float rs = __frcp_rn(bf_round(__fsqrt_rn(bf_round(bf_round(q2 * (1.0f / DM)) + 1e-5f))));
        const uint32_t k = (lane * 4) & 31;
        unsigned char* dst = smem + SM_XF + warp * 64 +
            (is_att ? (lane >> 3) * 256 + frag_off(k) : (lane >> 2) * 256 + frag_off(k & 15));
        const uint32_t step = is_att ? 1024 : 2048;
#pragma unroll
        for (int i = 0; i < 5; i++) {
            const uint32_t d0 = pack_bf2(bf_lo(raw[i].x) - mb, bf_hi(raw[i].x) - mb);
            const uint32_t d1 = pack_bf2(bf_lo(raw[i].y) - mb, bf_hi(raw[i].y) - mb);
            *reinterpret_cast<uint32_t*>(dst + i * step) = pack_bf2(bf_lo(d0) * rs, bf_hi(d0) * rs);
            *reinterpret_cast<uint32_t*>(dst + i * step + 16) = pack_bf2(bf_lo(d1) * rs, bf_hi(d1) * rs);
        }
    }
    asm volatile("bar.sync 2, %0;" ::"n"(NTHR) : "memory");
    uint32_t tag = (epoch + 1u) & 1u;
    asm volatile("" : "+r"(tag));
    if (tid == 0) TS(3);

    Ring ring{bar_full, sb + SM_RING, 0u, bar_full};
    float lo[3][4], hi[3][4];
    uint32_t off[3];
    const uint32_t a_lane = (g & 3) * 64 + t * 16;

    if (is_att) {
        float* lsum = reinterpret_cast<float*>(smem + SM_LS);
#pragma unroll 1
        for (int j = -1; j <= G; j++) {
            if (j >= 0 && j < G) {
                uint32_t qf[6][4];
                mbar_wait(bar_full + B_QRDY + j * 8, 0);
                if (j == 0 && tid == 0) TS(6);
#pragma unroll
                for (int i = 0; i < 6; i++) lds128(sb + SM_QS + j * (DH * 2) + t * 96 + i * 16, qf[i]);
                const uint32_t key = (warp & 1) * 16 + (lane & 15);
                float sv[NT / 4], m = -INFINITY;
#pragma unroll
                for (int rr = 0; rr < NT / 4; rr++) {
                    const uint32_t item = 5 + max(2 * j - 1, 0) * NT + rr * 4 + (warp >> 1), slot = item % NS;
#pragma unroll
                    for (int s = 0; s < 3; s++)
                        off[s] = sb + SM_RING + slot * SLOT + key * 384 + s * 128 + (((lane >> 4) ^ ((3 * key + s) & 7)) << 4);
                    pin3(off);
                    mbar_wait(bar_full + slot * 8, (item / NS) & 1);
                    float c[3][4] = {};
#pragma unroll
                    for (int dq = 0; dq < 4; dq++)
#pragma unroll
                        for (int s = 0; s < 3; s++) {
                            uint32_t a[4];
                            ldsm_x4(off[s] ^ (dq << 5), a);
                            mma16816(c[s], a, qf[s * 2 + (dq >> 1)][(dq & 1) * 2], qf[s * 2 + (dq >> 1)][(dq & 1) * 2 + 1]);
                        }
                    __syncwarp();
                    if (lane == 0)
                        asm volatile("mbarrier.arrive.shared::cta.b64 _, [%0], %1;" ::"r"(bar_full + (NS + slot) * 8), "n"(NCW / 2) : "memory");
                    const float raw = (t & 1) ? (c[0][2] + c[1][2]) + c[2][2] : (c[0][0] + c[1][0]) + c[2][0];
                    sv[rr] = bf_round(bf_round(raw) * 0.07216878364870323f);
                    m = fmaxf(m, sv[rr]);
                }
                ring.skip(NT);
                if (tid == 0 && j == G - 1) TS(14);
                m = fmaxf(m, shx(m, 1));
#pragma unroll
                for (int o = 4; o < 32; o <<= 1) m = fmaxf(m, shx(m, o));
                if (lane == 0) lsum[8 + warp] = m;
                cons_bar();
                {
                    const float4 m0 = reinterpret_cast<const float4*>(lsum)[2], m1 = reinterpret_cast<const float4*>(lsum)[3];
                    m = fmaxf(fmaxf(fmaxf(m0.x, m0.y), fmaxf(m0.z, m0.w)), fmaxf(fmaxf(m1.x, m1.y), fmaxf(m1.z, m1.w)));
                }
                float l = 0.f;
#pragma unroll
                for (int rr = 0; rr < NT / 4; rr++) {
                    const float p = __expf(sv[rr] - m);
                    l += p;
                    *reinterpret_cast<bf16*>(smem + SM_PF + ((j & 1) * NT + rr * 4 + (warp >> 1)) * 64 + frag_off((warp & 1) * 16 + (t & 1) * 8 + g)) =
                        __float2bfloat16_rn(p);
                }
                l += shx(l, 1);
#pragma unroll
                for (int o = 4; o < 32; o <<= 1) l += shx(l, o);
                if (lane == 0) lsum[warp] = l;
                cons_bar();
                if (tid < 4) {
                    const float4 l0 = reinterpret_cast<const float4*>(lsum)[0], l1 = reinterpret_cast<const float4*>(lsum)[1];
                    st_tag2(g_ml + (pair_of(sg, j) * G + r) * 32 + tid * 2, m,
                            ((l0.x + l0.y) + (l0.z + l0.w)) + ((l1.x + l1.y) + (l1.z + l1.w)), tag);
                    if (tid == 0) mbar_arrive(bar_full + B_WTRIG + (j & 1) * 8);
                }
                if (tid == 0 && j == G - 1) TS(13);
                if (j == 0) continue;
            }
            const bool kv = j >= 0;
            const int pair = pair_of(sg, j - 1);
            uint32_t trig = !kv ? bar_full + B_QTRIG : (pair >> 2) == h ? bar_full + B_OTRIG + (pair & 3) * 8 : 0;
            if (tid != 0) trig = 0;
            float4* oacc = g_oacc + pair * 64 + warp * 8 + 2 * t + g;
            uint32_t wrdy = bar_full + B_WRDY + (~j & 1) * 8;
#pragma unroll
            for (int s = 0; s < 3; s++) off[s] = lane * 384 + s * 128 + ((warp ^ ((3 * lane + s) & 7)) << 4);
            asm volatile("" : "+l"(oacc), "+r"(trig), "+r"(wrdy));
            gemv_loop(ring, kv ? NT : 5, kv ? sb + SM_PF + (~j & 1) * (NT * 64) + t * 16 : sb + SM_XF + qd * 5 * 256 + a_lane,
                      kv ? 64 : 256, off, lo, hi, lane);
            if (kv) {
                mbar_wait(wrdy, ((j - 1) >> 1) & 1);
                const float w = lsum[16 + (~j & 1)];
                if (g < 2)
                    asm volatile("red.relaxed.gpu.global.add.v4.f32 [%0], {%1,%2,%3,%4};"
                                 ::"l"(oacc), "f"(w * (g ? lo[0][1] + hi[0][3] : lo[0][0] + hi[0][2])),
                                   "f"(w * (g ? lo[1][1] + hi[1][3] : lo[1][0] + hi[1][2])),
                                   "f"(w * (g ? lo[2][1] + hi[2][3] : lo[2][0] + hi[2][2])), "f"(1.0f) : "memory");
            } else if (g < NB) {
#pragma unroll
                for (int s = 0; s < 3; s++)
                    st_tag2(g_qpart + (cta * NB + g) * VS + warp * 32 + 2 * t + s * 8, lo[s][0] + hi[s][2], lo[s][1] + hi[s][3], tag);
            }
            if (trig) mbar_arrive(trig);
            if (j == G && tid == 0) TS(5);
            if (j >= 0 && j < G && j != P_DRY) continue;
            if (tid == 0 && j < 0) TS(4);

            {
                const bool pass = j == G;
                constexpr int I0 = 5 + NKV;
                uint32_t b[6][3][4];
#pragma unroll
                for (int s = 0; s < 3; s++) {
                    const uint32_t w64 = lane * 320 + (warp + 8 * s) * 16;
                    off[s] = sb + SM_RING + (w64 ^ (((w64 >> 7) & 3) << 4));
#pragma unroll
                    for (int e = 0; e < 4; e++) { lo[s][e] = 0.f; hi[s][e] = 0.f; }
                }
                const int cell = g * 320 + (qd * 20 + warp) * 4 + t;
                const float4* accp = g_acc + cell;
                uint32_t* outp = reinterpret_cast<uint32_t*>(out) + cell;
                uint32_t live = pass && g < NB, live3 = live && warp < 4, a_addr = sb + SM_OF + a_lane;
                const uint32_t done = bar_full + B_QTRIG;
                uint32_t ordy = pass ? bar_full + B_ORDY : done, fb[6];
#pragma unroll
                for (int i = 0; i < 6; i++) fb[i] = pass ? bar_full + ((I0 + i) % NS) * 8 : done;
                pin3(off);
                asm volatile("" : "+l"(accp), "+l"(outp), "+r"(live), "+r"(live3), "+r"(a_addr), "+r"(ordy), "+r"(fb[3]), "+r"(fb[4]), "+r"(fb[5]));
                uint32_t a[6][4];
#pragma unroll
                for (int i = 0; i < 6; i++) {
                    if (i == P_PRE) {
                        mbar_wait(ordy, 0);
                        if (pass && tid == 0) TS(7);
#pragma unroll
                        for (int k = 0; k < 6; k++) lds128(a_addr + k * 256, a[k]);
                    }
                    mbar_wait(fb[i], pass ? ((I0 + i) / NS) & 1 : 0);
#pragma unroll
                    for (int s = 0; s < 3; s++) ldsm_x4_t(off[s] + ((I0 + i) % NS) * SLOT, b[i][s]);
#pragma unroll
                    for (int k = 0; k < 6; k++)
                        if (i >= P_PRE && (i == P_PRE ? k < i : k == i - 1) || (i == 5 && k == 5)) {
#pragma unroll
                            for (int s = 0; s < 3; s++)
                                if (s < 2 || warp < 4) { mma16816(lo[s], a[k], b[k][s][0], b[k][s][1]); mma16816(hi[s], a[k], b[k][s][2], b[k][s][3]); }
                        }
                }
                if (pass && tid == 0) TS(8);
                float v[3][2];
#pragma unroll
                for (int s = 0; s < 3; s++) { v[s][0] = lo[s][0] + hi[s][2]; v[s][1] = lo[s][1] + hi[s][3]; }
                add_out<3>(accp, outp, v, live, live3, epoch);
            }
        }
        if (tid == 0) { TS(9); TS_DUMP(3, 32); }
    } else {
        float gate[6][2];
#pragma unroll 1
        for (int ps = 0; ps < 4; ps++) {
            const uint32_t row = lane & 15, parts = ps < 2 ? 6 : 5;
#pragma unroll
            for (int s = 0; s < 3; s++) {
                const uint32_t r128 = row * parts + min(2 * s + (lane >> 4), parts - 1);
                off[s] = r128 * 128 + ((warp ^ (r128 & 7)) << 4);
            }
            gemv_loop(ring, ps < 2 ? 40 : 24, sb + (ps < 2 ? SM_XF : SM_HF) + a_lane, 256, off, lo, hi, lane);
            if (ps == 0) {
#pragma unroll
                for (int s = 0; s < 3; s++) {
                    gate[2 * s][0] = lo[s][0]; gate[2 * s][1] = lo[s][1];
                    gate[2 * s + 1][0] = hi[s][0]; gate[2 * s + 1][1] = hi[s][1];
                }
            } else if (ps == 1) {
#pragma unroll
                for (int p = 0; p < 6; p++) {
                    float hv[2];
#pragma unroll
                    for (int e = 0; e < 2; e++) {
                        const float gt = bf_round(gate[p][e]);
                        hv[e] = bf_round(__fdividef(gt, 1.0f + __expf(-gt))) * bf_round((p & 1) ? hi[p >> 1][e] : lo[p >> 1][e]);
                    }
                    if (g < NB)
                        *reinterpret_cast<uint32_t*>(smem + SM_HF + (p * 4 + (warp >> 1)) * 256 + g * 64 + t * 16 + (warp & 1) * 8) =
                            pack_bf2(hv[0], hv[1]);
                }
                cons_bar();
            } else {
                mbar_wait(bar_full + B_ORDY, 0);
                const int cell = g * 320 + ((ps - 2) * 40 + warp) * 4 + t;
                float v[5][2];
#pragma unroll
                for (int p = 0; p < 5; p++) {
                    v[p][0] = (p & 1) ? hi[p >> 1][0] : lo[p >> 1][0];
                    v[p][1] = (p & 1) ? hi[p >> 1][1] : lo[p >> 1][1];
                }
                add_out<5>(g_acc + cell, reinterpret_cast<uint32_t*>(out) + cell, v, g < NB, g < NB, epoch);
            }
        }
        if (tid == 0) { TS(9); TS_DUMP(3, 10); }
    }
}

typedef CUresult (*EncodeFn)(CUtensorMap*, CUtensorMapDataType, cuuint32_t, void*, const cuuint64_t*, const cuuint64_t*,
                             const cuuint32_t*, const cuuint32_t*, CUtensorMapInterleave, CUtensorMapSwizzle,
                             CUtensorMapL2promotion, CUtensorMapFloatOOBfill);

void make_map(EncodeFn enc, CUtensorMap* m, const void* p, uint64_t rows, uint64_t cols, uint32_t inner, uint32_t parts,
              uint32_t box_rows) {
    const cuuint64_t dims[3] = {inner, cols / inner, rows};
    const cuuint64_t strides[2] = {inner * 2ull, cols * 2ull};
    const cuuint32_t box[3] = {inner, parts, box_rows};
    const cuuint32_t es[3] = {1, 1, 1};
    enc(m, CU_TENSOR_MAP_DATA_TYPE_BFLOAT16, 3, const_cast<void*>(p), dims, strides, box, es, CU_TENSOR_MAP_INTERLEAVE_NONE,
        inner == 64 ? CU_TENSOR_MAP_SWIZZLE_128B : CU_TENSOR_MAP_SWIZZLE_64B, CU_TENSOR_MAP_L2_PROMOTION_NONE,
        CU_TENSOR_MAP_FLOAT_OOB_FILL_NONE);
}

}

extern "C" void kernel_launch(void* const* d_in, const int* in_sizes, int n_in, void* d_out, int out_size) {
    (void)in_sizes; (void)n_in; (void)out_size;
    static EncodeFn enc = nullptr;
    if (!enc) {
        void* fn = nullptr;
        cudaDriverEntryPointQueryResult qr;
        cudaGetDriverEntryPoint("cuTensorMapEncodeTiled", &fn, cudaEnableDefault, &qr);
        enc = (EncodeFn)fn;
        cudaFuncSetAttribute(fused_decode_kernel, cudaFuncAttributeMaxDynamicSharedMemorySize, SM_TOTAL);
    }
    Maps maps;
    make_map(enc, &maps.k, d_in[1], (uint64_t)NB * NH * SK, DH, 64, 3, TK);
    make_map(enc, &maps.v, d_in[2], (uint64_t)NB * NH * SK, DH, 64, 3, TK);
    make_map(enc, &maps.wq, d_in[3], DM, NH * DH, 64, 3, 32);
    make_map(enc, &maps.wo, d_in[4], NH * DH, DM, 32, 5, 32);
    make_map(enc, &maps.w1, d_in[6], DM, FF, 64, 6, 16);
    make_map(enc, &maps.w3, d_in[7], DM, FF, 64, 6, 16);
    make_map(enc, &maps.w2, d_in[8], FF, DM, 64, 5, 16);
    fused_decode_kernel<<<NCTA, NTHR, SM_TOTAL>>>(maps, (const bf16*)d_in[0], (bf16*)d_out);
}
```

```cpp
#include <cuda_runtime.h>
#include <cuda.h>
#include <cuda_bf16.h>
#include <stdint.h>

namespace {

typedef __nv_bfloat16 bf16;

constexpr int NB = 4, DM = 640, NH = 32, DH = 192, SK = 8192, WIN = 2048, FF = 1536;

#define P_G 16
#define P_DEPTH 4
#define P_DEPTH_FFN 5
#define P_GAIN 8
#define P_BIAS 16
#define P_SLEEP 500
#define P_DMIN P_DEPTH
#define P_DMAX 6
#define P_SETTLE 3000
#define P_QDELAY 1600
#define P_PRE 3
#define P_WSETTLE 2000
#define P_NSL 20
#define P_DRY (G - 1)
#define P_NS 16

constexpr int G = P_G;
constexpr int TK = 32;
constexpr int NT = WIN / TK / G;
constexpr int NS = P_NS;
constexpr int SLOT = 12288;
constexpr int DEPTH = P_DEPTH;
#define P_D0 5
constexpr int DEPTH0 = P_D0;
static_assert(DEPTH0 <= 5, "DEPTH0");
constexpr int NATT = 128, NFFN = 4, NCTA = NATT + NFFN;
constexpr int NCW = 8;
constexpr int NXW = 3;
constexpr int W_PROD = NCW, W_WGT = NCW + 1 + NXW, W_PACE = W_WGT + 1;
constexpr int NTHR = (W_PACE + 1) * 32;
constexpr int NSRC = NH + NFFN;
constexpr int VS = 256;
#define P_ACS 16
constexpr int ACS = P_ACS;
static_assert(G == 8 || G == 16, "G");

constexpr int SM_RING = 0;
constexpr int SM_XF = SM_RING + NS * SLOT;
constexpr int SM_QS = SM_XF + 20 * 256;
constexpr int SM_PF = SM_QS + G * DH * 2;
constexpr int SM_OF = SM_PF + 2 * NT * 64;
constexpr int SM_LS = SM_OF + 6 * 256;
constexpr int SM_ATT_END = SM_LS + 80;
constexpr int SM_HF = SM_XF + 40 * 256;
constexpr int SM_FFN_END = SM_HF + 12 * 256;
constexpr int SM_BAR = SM_ATT_END > SM_FFN_END ? SM_ATT_END : SM_FFN_END;
constexpr int B_QRDY = 2 * NS * 8, B_ORDY = B_QRDY + G * 8, B_OTRIG = B_ORDY + 8, B_QTRIG = B_OTRIG + 32,
              B_WTRIG = B_QTRIG + 8, B_WRDY = B_WTRIG + 16, NBAR = 2 * NS + G + 10;
constexpr int SM_PACE = SM_BAR + NBAR * 8;
constexpr int SM_TS = SM_PACE + 8;
constexpr int SM_TOTAL = SM_TS + 256;
static_assert(SM_TOTAL <= 232448, "smem");

constexpr int NKV = 2 * NT * G;
constexpr int ITEMS_ATT = 5 + NKV + 6;
constexpr int ITEMS_FFN = 80 + 48;

struct Maps { CUtensorMap k, v, wq, wo, w1, w3, w2; };

struct alignas(32) Sync { unsigned epoch, inits, prog[2]; };
__device__ Sync g_sync;
__device__ __align__(128) float g_qpart[NATT * NB * VS];
__device__ __align__(128) float g_ml[NATT * G * 32];
__device__ __align__(128) float4 g_oacc[NATT * 64];
__device__ __align__(128) float4 g_acc[NB * 4 * NCW * ACS];
#define TS(i)
#define TS_DUMP(lo, hi)

constexpr unsigned SPIN_LIMIT = 1u << 24;

__device__ __forceinline__ void mbar_init(uint32_t bar, int cnt) {
    asm volatile("mbarrier.init.shared::cta.b64 [%0], %1;" ::"r"(bar), "r"(cnt) : "memory");
}
__device__ __forceinline__ void mbar_expect_tx(uint32_t bar, uint32_t bytes) {
    asm volatile("mbarrier.arrive.expect_tx.shared::cta.b64 _, [%0], %1;" ::"r"(bar), "r"(bytes) : "memory");
}
__device__ __forceinline__ void mbar_arrive(uint32_t bar) {
    asm volatile("mbarrier.arrive.shared::cta.b64 _, [%0];" ::"r"(bar) : "memory");
}
__device__ __forceinline__ void mbar_wait(uint32_t bar, uint32_t parity) {
    asm volatile("{\n.reg .pred p, q;\n.reg .u32 n;\nmov.u32 n, 0;\n"
                 "W: mbarrier.try_wait.parity.shared::cta.b64 p, [%0], %1;\n"
                 "@p bra D;\nadd.u32 n, n, 1;\nsetp.lt.u32 q, n, %2;\n@q bra W;\ntrap;\nD:\n}"
                 ::"r"(bar), "r"(parity), "n"(SPIN_LIMIT) : "memory");
}
__device__ __forceinline__ void tma3d(uint32_t dst, const CUtensorMap* map, int c1, int c2, uint32_t bar) {
    const uint64_t pol = 0x12F0000000000000ull;
    asm volatile("cp.async.bulk.tensor.3d.shared::cluster.global.mbarrier::complete_tx::bytes.L2::cache_hint "
                 "[%0], [%1, {%2, %3, %4}], [%5], %6;"
                 ::"r"(dst), "l"(map), "r"(0), "r"(c1), "r"(c2), "r"(bar), "l"(pol) : "memory");
}
__device__ __forceinline__ void ldsm_x4(uint32_t addr, uint32_t (&r)[4]) {
    asm volatile("ldmatrix.sync.aligned.m8n8.x4.shared.b16 {%0,%1,%2,%3}, [%4];"
                 : "=r"(r[0]), "=r"(r[1]), "=r"(r[2]), "=r"(r[3]) : "r"(addr) : "memory");
}
__device__ __forceinline__ void ldsm_x4_t(uint32_t addr, uint32_t (&r)[4]) {
    asm volatile("ldmatrix.sync.aligned.m8n8.x4.trans.shared.b16 {%0,%1,%2,%3}, [%4];"
                 : "=r"(r[0]), "=r"(r[1]), "=r"(r[2]), "=r"(r[3]) : "r"(addr) : "memory");
}
__device__ __forceinline__ void lds128(uint32_t addr, uint32_t (&r)[4]) {
    asm volatile("ld.shared.v4.u32 {%0,%1,%2,%3}, [%4];"
                 : "=r"(r[0]), "=r"(r[1]), "=r"(r[2]), "=r"(r[3]) : "r"(addr) : "memory");
}
__device__ __forceinline__ void mma16816(float (&c)[4], const uint32_t (&a)[4], uint32_t b0, uint32_t b1) {
    asm volatile("mma.sync.aligned.m16n8k16.row.col.f32.bf16.bf16.f32 {%0,%1,%2,%3}, {%4,%5,%6,%7}, {%8,%9}, {%0,%1,%2,%3};"
                 : "+f"(c[0]), "+f"(c[1]), "+f"(c[2]), "+f"(c[3])
                 : "r"(a[0]), "r"(a[1]), "r"(a[2]), "r"(a[3]), "r"(b0), "r"(b1));
}
__device__ __forceinline__ void cons_bar() { asm volatile("bar.sync 1, 256;" ::: "memory"); }

__device__ __forceinline__ float bf_round(float v) { return __bfloat162float(__float2bfloat16_rn(v)); }
__device__ __forceinline__ uint32_t pack_bf2(float lo, float hi) {
    __nv_bfloat162 t = __floats2bfloat162_rn(lo, hi);
    return *reinterpret_cast<uint32_t*>(&t);
}
__device__ __forceinline__ float bf_lo(uint32_t u) { return __uint_as_float(u << 16); }
__device__ __forceinline__ float bf_hi(uint32_t u) { return __uint_as_float(u & 0xffff0000u); }
__device__ __forceinline__ float shx(float v, int o) { return __shfl_xor_sync(0xffffffffu, v, o); }

__device__ __forceinline__ uint32_t frag_off(uint32_t k) {
    return ((k >> 1) & 3) * 16 + ((k >> 3) & 1) * 8 + ((k >> 4) & 1) * 4 + (k & 1) * 2;
}

__device__ __forceinline__ void st_tag2(float* p, float a, float b, uint32_t tag) {
    asm volatile("{\n.reg .b64 w;\n.reg .b32 x;\nlop3.b32 x, %1, 0xfffffffe, %3, 0xea;\nmov.b64 w, {x, %2};\n"
                 "st.relaxed.gpu.global.b64 [%0], w;\n}"
                 ::"l"(p), "r"(__float_as_uint(a)), "r"(__float_as_uint(b)), "r"(tag) : "memory");
}
__device__ __forceinline__ void st_fill4(float* p, uint32_t v) {
    asm volatile("{\n.reg .b64 w;\nmov.b64 w, {%1, %1};\nst.relaxed.gpu.global.v2.b64 [%0], {w, w};\n}" ::"l"(p), "r"(v) : "memory");
}
__device__ __forceinline__ uint2 ld_word(const float* p) {
    uint2 v;
    asm volatile("{\n.reg .b64 w;\nld.relaxed.gpu.global.b64 w, [%2];\nmov.b64 {%0,%1}, w;\n}" : "=r"(v.x), "=r"(v.y) : "l"(p) : "memory");
    return v;
}
__device__ __forceinline__ uint4 ld_word2(const float* p) {
    uint4 v;
    asm volatile("{\n.reg .b64 w0, w1;\nld.relaxed.gpu.global.v2.b64 {w0, w1}, [%4];\nmov.b64 {%0,%1}, w0;\nmov.b64 {%2,%3}, w1;\n}"
                 : "=r"(v.x), "=r"(v.y), "=r"(v.z), "=r"(v.w) : "l"(p) : "memory");
    return v;
}

__device__ __forceinline__ void add_out(const float4* acc, bf16* out, const float (&lo)[3][4], const float (&hi)[3][4],
                                        bool odd, bool third, bool live, uint32_t epoch) {
    const float v0 = odd ? lo[0][1] + hi[0][3] : lo[0][0] + hi[0][2];
    const float v1 = odd ? lo[1][1] + hi[1][3] : lo[1][0] + hi[1][2];
    const float v2 = odd ? lo[2][1] + hi[2][3] : lo[2][0] + hi[2][2];
    float o0, o1, o2, n = 0.f;
    asm volatile("{\n.reg .pred p;\nsetp.ne.u32 p, %5, 0;\n"
                 "@p atom.relaxed.gpu.global.add.v4.f32 {%0,%1,%2,%3}, [%4], {%6,%7,%8,%9};\n}"
                 : "=f"(o0), "=f"(o1), "=f"(o2), "+f"(n)
                 : "l"(acc), "r"((uint32_t)live), "f"(v0), "f"(v1), "f"(v2), "f"(1.0f) : "memory");
    asm volatile("{\n.reg .pred p, q;\nsetp.eq.f32 p, %4, %5;\nsetp.ne.and.u32 q, %6, 0, p;\n"
                 "@p st.global.u16 [%0], %1;\n@p st.global.u16 [%0+128], %2;\n@q st.global.u16 [%0+256], %3;\n}"
                 ::"l"(out), "h"(__bfloat16_as_ushort(__float2bfloat16_rn(o0 + v0))),
                   "h"(__bfloat16_as_ushort(__float2bfloat16_rn(o1 + v1))), "h"(__bfloat16_as_ushort(__float2bfloat16_rn(o2 + v2))),
                   "f"(n), "f"((float)(NSRC - 1)), "r"((uint32_t)third) : "memory");
    if (acc == g_acc && n == (float)(NSRC - 1))
        asm volatile("st.relaxed.gpu.global.u32 [%0], %1;" ::"l"(&g_sync.epoch), "r"(epoch + 1u) : "memory");
}

__device__ __forceinline__ int pair_of(int sg, uint32_t j) { return sg * G + (j % (G / 4)) * 4 + j / (G / 4); }

__device__ __forceinline__ void settle(int cycles) {
    const uint32_t t0 = (uint32_t)clock();
    while ((uint32_t)clock() - t0 < (uint32_t)cycles) __nanosleep(P_NSL);
}

struct Ring {
    uint32_t full, addr, phase, first_full;
    __device__ __forceinline__ void wait() const { mbar_wait(full, phase); }
    __device__ __forceinline__ void skip(int n) {
        full += n * 8; addr += n * SLOT;
        if (full >= first_full + NS * 8) { full -= NS * 8; addr -= NS * SLOT; phase ^= 1; }
    }
    __device__ __forceinline__ void release(int lane) {
        __syncwarp();
        if (lane == 0) mbar_arrive(full + NS * 8);
        full += 8; addr += SLOT;
        if (full == first_full + NS * 8) { full = first_full; addr -= NS * SLOT; phase ^= 1; }
    }
};

__device__ __forceinline__ void pin3(uint32_t (&v)[3]) {
    asm volatile("" : "+r"(v[0]), "+r"(v[1]), "+r"(v[2]));
}
__device__ __forceinline__ void gemv_loop(Ring& ring, int n, uint32_t a_addr, uint32_t a_step, uint32_t (&off)[3],
                                          float (&lo)[3][4], float (&hi)[3][4], int lane) {
    pin3(off);
#pragma unroll
    for (int s = 0; s < 3; s++)
#pragma unroll
        for (int e = 0; e < 4; e++) { lo[s][e] = 0.f; hi[s][e] = 0.f; }
#pragma unroll 1
    for (int it = 0; it < n; it++) {
        uint32_t a[4], b[3][4];
        lds128(a_addr, a);
        a_addr += a_step;
        ring.wait();
#pragma unroll
        for (int s = 0; s < 3; s++) ldsm_x4_t(ring.addr + off[s], b[s]);
#pragma unroll
        for (int s = 0; s < 3; s++) { mma16816(lo[s], a, b[s][0], b[s][1]); mma16816(hi[s], a, b[s][2], b[s][3]); }
        ring.release(lane);
    }
}

__global__ void __launch_bounds__(NTHR, 1)
fused_decode_kernel(const __grid_constant__ Maps maps, const bf16* __restrict__ x, bf16* __restrict__ out) {
    extern __shared__ __align__(1024) unsigned char smem[];
    const uint32_t sb = (uint32_t)__cvta_generic_to_shared(smem);
    const uint32_t bar_full = sb + SM_BAR;
    if (threadIdx.x == 0 && blockIdx.x < NATT) {
        TS(0);
#pragma unroll 1
        for (int i = 0; i < DEPTH0; i++) {
            mbar_init(bar_full + i * 8, 1);
            mbar_expect_tx(bar_full + i * 8, 12288);
            tma3d(sb + SM_RING + i * SLOT, &maps.wq, (blockIdx.x >> 2) * 3, (blockIdx.x & 3) * 160 + i * 32, bar_full + i * 8);
        }
        TS(1);
    }
    unsigned ptid, cta;
    asm volatile("mov.u32 %0, %%tid.x;\nmov.u32 %1, %%ctaid.x;" : "=r"(ptid), "=r"(cta));
    const int tid = ptid < 32 ? ptid + NCW * 32 : ptid < (NCW + 1) * 32 ? ptid - 32 : ptid;
    const int warp = tid >> 5, lane = tid & 31;
    const bool is_att = cta < NATT;
    const int h = cta >> 2, qd = cta & 3;
    const int sg = cta / G, r = cta % G;

    if (warp == NCW) {
        volatile int* pace = reinterpret_cast<volatile int*>(smem + SM_PACE);
        if (lane == 0) {
            if (!is_att) { TS(0); TS(1); }
            pace[0] = 0;
            pace[1] = is_att ? DEPTH : P_DEPTH_FFN;
#pragma unroll
            for (int i = 0; i < NBAR; i++)
                if (i >= DEPTH0 || !is_att)
                mbar_init(bar_full + i * 8, i < NS ? 1 : i < 2 * NS ? NCW : i < 2 * NS + G ? NXW : i == 2 * NS + G && is_att ? 2 * NB : 1);
            asm volatile("fence.mbarrier_init.release.cluster;" ::: "memory");
        }
        __syncwarp();
        asm volatile("bar.arrive 2, %0;" ::"n"(NTHR) : "memory");
        if (lane == 0) {
            const int n_items = is_att ? ITEMS_ATT : ITEMS_FFN;

            asm volatile("prefetch.tensormap [%0];" ::"l"(is_att ? &maps.k : &maps.w3) : "memory");
            asm volatile("prefetch.tensormap [%0];" ::"l"(is_att ? &maps.v : &maps.w2) : "memory");
            asm volatile("prefetch.tensormap [%0];" ::"l"(&maps.wo) : "memory");
#pragma unroll 1
            for (int i = is_att ? DEPTH0 : 0; i < n_items; i++) {
                const CUtensorMap* map;
                int c1, c2;
                uint32_t bytes = 12288;
                if (is_att) {
                    const uint32_t u = i - 5;
                    if (u < NKV) {
                        const uint32_t blk = u / NT;
                        const bool isv = blk == 2 * G - 1 || (blk && !(blk & 1));
                        const int pair = pair_of(sg, isv ? (blk - 1) / 2 : (blk + 1) / 2);
                        map = isv ? &maps.v : &maps.k;
                        c1 = 0;
                        c2 = ((pair & 3) * NH + (pair >> 2)) * SK + (SK - WIN) + ((u % NT) * G + r) * TK;
                    } else if (i < 5) {
                        map = &maps.wq; c1 = h * 3; c2 = qd * 160 + i * 32;
                    } else {
                        map = &maps.wo; c1 = qd * 5; c2 = h * DH + (u - NKV) * 32; bytes = 10240;
                    }
                } else {
                    if (i < 80) {
                        map = i < 40 ? &maps.w1 : &maps.w3; c1 = qd * 6; c2 = (i < 40 ? i : i - 40) * 16;
                    } else {
                        map = &maps.w2; c1 = (i - 80) / 12 * 5; c2 = qd * 384 + (i - 80) % 12 * 32; bytes = 10240;
                    }
                }
                const int depth = pace[1];
                const uint32_t slot = (uint32_t)i % NS, landed = i - depth;
                if (i >= NS) mbar_wait(bar_full + (NS + slot) * 8, ((uint32_t)i / NS - 1) & 1);
                mbar_expect_tx(bar_full + slot * 8, bytes);
                uint32_t dst = sb + SM_RING + slot * SLOT, fb = bar_full + slot * 8;
                asm volatile("" : "+r"(dst), "+r"(fb), "+l"(map), "+r"(c1), "+r"(c2));
                if (i == 4) TS(22);
                if (i >= depth) mbar_wait(bar_full + (landed % NS) * 8, (landed / NS) & 1);
                tma3d(dst, map, c1, c2, fb);
                if (i == 4) TS(23);
                if (i == 5) TS(30);
                if (i == 8) TS(31);
                pace[0] = landed + 1;
            }
        }
        return;
    }

    const int g = lane >> 2, t = lane & 3;
    uint32_t epoch;
    asm volatile("ld.relaxed.gpu.global.u32 %0, [%1];" : "=r"(epoch) : "l"(&g_sync.epoch) : "memory");

    if (warp == W_PACE) {
        asm volatile("bar.sync 2, %0;" ::"n"(NTHR) : "memory");
        if (lane == 0 && is_att && P_GAIN) {
            volatile int* pace = reinterpret_cast<volatile int*>(smem + SM_PACE);
            if (cta == 0) asm volatile("st.relaxed.gpu.global.u32 [%0], %1;" ::"l"(&g_sync.prog[epoch & 1u]), "r"(0u) : "memory");
            unsigned* prog = &g_sync.prog[~epoch & 1u];
            int reported = 0;
#pragma unroll 1
            for (int it = 0; it < 4096; it++) {
                const int landed = pace[0];
                if (landed >= NKV + 5 - P_DMAX) break;
                int sum;
                asm volatile("atom.relaxed.gpu.global.add.u32 %0, [%1], %2;" : "=r"(sum) : "l"(prog), "r"(landed - reported) : "memory");
                reported = landed;
                const int lag16 = sum / (NATT / 16) - landed * 16 + P_BIAS;
                pace[1] = min(max(DEPTH + ((lag16 * P_GAIN + 128) >> 8), P_DMIN), P_DMAX);
                __nanosleep(P_SLEEP);
            }
        }
        return;
    }
    if (warp == W_WGT) {
        const uint32_t tag = (epoch + 1u) & 1u;
        if (is_att && lane < 2 * G) st_fill4(g_ml + ((sg * G + (lane >> 1)) * G + r) * 32 + (lane & 1) * 4, tag ^ 1u);
        asm volatile("bar.sync 2, %0;" ::"n"(NTHR) : "memory");
        if (lane == 0) asm volatile("red.release.gpu.global.add.u32 [%0], 1;" ::"l"(&g_sync.inits) : "memory");
        __syncwarp();
#pragma unroll 1
        for (int j = 0; j < G; j++) {
            if (is_att) mbar_wait(bar_full + B_WTRIG + (j & 1) * 8, (j >> 1) & 1);
            settle(P_WSETTLE);
            unsigned spin = 0;
            if (j == 0) {
                unsigned n;
                do {
                    asm volatile("ld.acquire.gpu.global.u32 %0, [%1];" : "=r"(n) : "l"(&g_sync.inits) : "memory");
                    if (++spin > SPIN_LIMIT) __trap();
                } while (n != (epoch + 1u) * NCTA);
                if (!is_att) {
                    if (lane == 0) mbar_arrive(bar_full + B_ORDY);
                    return;
                }
            }
            const float* src = g_ml + (pair_of(sg, j) * G + lane % G) * 32;
            uint2 ml;
            do {
                ml = ld_word(src);
                if (++spin > SPIN_LIMIT) __trap();
            } while ((ml.x ^ tag) & 1u);
            const float mk = __uint_as_float(ml.x & ~1u);
            float M = mk;
#pragma unroll
            for (int o = G / 2; o; o >>= 1) M = fmaxf(M, shx(M, o));
            const float w = __expf(mk - M);
            float L = w * __uint_as_float(ml.y);
#pragma unroll
            for (int o = G / 2; o; o >>= 1) L += shx(L, o);
            if (lane == r) {
                reinterpret_cast<float*>(smem + SM_LS)[16 + (j & 1)] = __fdividef(w, L);
                mbar_arrive(bar_full + B_WRDY + (j & 1) * 8);
                if (j == G - 1) TS(11);
            }
        }
        return;
    }
    if (warp > W_PROD) {
        const uint32_t tag = (epoch + 1u) & 1u;
        const int e = tid - (W_PROD + 1) * 32;
        if (is_att) {
#pragma unroll
            for (int i = 0; i < 2; i++)
                st_fill4(g_qpart + (cta * NB + i * 2 + e / 48) * VS + (e % 48) / 6 * 32 + (e % 6) * 4, tag ^ 1u);
            if (e < 64) st_fill4(reinterpret_cast<float*>(g_oacc + cta * 64 + e), 0u);
        } else {
#pragma unroll 1
            for (int c = e; c < 256; c += NXW * 32) {
                const bf16* xp = x + qd * DM + (c >> 6) * 160 + ((c >> 3) & 7) * 8 + (c & 3) * 2 + ((c >> 2) & 1);
                asm volatile("st.relaxed.gpu.global.v4.f32 [%0], {%1,%2,%3,%4};"
                             ::"l"(g_acc + (qd * 32 + (c >> 3)) * ACS + (c & 7)), "f"(__bfloat162float(xp[0])),
                               "f"(__bfloat162float(xp[64])), "f"((c & 32) ? 0.f : __bfloat162float(xp[128])), "f"(0.f) : "memory");
            }
        }
        asm volatile("bar.sync 2, %0;" ::"n"(NTHR) : "memory");
        if (!is_att) return;
        {
            const uint32_t xw = (e >> 1) / 6, xr = (e >> 1) % 6, up = e & 1;
            const uint32_t col = (xr >> 1) * 64 + xw * 8 + (xr & 1) * 4 + up * 2;
            mbar_wait(bar_full + B_QTRIG, 0);
            if (e == 0) TS(10);
            settle(P_QDELAY);
#pragma unroll 1
            for (int j = 0; j < G; j++) {
                const int pair = pair_of(sg, j);
                const float* src = g_qpart + (((pair >> 2) * 4 + up * 2) * NB + (pair & 3)) * VS + xw * 32 + xr * 4;
                uint4 u, v;
                unsigned spin = 0;
                do {
                    u = ld_word2(src);
                    v = ld_word2(src + NB * VS);
                    if (++spin > SPIN_LIMIT) __trap();
                } while (((u.x ^ tag) | (u.z ^ tag) | (v.x ^ tag) | (v.z ^ tag)) & 1u);
                const float a0 = __uint_as_float(u.x) + __uint_as_float(v.x), a1 = __uint_as_float(u.y) + __uint_as_float(v.y);
                const float a2 = __uint_as_float(u.z) + __uint_as_float(v.z), a3 = __uint_as_float(u.w) + __uint_as_float(v.w);
                *reinterpret_cast<uint32_t*>(smem + SM_QS + j * (DH * 2) + ((col & 7) >> 1) * 96 + (col >> 3) * 4) =
                    pack_bf2((up ? a2 : a0) + shx(up ? a0 : a2, 1), (up ? a3 : a1) + shx(up ? a1 : a3, 1));
                __syncwarp();
                if (lane == 0) mbar_arrive(bar_full + B_QRDY + j * 8);
                if (e == 0 && j == 0) TS(12);
            }
        }
        if (e >= 64) return;
#pragma unroll 1
        for (int b = 0; b < NB; b++) {
            const float4* src = g_oacc + (h * NB + b) * 64 + e;
            uint32_t dst = sb + SM_OF + (e >> 5) * 256 + b * 64 + frag_off(lane), ordy = bar_full + B_ORDY;
            asm volatile("" : "+r"(dst), "+l"(src), "+r"(ordy));
            mbar_wait(bar_full + B_OTRIG + b * 8, 0);
            if (h * NB + b != sg * G + G - 1) settle(P_SETTLE);
            unsigned spin = 0;
            float o0, o1, o2, n;
            do {
                asm volatile("atom.relaxed.gpu.global.add.v4.f32 {%0,%1,%2,%3}, [%4], {%5,%5,%5,%5};"
                             : "=f"(o0), "=f"(o1), "=f"(o2), "=f"(n) : "l"(src), "f"(0.f) : "memory");
                asm volatile("st.shared.u16 [%0], %1;\nst.shared.u16 [%0+512], %2;\nst.shared.u16 [%0+1024], %3;"
                             ::"r"(dst), "h"(__bfloat16_as_ushort(__float2bfloat16_rn(o0))),
                               "h"(__bfloat16_as_ushort(__float2bfloat16_rn(o1))), "h"(__bfloat16_as_ushort(__float2bfloat16_rn(o2))) : "memory");
                if (++spin > SPIN_LIMIT) __trap();
            } while (n != (float)G);
            __syncwarp();
            if (lane == 0) mbar_arrive(ordy);
        }
        return;
    }

    if (warp < NB) {
        uint2 raw[5];
#pragma unroll
        for (int i = 0; i < 5; i++) raw[i] = __ldg(reinterpret_cast<const uint2*>(x + warp * DM) + i * 32 + lane);
        float s = 0.f;
#pragma unroll
        for (int i = 0; i < 5; i++) s += (bf_lo(raw[i].x) + bf_hi(raw[i].x)) + (bf_lo(raw[i].y) + bf_hi(raw[i].y));
#pragma unroll
        for (int o = 16; o; o >>= 1) s += shx(s, o);
        const float mean = s * (1.0f / DM);
        float q2 = 0.f;
#pragma unroll
        for (int i = 0; i < 5; i++) {
            const float d0 = bf_lo(raw[i].x) - mean, d1 = bf_hi(raw[i].x) - mean;
            const float d2 = bf_lo(raw[i].y) - mean, d3 = bf_hi(raw[i].y) - mean;
            q2 += (d0 * d0 + d1 * d1) + (d2 * d2 + d3 * d3);
        }
#pragma unroll
        for (int o = 16; o; o >>= 1) q2 += shx(q2, o);
        const float mb = bf_round(mean);
        const float rs = __frcp_rn(bf_round(__fsqrt_rn(bf_round(bf_round(q2 * (1.0f / DM)) + 1e-5f))));
        const uint32_t k = (lane * 4) & 31;
        unsigned char* dst = smem + SM_XF + warp * 64 +
            (is_att ? (lane >> 3) * 256 + frag_off(k) : (lane >> 2) * 256 + frag_off(k & 15));
        const uint32_t step = is_att ? 1024 : 2048;
#pragma unroll
        for (int i = 0; i < 5; i++) {
            const uint32_t d0 = pack_bf2(bf_lo(raw[i].x) - mb, bf_hi(raw[i].x) - mb);
            const uint32_t d1 = pack_bf2(bf_lo(raw[i].y) - mb, bf_hi(raw[i].y) - mb);
            *reinterpret_cast<uint32_t*>(dst + i * step) = pack_bf2(bf_lo(d0) * rs, bf_hi(d0) * rs);
            *reinterpret_cast<uint32_t*>(dst + i * step + 16) = pack_bf2(bf_lo(d1) * rs, bf_hi(d1) * rs);
        }
    }
    asm volatile("bar.sync 2, %0;" ::"n"(NTHR) : "memory");
    uint32_t tag = (epoch + 1u) & 1u;
    asm volatile("" : "+r"(tag));
    if (tid == 0) TS(3);

    Ring ring{bar_full, sb + SM_RING, 0u, bar_full};
    float lo[3][4], hi[3][4];
    uint32_t off[3];
    const uint32_t a_lane = (g & 3) * 64 + t * 16;

    if (is_att) {
        float* lsum = reinterpret_cast<float*>(smem + SM_LS);
#pragma unroll 1
        for (int j = -1; j <= G; j++) {
            if (j >= 0 && j < G) {
                uint32_t qf[6][4];
                mbar_wait(bar_full + B_QRDY + j * 8, 0);
                if (j == 0 && tid == 0) TS(6);
#pragma unroll
                for (int i = 0; i < 6; i++) lds128(sb + SM_QS + j * (DH * 2) + t * 96 + i * 16, qf[i]);
                const uint32_t key = (warp & 1) * 16 + (lane & 15);
                float sv[NT / 4], m = -INFINITY;
#pragma unroll
                for (int rr = 0; rr < NT / 4; rr++) {
                    const uint32_t item = 5 + max(2 * j - 1, 0) * NT + rr * 4 + (warp >> 1), slot = item % NS;
#pragma unroll
                    for (int s = 0; s < 3; s++)
                        off[s] = sb + SM_RING + slot * SLOT + key * 384 + s * 128 + (((lane >> 4) ^ ((3 * key + s) & 7)) << 4);
                    pin3(off);
                    mbar_wait(bar_full + slot * 8, (item / NS) & 1);
                    float c[3][4] = {};
#pragma unroll
                    for (int dq = 0; dq < 4; dq++)
#pragma unroll
                        for (int s = 0; s < 3; s++) {
                            uint32_t a[4];
                            ldsm_x4(off[s] ^ (dq << 5), a);
                            mma16816(c[s], a, qf[s * 2 + (dq >> 1)][(dq & 1) * 2], qf[s * 2 + (dq >> 1)][(dq & 1) * 2 + 1]);
                        }
                    __syncwarp();
                    if (lane == 0)
                        asm volatile("mbarrier.arrive.shared::cta.b64 _, [%0], %1;" ::"r"(bar_full + (NS + slot) * 8), "n"(NCW / 2) : "memory");
                    const float raw = (t & 1) ? (c[0][2] + c[1][2]) + c[2][2] : (c[0][0] + c[1][0]) + c[2][0];
                    sv[rr] = bf_round(bf_round(raw) * 0.07216878364870323f);
                    m = fmaxf(m, sv[rr]);
                }
                ring.skip(NT);
                if (tid == 0 && j == G - 1) TS(14);
                m = fmaxf(m, shx(m, 1));
#pragma unroll
                for (int o = 4; o < 32; o <<= 1) m = fmaxf(m, shx(m, o));
                if (lane == 0) lsum[8 + warp] = m;
                cons_bar();
                {
                    const float4 m0 = reinterpret_cast<const float4*>(lsum)[2], m1 = reinterpret_cast<const float4*>(lsum)[3];
                    m = fmaxf(fmaxf(fmaxf(m0.x, m0.y), fmaxf(m0.z, m0.w)), fmaxf(fmaxf(m1.x, m1.y), fmaxf(m1.z, m1.w)));
                }
                float l = 0.f;
#pragma unroll
                for (int rr = 0; rr < NT / 4; rr++) {
                    const float p = __expf(sv[rr] - m);
                    l += p;
                    *reinterpret_cast<bf16*>(smem + SM_PF + ((j & 1) * NT + rr * 4 + (warp >> 1)) * 64 + frag_off((warp & 1) * 16 + (t & 1) * 8 + g)) =
                        __float2bfloat16_rn(p);
                }
                l += shx(l, 1);
#pragma unroll
                for (int o = 4; o < 32; o <<= 1) l += shx(l, o);
                if (lane == 0) lsum[warp] = l;
                cons_bar();
                if (tid < 4) {
                    const float4 l0 = reinterpret_cast<const float4*>(lsum)[0], l1 = reinterpret_cast<const float4*>(lsum)[1];
                    st_tag2(g_ml + (pair_of(sg, j) * G + r) * 32 + tid * 2, m,
                            ((l0.x + l0.y) + (l0.z + l0.w)) + ((l1.x + l1.y) + (l1.z + l1.w)), tag);
                    if (tid == 0) mbar_arrive(bar_full + B_WTRIG + (j & 1) * 8);
                }
                if (tid == 0 && j == G - 1) TS(13);
                if (j == 0) continue;
            }
            const bool kv = j >= 0;
            const int pair = pair_of(sg, j - 1);
            uint32_t trig = !kv ? bar_full + B_QTRIG : (pair >> 2) == h ? bar_full + B_OTRIG + (pair & 3) * 8 : 0;
            if (tid != 0) trig = 0;
            float4* oacc = g_oacc + pair * 64 + warp * 8 + 2 * t + g;
            uint32_t wrdy = bar_full + B_WRDY + (~j & 1) * 8;
#pragma unroll
            for (int s = 0; s < 3; s++) off[s] = lane * 384 + s * 128 + ((warp ^ ((3 * lane + s) & 7)) << 4);
            asm volatile("" : "+l"(oacc), "+r"(trig), "+r"(wrdy));
            gemv_loop(ring, kv ? NT : 5, kv ? sb + SM_PF + (~j & 1) * (NT * 64) + t * 16 : sb + SM_XF + qd * 5 * 256 + a_lane,
                      kv ? 64 : 256, off, lo, hi, lane);
            if (kv) {
                mbar_wait(wrdy, ((j - 1) >> 1) & 1);
                const float w = lsum[16 + (~j & 1)];
                if (g < 2)
                    asm volatile("red.relaxed.gpu.global.add.v4.f32 [%0], {%1,%2,%3,%4};"
                                 ::"l"(oacc), "f"(w * (g ? lo[0][1] + hi[0][3] : lo[0][0] + hi[0][2])),
                                   "f"(w * (g ? lo[1][1] + hi[1][3] : lo[1][0] + hi[1][2])),
                                   "f"(w * (g ? lo[2][1] + hi[2][3] : lo[2][0] + hi[2][2])), "f"(1.0f) : "memory");
            } else if (g < NB) {
#pragma unroll
                for (int s = 0; s < 3; s++)
                    st_tag2(g_qpart + (cta * NB + g) * VS + warp * 32 + 2 * t + s * 8, lo[s][0] + hi[s][2], lo[s][1] + hi[s][3], tag);
            }
            if (trig) mbar_arrive(trig);
            if (j == G && tid == 0) TS(5);
            if (j >= 0 && j < G && j != P_DRY) continue;
            if (tid == 0 && j < 0) TS(4);

            {
                const bool pass = j == G;
                constexpr int I0 = 5 + NKV;
                uint32_t b[6][3][4];
#pragma unroll
                for (int s = 0; s < 3; s++) {
                    const uint32_t w64 = lane * 320 + (warp + 8 * s) * 16;
                    off[s] = sb + SM_RING + (w64 ^ (((w64 >> 7) & 3) << 4));
#pragma unroll
                    for (int e = 0; e < 4; e++) { lo[s][e] = 0.f; hi[s][e] = 0.f; }
                }
                const float4* accp = g_acc + (((g & 3) * 4 + qd) * NCW + warp) * ACS + (g >> 2) * 4 + t;
                bf16* outp = out + (g & 3) * DM + qd * 160 + warp * 8 + 2 * t + (g >> 2);
                uint32_t a_addr = sb + SM_OF + a_lane;
                const uint32_t done = bar_full + B_QTRIG;
                uint32_t ordy = pass ? bar_full + B_ORDY : done, fb[6];
#pragma unroll
                for (int i = 0; i < 6; i++) fb[i] = pass ? bar_full + ((I0 + i) % NS) * 8 : done;
                pin3(off);
                asm volatile("" : "+l"(accp), "+l"(outp), "+r"(a_addr), "+r"(ordy), "+r"(fb[3]), "+r"(fb[4]), "+r"(fb[5]));
                uint32_t a[6][4];
#pragma unroll
                for (int i = 0; i < 6; i++) {
                    if (i == P_PRE) {
                        mbar_wait(ordy, 0);
                        if (pass && tid == 0) TS(7);
#pragma unroll
                        for (int k = 0; k < 6; k++) lds128(a_addr + k * 256, a[k]);
                    }
                    mbar_wait(fb[i], pass ? ((I0 + i) / NS) & 1 : 0);
#pragma unroll
                    for (int s = 0; s < 3; s++) ldsm_x4_t(off[s] + ((I0 + i) % NS) * SLOT, b[i][s]);
#pragma unroll
                    for (int k = 0; k < 6; k++)
                        if (i >= P_PRE && (i == P_PRE ? k < i : k == i - 1) || (i == 5 && k == 5)) {
#pragma unroll
                            for (int s = 0; s < 3; s++)
                                if (s < 2 || warp < 4) { mma16816(lo[s], a[k], b[k][s][0], b[k][s][1]); mma16816(hi[s], a[k], b[k][s][2], b[k][s][3]); }
                        }
                }
                if (pass && tid == 0) TS(8);
                add_out(accp, outp, lo, hi, g >= NB, warp < 4, pass, epoch);
            }
        }
        if (tid == 0) { TS(9); TS_DUMP(3, 32); }
    } else {
        float gate[6][2];
#pragma unroll 1
        for (int ps = 0; ps < 6; ps++) {
#pragma unroll
            for (int s = 0; s < 3; s++) {
                const uint32_t r128 = (lane & 15) * 6 + 2 * s + (lane >> 4), w64 = lane * 320 + (warp + 8 * s) * 16;
                off[s] = ps < 2 ? r128 * 128 + ((warp ^ (r128 & 7)) << 4) : w64 ^ (((w64 >> 7) & 3) << 4);
            }
            gemv_loop(ring, ps < 2 ? 40 : 12, sb + (ps < 2 ? SM_XF : SM_HF) + a_lane, 256, off, lo, hi, lane);
            if (ps == 0) {
#pragma unroll
                for (int s = 0; s < 3; s++) {
                    gate[2 * s][0] = lo[s][0]; gate[2 * s][1] = lo[s][1];
                    gate[2 * s + 1][0] = hi[s][0]; gate[2 * s + 1][1] = hi[s][1];
                }
            } else if (ps == 1) {
#pragma unroll
                for (int p = 0; p < 6; p++) {
                    float hv[2];
#pragma unroll
                    for (int e = 0; e < 2; e++) {
                        const float gt = bf_round(gate[p][e]);
                        hv[e] = bf_round(__fdividef(gt, 1.0f + __expf(-gt))) * bf_round((p & 1) ? hi[p >> 1][e] : lo[p >> 1][e]);
                    }
                    if (g < NB)
                        *reinterpret_cast<uint32_t*>(smem + SM_HF + (p * 2 + (warp >> 2)) * 256 + g * 64 + frag_off((warp & 3) * 8 + 2 * t)) =
                            pack_bf2(hv[0], hv[1]);
                }
                cons_bar();
            } else {
                mbar_wait(bar_full + B_ORDY, 0);
                if (warp >= 4) lo[2][0] = lo[2][1] = hi[2][2] = hi[2][3] = 0.f;
                add_out(g_acc + (((g & 3) * 4 + ps - 2) * NCW + warp) * ACS + (g >> 2) * 4 + t,
                        out + (g & 3) * DM + (ps - 2) * 160 + warp * 8 + 2 * t + (g >> 2), lo, hi, g >= NB, warp < 4, true, epoch);
            }
        }
        if (tid == 0) { TS(9); TS_DUMP(3, 10); }
    }
}

typedef CUresult (*EncodeFn)(CUtensorMap*, CUtensorMapDataType, cuuint32_t, void*, const cuuint64_t*, const cuuint64_t*,
                             const cuuint32_t*, const cuuint32_t*, CUtensorMapInterleave, CUtensorMapSwizzle,
                             CUtensorMapL2promotion, CUtensorMapFloatOOBfill);

void make_map(EncodeFn enc, CUtensorMap* m, const void* p, uint64_t rows, uint64_t cols, uint32_t inner, uint32_t parts,
              uint32_t box_rows) {
    const cuuint64_t dims[3] = {inner, cols / inner, rows};
    const cuuint64_t strides[2] = {inner * 2ull, cols * 2ull};
    const cuuint32_t box[3] = {inner, parts, box_rows};
    const cuuint32_t es[3] = {1, 1, 1};
    enc(m, CU_TENSOR_MAP_DATA_TYPE_BFLOAT16, 3, const_cast<void*>(p), dims, strides, box, es, CU_TENSOR_MAP_INTERLEAVE_NONE,
        inner == 64 ? CU_TENSOR_MAP_SWIZZLE_128B : CU_TENSOR_MAP_SWIZZLE_64B, CU_TENSOR_MAP_L2_PROMOTION_NONE,
        CU_TENSOR_MAP_FLOAT_OOB_FILL_NONE);
}

}

extern "C" void kernel_launch(void* const* d_in, const int* in_sizes, int n_in, void* d_out, int out_size) {
    (void)in_sizes; (void)n_in; (void)out_size;
    static EncodeFn enc = nullptr;
    if (!enc) {
        void* fn = nullptr;
        cudaDriverEntryPointQueryResult qr;
        cudaGetDriverEntryPoint("cuTensorMapEncodeTiled", &fn, cudaEnableDefault, &qr);
        enc = (EncodeFn)fn;
        cudaFuncSetAttribute(fused_decode_kernel, cudaFuncAttributeMaxDynamicSharedMemorySize, SM_TOTAL);
    }
    Maps maps;
    make_map(enc, &maps.k, d_in[1], (uint64_t)NB * NH * SK, DH, 64, 3, TK);
    make_map(enc, &maps.v, d_in[2], (uint64_t)NB * NH * SK, DH, 64, 3, TK);
    make_map(enc, &maps.wq, d_in[3], DM, NH * DH, 64, 3, 32);
    make_map(enc, &maps.wo, d_in[4], NH * DH, DM, 32, 5, 32);
    make_map(enc, &maps.w1, d_in[6], DM, FF, 64, 6, 16);
    make_map(enc, &maps.w3, d_in[7], DM, FF, 64, 6, 16);
    make_map(enc, &maps.w2, d_in[8], FF, DM, 32, 5, 32);
    fused_decode_kernel<<<NCTA, NTHR, SM_TOTAL>>>(maps, (const bf16*)d_in[0], (bf16*)d_out);
}
```

```cpp
#include <cuda_runtime.h>
#include <cuda.h>
#include <cuda_bf16.h>
#include <stdint.h>

namespace {

typedef __nv_bfloat16 bf16;

constexpr int NB = 4, DM = 640, NH = 32, DH = 192, SK = 8192, WIN = 2048, FF = 1536;

#define P_G 16
#define P_DEPTH 4
#define P_DEPTH_FFN 5
#define P_GAIN 8
#define P_BIAS 16
#define P_SLEEP 500
#define P_DMIN P_DEPTH
#define P_DMAX 6
#define P_SETTLE 3000
#define P_QDELAY 1600
#define P_PRE 6
#define P_NSL 20
#define P_DRY (G - 1)
#define P_FLUSH 112
#define P_PRE0 0
#define P_NS 16

constexpr int G = P_G;
constexpr int TK = 32;
constexpr int NT = WIN / TK / G;
constexpr int NS = P_NS;
constexpr int SLOT = 12288;
constexpr int DEPTH = P_DEPTH;
#define P_D0 5
constexpr int DEPTH0 = P_D0;
static_assert(DEPTH0 <= 5, "DEPTH0");
constexpr int NATT = 128, NFFN = 4, NCTA = NATT + NFFN;
constexpr int NCW = 8;
constexpr int NXW = 2;
constexpr int W_PROD = NCW, W_PACE = NCW + 1 + NXW;
constexpr int NTHR = (W_PACE + 1) * 32;
constexpr int NSRC = NH;
constexpr int VS = 256;
#define P_ACS 16
constexpr int ACS = P_ACS;
static_assert(G == 8 || G == 16, "G");

constexpr int SM_RING = 0;
constexpr int SM_XF = SM_RING + NS * SLOT;
constexpr int SM_QS = SM_XF + 20 * 256;
constexpr int SM_PF = SM_QS + G * DH * 2;
constexpr int SM_OF = SM_PF + 2 * NT * 64;
constexpr int SM_HF = SM_OF + 6 * 256;
constexpr int SM_LS = SM_HF + 2 * 256;
constexpr int SM_ATT_END = SM_LS + 80;
constexpr int SM_FFN_END = SM_XF + 40 * 256;
constexpr int SM_BAR = SM_ATT_END > SM_FFN_END ? SM_ATT_END : SM_FFN_END;
constexpr int B_QRDY = 2 * NS * 8, B_ORDY = B_QRDY + G * 8, B_OTRIG = B_ORDY + 8, B_QTRIG = B_OTRIG + 32,
              B_WTRIG = B_QTRIG + 8, B_WRDY = B_WTRIG + 16, B_HRDY = B_WRDY + 16, NBAR = 2 * NS + G + 11;
constexpr int SM_PACE = SM_BAR + NBAR * 8;
constexpr int SM_TS = SM_PACE + 8;
constexpr int SM_TOTAL = SM_TS + 256;
static_assert(SM_TOTAL <= 232448, "smem");

constexpr int NKV = 2 * NT * G;
constexpr int ITEMS_ATT = 5 + NKV + 2 + 6;
constexpr int ITEMS_FFN = 80;

struct Maps { CUtensorMap k, v, wq, wo, w1, w3, w2; };

struct alignas(32) Sync { unsigned epoch, inits, prog[2]; };
__device__ Sync g_sync;
__device__ __align__(128) float g_qpart[NATT * NB * VS];
__device__ __align__(128) float g_ml[NATT * G * 32];
__device__ __align__(128) float g_h[NB * FF];
__device__ __align__(128) float4 g_oacc[NATT * 64];
__device__ __align__(128) float4 g_acc[NB * 4 * NCW * ACS];
#define TS(i)
#define TS_DUMP(lo, hi)

constexpr unsigned SPIN_LIMIT = 1u << 24;

__device__ __forceinline__ void mbar_init(uint32_t bar, int cnt) {
    asm volatile("mbarrier.init.shared::cta.b64 [%0], %1;" ::"r"(bar), "r"(cnt) : "memory");
}
__device__ __forceinline__ void mbar_expect_tx(uint32_t bar, uint32_t bytes) {
    asm volatile("mbarrier.arrive.expect_tx.shared::cta.b64 _, [%0], %1;" ::"r"(bar), "r"(bytes) : "memory");
}
__device__ __forceinline__ void mbar_arrive(uint32_t bar) {
    asm volatile("mbarrier.arrive.shared::cta.b64 _, [%0];" ::"r"(bar) : "memory");
}
__device__ __forceinline__ void mbar_wait(uint32_t bar, uint32_t parity) {
    asm volatile("{\n.reg .pred p, q;\n.reg .u32 n;\nmov.u32 n, 0;\n"
                 "W: mbarrier.try_wait.parity.shared::cta.b64 p, [%0], %1;\n"
                 "@p bra D;\nadd.u32 n, n, 1;\nsetp.lt.u32 q, n, %2;\n@q bra W;\ntrap;\nD:\n}"
                 ::"r"(bar), "r"(parity), "n"(SPIN_LIMIT) : "memory");
}
__device__ __forceinline__ bool mbar_test(uint32_t bar, uint32_t parity) {
    uint32_t ok;
    asm volatile("{\n.reg .pred p;\nmbarrier.test_wait.parity.shared::cta.b64 p, [%1], %2;\nselp.u32 %0, 1, 0, p;\n}"
                 : "=r"(ok) : "r"(bar), "r"(parity) : "memory");
    return ok;
}
__device__ __forceinline__ void tma3d(uint32_t dst, const CUtensorMap* map, int c1, int c2, uint32_t bar) {
    const uint64_t pol = 0x12F0000000000000ull;
    asm volatile("cp.async.bulk.tensor.3d.shared::cluster.global.mbarrier::complete_tx::bytes.L2::cache_hint "
                 "[%0], [%1, {%2, %3, %4}], [%5], %6;"
                 ::"r"(dst), "l"(map), "r"(0), "r"(c1), "r"(c2), "r"(bar), "l"(pol) : "memory");
}
__device__ __forceinline__ void ldsm_x4(uint32_t addr, uint32_t (&r)[4]) {
    asm volatile("ldmatrix.sync.aligned.m8n8.x4.shared.b16 {%0,%1,%2,%3}, [%4];"
                 : "=r"(r[0]), "=r"(r[1]), "=r"(r[2]), "=r"(r[3]) : "r"(addr) : "memory");
}
__device__ __forceinline__ void ldsm_x4_t(uint32_t addr, uint32_t (&r)[4]) {
    asm volatile("ldmatrix.sync.aligned.m8n8.x4.trans.shared.b16 {%0,%1,%2,%3}, [%4];"
                 : "=r"(r[0]), "=r"(r[1]), "=r"(r[2]), "=r"(r[3]) : "r"(addr) : "memory");
}
__device__ __forceinline__ void lds128(uint32_t addr, uint32_t (&r)[4]) {
    asm volatile("ld.shared.v4.u32 {%0,%1,%2,%3}, [%4];"
                 : "=r"(r[0]), "=r"(r[1]), "=r"(r[2]), "=r"(r[3]) : "r"(addr) : "memory");
}
__device__ __forceinline__ void mma16816(float (&c)[4], const uint32_t (&a)[4], uint32_t b0, uint32_t b1) {
    asm volatile("mma.sync.aligned.m16n8k16.row.col.f32.bf16.bf16.f32 {%0,%1,%2,%3}, {%4,%5,%6,%7}, {%8,%9}, {%0,%1,%2,%3};"
                 : "+f"(c[0]), "+f"(c[1]), "+f"(c[2]), "+f"(c[3])
                 : "r"(a[0]), "r"(a[1]), "r"(a[2]), "r"(a[3]), "r"(b0), "r"(b1));
}
__device__ __forceinline__ void cons_bar() { asm volatile("bar.sync 1, 256;" ::: "memory"); }

__device__ __forceinline__ float bf_round(float v) { return __bfloat162float(__float2bfloat16_rn(v)); }
__device__ __forceinline__ uint32_t pack_bf2(float lo, float hi) {
    __nv_bfloat162 t = __floats2bfloat162_rn(lo, hi);
    return *reinterpret_cast<uint32_t*>(&t);
}
__device__ __forceinline__ float bf_lo(uint32_t u) { return __uint_as_float(u << 16); }
__device__ __forceinline__ float bf_hi(uint32_t u) { return __uint_as_float(u & 0xffff0000u); }
__device__ __forceinline__ float shx(float v, int o) { return __shfl_xor_sync(0xffffffffu, v, o); }

__device__ __forceinline__ uint32_t frag_off(uint32_t k) {
    return ((k >> 1) & 3) * 16 + ((k >> 3) & 1) * 8 + ((k >> 4) & 1) * 4 + (k & 1) * 2;
}

__device__ __forceinline__ void st_tag2(float* p, float a, float b, uint32_t tag) {
    asm volatile("{\n.reg .b64 w;\n.reg .b32 x;\nlop3.b32 x, %1, 0xfffffffe, %3, 0xea;\nmov.b64 w, {x, %2};\n"
                 "st.relaxed.gpu.global.b64 [%0], w;\n}"
                 ::"l"(p), "r"(__float_as_uint(a)), "r"(__float_as_uint(b)), "r"(tag) : "memory");
}
__device__ __forceinline__ void st_fill4(float* p, uint32_t v) {
    asm volatile("{\n.reg .b64 w;\nmov.b64 w, {%1, %1};\nst.relaxed.gpu.global.v2.b64 [%0], {w, w};\n}" ::"l"(p), "r"(v) : "memory");
}
__device__ __forceinline__ uint2 ld_word(const float* p) {
    uint2 v;
    asm volatile("{\n.reg .b64 w;\nld.relaxed.gpu.global.b64 w, [%2];\nmov.b64 {%0,%1}, w;\n}" : "=r"(v.x), "=r"(v.y) : "l"(p) : "memory");
    return v;
}
__device__ __forceinline__ uint4 ld_word2(const float* p) {
    uint4 v;
    asm volatile("{\n.reg .b64 w0, w1;\nld.relaxed.gpu.global.v2.b64 {w0, w1}, [%4];\nmov.b64 {%0,%1}, w0;\nmov.b64 {%2,%3}, w1;\n}"
                 : "=r"(v.x), "=r"(v.y), "=r"(v.z), "=r"(v.w) : "l"(p) : "memory");
    return v;
}

__device__ __forceinline__ void add_out(const float4* acc, bf16* out, const float (&lo)[3][4], const float (&hi)[3][4],
                                        bool odd, bool third, bool live, uint32_t epoch) {
    const float v0 = odd ? lo[0][1] + hi[0][3] : lo[0][0] + hi[0][2];
    const float v1 = odd ? lo[1][1] + hi[1][3] : lo[1][0] + hi[1][2];
    const float v2 = odd ? lo[2][1] + hi[2][3] : lo[2][0] + hi[2][2];
    float o0, o1, o2, n = 0.f;
    asm volatile("{\n.reg .pred p;\nsetp.ne.u32 p, %5, 0;\n"
                 "@p atom.relaxed.gpu.global.add.v4.f32 {%0,%1,%2,%3}, [%4], {%6,%7,%8,%9};\n}"
                 : "=f"(o0), "=f"(o1), "=f"(o2), "+f"(n)
                 : "l"(acc), "r"((uint32_t)live), "f"(v0), "f"(v1), "f"(v2), "f"(1.0f) : "memory");
    asm volatile("{\n.reg .pred p, q;\nsetp.eq.f32 p, %4, %5;\nsetp.ne.and.u32 q, %6, 0, p;\n"
                 "@p st.global.u16 [%0], %1;\n@p st.global.u16 [%0+128], %2;\n@q st.global.u16 [%0+256], %3;\n}"
                 ::"l"(out), "h"(__bfloat16_as_ushort(__float2bfloat16_rn(o0 + v0))),
                   "h"(__bfloat16_as_ushort(__float2bfloat16_rn(o1 + v1))), "h"(__bfloat16_as_ushort(__float2bfloat16_rn(o2 + v2))),
                   "f"(n), "f"((float)(NSRC - 1)), "r"((uint32_t)third) : "memory");
    if (acc == g_acc && n == (float)(NSRC - 1))
        asm volatile("st.relaxed.gpu.global.u32 [%0], %1;" ::"l"(&g_sync.epoch), "r"(epoch + 1u) : "memory");
}

__device__ __forceinline__ int pair_of(int sg, uint32_t j) { return sg * G + (j % (G / 4)) * 4 + j / (G / 4); }

__device__ __forceinline__ void settle(int cycles) {
    const uint32_t t0 = (uint32_t)clock();
    while ((uint32_t)clock() - t0 < (uint32_t)cycles) __nanosleep(P_NSL);
}

template <int V> struct IntC { static constexpr int value = V; };

struct Ring {
    uint32_t full, addr, phase, first_full;
    __device__ __forceinline__ void wait() const { mbar_wait(full, phase); }
    __device__ __forceinline__ void skip(int n) {
        full += n * 8; addr += n * SLOT;
        if (full >= first_full + NS * 8) { full -= NS * 8; addr -= NS * SLOT; phase ^= 1; }
    }
    __device__ __forceinline__ void release(int lane) {
        __syncwarp();
        if (lane == 0) mbar_arrive(full + NS * 8);
        full += 8; addr += SLOT;
        if (full == first_full + NS * 8) { full = first_full; addr -= NS * SLOT; phase ^= 1; }
    }
};

__device__ __forceinline__ void pin3(uint32_t (&v)[3]) {
    asm volatile("" : "+r"(v[0]), "+r"(v[1]), "+r"(v[2]));
}
__device__ __forceinline__ void gemv_loop(Ring& ring, int n, uint32_t a_addr, uint32_t a_step, uint32_t (&off)[3],
                                          float (&lo)[3][4], float (&hi)[3][4], int lane) {
    pin3(off);
#pragma unroll
    for (int s = 0; s < 3; s++)
#pragma unroll
        for (int e = 0; e < 4; e++) { lo[s][e] = 0.f; hi[s][e] = 0.f; }
#pragma unroll 1
    for (int it = 0; it < n; it++) {
        uint32_t a[4], b[3][4];
        lds128(a_addr, a);
        a_addr += a_step;
        ring.wait();
#pragma unroll
        for (int s = 0; s < 3; s++) ldsm_x4_t(ring.addr + off[s], b[s]);
#pragma unroll
        for (int s = 0; s < 3; s++) { mma16816(lo[s], a, b[s][0], b[s][1]); mma16816(hi[s], a, b[s][2], b[s][3]); }
        ring.release(lane);
    }
}

__global__ void __launch_bounds__(NTHR, 1)
fused_decode_kernel(const __grid_constant__ Maps maps, const bf16* __restrict__ x, bf16* __restrict__ out) {
    extern __shared__ __align__(1024) unsigned char smem[];
    const uint32_t sb = (uint32_t)__cvta_generic_to_shared(smem);
    const uint32_t bar_full = sb + SM_BAR;
    if (threadIdx.x == 0 && blockIdx.x < NATT) {
        TS(0);
#pragma unroll 1
        for (int i = 0; i < DEPTH0; i++) {
            mbar_init(bar_full + i * 8, 1);
            mbar_expect_tx(bar_full + i * 8, 12288);
            tma3d(sb + SM_RING + i * SLOT, &maps.wq, (blockIdx.x >> 2) * 3, (blockIdx.x & 3) * 160 + i * 32, bar_full + i * 8);
        }
        TS(1);
    }
    unsigned ptid, cta;
    asm volatile("mov.u32 %0, %%tid.x;\nmov.u32 %1, %%ctaid.x;" : "=r"(ptid), "=r"(cta));
    const int tid = ptid < 32 ? ptid + NCW * 32 : ptid < (NCW + 1) * 32 ? ptid - 32 : ptid;
    const int warp = tid >> 5, lane = tid & 31;
    const bool is_att = cta < NATT;
    const int h = cta >> 2, qd = cta & 3;
    const int sg = cta / G, r = cta % G;

    if (warp == NCW) {
        volatile int* pace = reinterpret_cast<volatile int*>(smem + SM_PACE);
        if (lane == 0) {
            if (!is_att) { TS(0); TS(1); }
            pace[0] = 0;
            pace[1] = is_att ? DEPTH : P_DEPTH_FFN;
#pragma unroll
            for (int i = 0; i < NBAR; i++)
                if (i >= DEPTH0 || !is_att)
                mbar_init(bar_full + i * 8, i < NS ? 1 : i < 2 * NS ? NCW : i < 2 * NS + G ? NXW : i == 2 * NS + G ? NXW * NB : i == NBAR - 1 ? NXW : 1);
            asm volatile("fence.mbarrier_init.release.cluster;" ::: "memory");
        }
        __syncwarp();
        asm volatile("bar.arrive 2, %0;" ::"n"(NTHR) : "memory");
        if (lane == 0) {
            const int n_items = is_att ? ITEMS_ATT : ITEMS_FFN;

            asm volatile("prefetch.tensormap [%0];" ::"l"(is_att ? &maps.k : &maps.w3) : "memory");
            asm volatile("prefetch.tensormap [%0];" ::"l"(&maps.v) : "memory");
            asm volatile("prefetch.tensormap [%0];" ::"l"(&maps.w2) : "memory");
            asm volatile("prefetch.tensormap [%0];" ::"l"(&maps.wo) : "memory");
#pragma unroll 1
            for (int i = is_att ? DEPTH0 : 0; i < n_items; i++) {
                const CUtensorMap* map;
                int c1, c2;
                uint32_t bytes = 12288;
                if (is_att) {
                    const uint32_t u = i - 5;
                    if (u < NKV) {
                        const uint32_t blk = u / NT;
                        const bool isv = blk == 2 * G - 1 || (blk && !(blk & 1));
                        const int pair = pair_of(sg, isv ? (blk - 1) / 2 : (blk + 1) / 2);
                        map = isv ? &maps.v : &maps.k;
                        c1 = 0;
                        c2 = ((pair & 3) * NH + (pair >> 2)) * SK + (SK - WIN) + ((u % NT) * G + r) * TK;
                    } else if (i < 5) {
                        map = &maps.wq; c1 = h * 3; c2 = qd * 160 + i * 32;
                    } else if (u < NKV + 2) {
                        map = &maps.w2; c1 = qd * 5; c2 = h * 48 + (u - NKV) * 24; bytes = 7680;
                    } else {
                        map = &maps.wo; c1 = qd * 5; c2 = h * DH + (u - NKV - 2) * 32; bytes = 10240;
                    }
                } else {
                    map = i < 40 ? &maps.w1 : &maps.w3; c1 = qd * 6; c2 = (i < 40 ? i : i - 40) * 16;
                }
                const int depth = pace[1];
                const uint32_t slot = (uint32_t)i % NS, landed = i - depth;
                if (i >= NS) mbar_wait(bar_full + (NS + slot) * 8, ((uint32_t)i / NS - 1) & 1);
                mbar_expect_tx(bar_full + slot * 8, bytes);
                uint32_t dst = sb + SM_RING + slot * SLOT, fb = bar_full + slot * 8;
                asm volatile("" : "+r"(dst), "+r"(fb), "+l"(map), "+r"(c1), "+r"(c2));
                if (i >= depth) mbar_wait(bar_full + (landed % NS) * 8, (landed / NS) & 1);
                tma3d(dst, map, c1, c2, fb);
                pace[0] = landed + 1;
            }
            pace[0] = n_items - DEPTH;
        }
        return;
    }

    const int g = lane >> 2, t = lane & 3;
    uint32_t epoch;
    asm volatile("ld.relaxed.gpu.global.u32 %0, [%1];" : "=r"(epoch) : "l"(&g_sync.epoch) : "memory");

    if (warp == W_PACE) {
        const uint32_t tag = (epoch + 1u) & 1u;
        if (is_att && lane < 2 * G) st_fill4(g_ml + ((sg * G + (lane >> 1)) * G + r) * 32 + (lane & 1) * 4, tag ^ 1u);
        asm volatile("bar.sync 2, %0;" ::"n"(NTHR) : "memory");
        if (lane == 0) asm volatile("red.release.gpu.global.add.u32 [%0], 1;" ::"l"(&g_sync.inits) : "memory");
        if (!is_att) return;
        volatile int* pace = reinterpret_cast<volatile int*>(smem + SM_PACE);
        if (cta == 0 && lane == 0) asm volatile("st.relaxed.gpu.global.u32 [%0], %1;" ::"l"(&g_sync.prog[epoch & 1u]), "r"(0u) : "memory");
        int reported = 0, j = 0;
        bool due = false;
#pragma unroll 1
        for (unsigned it = 0;; it++) {
            const int landed = pace[0];
            int sum = 0;
            uint2 ml = make_uint2(~tag, 0u);
            unsigned n = (epoch + 1u) * NCTA;
            if (lane == 0 && reported < ITEMS_ATT - DEPTH)
                asm volatile("atom.relaxed.gpu.global.add.u32 %0, [%1], %2;"
                             : "=r"(sum) : "l"(&g_sync.prog[~epoch & 1u]), "r"(landed - reported) : "memory");
            if (due) {
                ml = ld_word(g_ml + (pair_of(sg, j) * G + lane % G) * 32);
                if (j == 0) asm volatile("ld.acquire.gpu.global.u32 %0, [%1];" : "=r"(n) : "l"(&g_sync.inits) : "memory");
            }
            reported = landed;
            if (lane == 0 && P_GAIN) {
                const int avg16 = sum / (NATT / 16), lag16 = avg16 - landed * 16 + P_BIAS;
                pace[1] = avg16 >= ITEMS_ATT * 16 - P_FLUSH ? 8 : min(max(DEPTH + ((lag16 * P_GAIN + 128) >> 8), P_DMIN), P_DMAX);
            }
            if (__all_sync(0xffffffffu, !((ml.x ^ tag) & 1u) && n == (epoch + 1u) * NCTA)) {
                const float mk = __uint_as_float(ml.x & ~1u);
                float M = mk;
#pragma unroll
                for (int o = G / 2; o; o >>= 1) M = fmaxf(M, shx(M, o));
                const float w = __expf(mk - M);
                float L = w * __uint_as_float(ml.y);
#pragma unroll
                for (int o = G / 2; o; o >>= 1) L += shx(L, o);
                if (lane == r) {
                    reinterpret_cast<float*>(smem + SM_LS)[16 + (j & 1)] = __fdividef(w, L);
                    mbar_arrive(bar_full + B_WRDY + (j & 1) * 8);
                    if (j == G - 1) TS(11);
                }
                j++;
                due = false;
            }
            if (j == G) {
                if (landed >= ITEMS_ATT - DEPTH) return;
            } else {
                if (!due) due = mbar_test(bar_full + B_WTRIG + (j & 1) * 8, (j >> 1) & 1);
                __nanosleep(P_SLEEP);
            }
            if (it > SPIN_LIMIT) __trap();
        }
    }
    if (warp > W_PROD) {
        const uint32_t tag = (epoch + 1u) & 1u;
        const int e = tid - (W_PROD + 1) * 32;
        if (is_att) {
#pragma unroll 1
            for (int i = e; i < 192; i += NXW * 32)
                st_fill4(g_qpart + (cta * NB + i / 48) * VS + (i % 48) / 6 * 32 + (i % 6) * 4, tag ^ 1u);
            st_fill4(reinterpret_cast<float*>(g_oacc + cta * 64 + e), 0u);
            if (e < 32) *reinterpret_cast<uint32_t*>(smem + SM_HF + e * 16 + 12) = 0u;
        } else {
#pragma unroll 1
            for (int c = e; c < 256; c += NXW * 32) {
                const bf16* xp = x + qd * DM + (c >> 6) * 160 + ((c >> 3) & 7) * 8 + (c & 3) * 2 + ((c >> 2) & 1);
                asm volatile("st.relaxed.gpu.global.v4.f32 [%0], {%1,%2,%3,%4};"
                             ::"l"(g_acc + (qd * 32 + (c >> 3)) * ACS + (c & 7)), "f"(__bfloat162float(xp[0])),
                               "f"(__bfloat162float(xp[64])), "f"((c & 32) ? 0.f : __bfloat162float(xp[128])), "f"(0.f) : "memory");
            }
        }
        asm volatile("bar.sync 2, %0;" ::"n"(NTHR) : "memory");
        if (!is_att) return;
        {
            const uint32_t eq = (e >> 5) * 24 + min(lane, 23), xw = eq / 6, xr = eq % 6;
            mbar_wait(bar_full + B_QTRIG, 0);
            if (e == 0) TS(10);
            settle(P_QDELAY);
#pragma unroll 1
            for (int j = 0; j < G; j++) {
                const int pair = pair_of(sg, j);
                const float* src = g_qpart + ((pair >> 2) * 4 * NB + (pair & 3)) * VS + xw * 32 + xr * 4;
                uint4 v[4];
                uint32_t bad;
                unsigned spin = 0;
                do {
#pragma unroll
                    for (int k = 0; k < 4; k++) v[k] = ld_word2(src + k * NB * VS);
                    bad = 0;
#pragma unroll
                    for (int k = 0; k < 4; k++) bad |= (v[k].x ^ tag) | (v[k].z ^ tag);
                    if (++spin > SPIN_LIMIT) __trap();
                } while (bad & 1u);
#define SUM4(c) ((__uint_as_float(v[0].c) + __uint_as_float(v[1].c)) + (__uint_as_float(v[2].c) + __uint_as_float(v[3].c)))
                unsigned char* dst = smem + SM_QS + j * (DH * 2) + (xr & 1) * 192 + ((xr >> 1) * 8 + xw) * 4;
                *reinterpret_cast<uint32_t*>(dst) = pack_bf2(SUM4(x), SUM4(y));
                *reinterpret_cast<uint32_t*>(dst + 96) = pack_bf2(SUM4(z), SUM4(w));
#undef SUM4
                __syncwarp();
                if (lane == 0) mbar_arrive(bar_full + B_QRDY + j * 8);
                if (e == 0 && j == 0) TS(12);
            }
        }
#pragma unroll 1
        for (int b = 0; b < NB; b++) {
            if (b == NB - 1) {
#pragma unroll 1
                for (int i = e; i < 96; i += NXW * 32) {
                    const int k = (i % 24) * 2;
                    uint2 v;
                    unsigned spin = 0;
                    do {
                        v = ld_word(g_h + i / 24 * FF + h * 48 + k);
                        if (++spin > SPIN_LIMIT) __trap();
                    } while ((v.x ^ tag) & 1u);
                    *reinterpret_cast<uint32_t*>(smem + SM_HF + k / 24 * 256 + i / 24 * 64 + frag_off(k % 24)) = __byte_perm(v.x, v.y, 0x7632);
                }
                __syncwarp();
                if (lane == 0) mbar_arrive(bar_full + B_HRDY);
            }
            const float4* src = g_oacc + (h * NB + b) * 64 + e;
            uint32_t dst = sb + SM_OF + (e >> 5) * 256 + b * 64 + frag_off(lane), ordy = bar_full + B_ORDY;
            asm volatile("" : "+r"(dst), "+l"(src), "+r"(ordy));
            mbar_wait(bar_full + B_OTRIG + b * 8, 0);
            if (h * NB + b != sg * G + G - 1) settle(P_SETTLE);
            unsigned spin = 0;
            float o0, o1, o2, n;
            do {
                asm volatile("atom.relaxed.gpu.global.add.v4.f32 {%0,%1,%2,%3}, [%4], {%5,%5,%5,%5};"
                             : "=f"(o0), "=f"(o1), "=f"(o2), "=f"(n) : "l"(src), "f"(0.f) : "memory");
                asm volatile("st.shared.u16 [%0], %1;\nst.shared.u16 [%0+512], %2;\nst.shared.u16 [%0+1024], %3;"
                             ::"r"(dst), "h"(__bfloat16_as_ushort(__float2bfloat16_rn(o0))),
                               "h"(__bfloat16_as_ushort(__float2bfloat16_rn(o1))), "h"(__bfloat16_as_ushort(__float2bfloat16_rn(o2))) : "memory");
                if (++spin > SPIN_LIMIT) __trap();
            } while (n != (float)G);
            __syncwarp();
            if (lane == 0) mbar_arrive(ordy);
        }
        return;
    }

    if (warp < NB) {
        uint2 raw[5];
#pragma unroll
        for (int i = 0; i < 5; i++) raw[i] = __ldg(reinterpret_cast<const uint2*>(x + warp * DM) + i * 32 + lane);
        float s = 0.f;
#pragma unroll
        for (int i = 0; i < 5; i++) s += (bf_lo(raw[i].x) + bf_hi(raw[i].x)) + (bf_lo(raw[i].y) + bf_hi(raw[i].y));
#pragma unroll
        for (int o = 16; o; o >>= 1) s += shx(s, o);
        const float mean = s * (1.0f / DM);
        float q2 = 0.f;
#pragma unroll
        for (int i = 0; i < 5; i++) {
            const float d0 = bf_lo(raw[i].x) - mean, d1 = bf_hi(raw[i].x) - mean;
            const float d2 = bf_lo(raw[i].y) - mean, d3 = bf_hi(raw[i].y) - mean;
            q2 += (d0 * d0 + d1 * d1) + (d2 * d2 + d3 * d3);
        }
#pragma unroll
        for (int o = 16; o; o >>= 1) q2 += shx(q2, o);
        const float mb = bf_round(mean);
        const float rs = __frcp_rn(bf_round(__fsqrt_rn(bf_round(bf_round(q2 * (1.0f / DM)) + 1e-5f))));
        const uint32_t k = (lane * 4) & 31;
        unsigned char* dst = smem + SM_XF + warp * 64 +
            (is_att ? (lane >> 3) * 256 + frag_off(k) : (lane >> 2) * 256 + frag_off(k & 15));
        const uint32_t step = is_att ? 1024 : 2048;
#pragma unroll
        for (int i = 0; i < 5; i++) {
            const uint32_t d0 = pack_bf2(bf_lo(raw[i].x) - mb, bf_hi(raw[i].x) - mb);
            const uint32_t d1 = pack_bf2(bf_lo(raw[i].y) - mb, bf_hi(raw[i].y) - mb);
            *reinterpret_cast<uint32_t*>(dst + i * step) = pack_bf2(bf_lo(d0) * rs, bf_hi(d0) * rs);
            *reinterpret_cast<uint32_t*>(dst + i * step + 16) = pack_bf2(bf_lo(d1) * rs, bf_hi(d1) * rs);
        }
    }
    asm volatile("bar.sync 2, %0;" ::"n"(NTHR) : "memory");
    uint32_t tag = (epoch + 1u) & 1u;
    asm volatile("" : "+r"(tag));
    if (tid == 0) TS(3);

    Ring ring{bar_full, sb + SM_RING, 0u, bar_full};
    float lo[3][4] = {}, hi[3][4] = {};
    uint32_t off[3];
    const uint32_t a_lane = (g & 3) * 64 + t * 16;

    if (is_att) {
        float* lsum = reinterpret_cast<float*>(smem + SM_LS);
#pragma unroll 1
        for (int j = -1; j <= G; j++) {
            if (j >= 0 && j < G) {
                uint32_t qf[6][4];
                mbar_wait(bar_full + B_QRDY + j * 8, 0);
                if (j == 0 && tid == 0) TS(6);
#pragma unroll
                for (int i = 0; i < 6; i++) lds128(sb + SM_QS + j * (DH * 2) + t * 96 + i * 16, qf[i]);
                const uint32_t key = (warp & 1) * 16 + (lane & 15);
                float sv[NT / 4], m = -INFINITY;
#pragma unroll
                for (int rr = 0; rr < NT / 4; rr++) {
                    const uint32_t item = 5 + max(2 * j - 1, 0) * NT + rr * 4 + (warp >> 1), slot = item % NS;
#pragma unroll
                    for (int s = 0; s < 3; s++)
                        off[s] = sb + SM_RING + slot * SLOT + key * 384 + s * 128 + (((lane >> 4) ^ ((3 * key + s) & 7)) << 4);
                    pin3(off);
                    mbar_wait(bar_full + slot * 8, (item / NS) & 1);
                    float c[3][4] = {};
#pragma unroll
                    for (int dq = 0; dq < 4; dq++)
#pragma unroll
                        for (int s = 0; s < 3; s++) {
                            uint32_t a[4];
                            ldsm_x4(off[s] ^ (dq << 5), a);
                            mma16816(c[s], a, qf[s * 2 + (dq >> 1)][(dq & 1) * 2], qf[s * 2 + (dq >> 1)][(dq & 1) * 2 + 1]);
                        }
                    __syncwarp();
                    if (lane == 0)
                        asm volatile("mbarrier.arrive.shared::cta.b64 _, [%0], %1;" ::"r"(bar_full + (NS + slot) * 8), "n"(NCW / 2) : "memory");
                    const float raw = (t & 1) ? (c[0][2] + c[1][2]) + c[2][2] : (c[0][0] + c[1][0]) + c[2][0];
                    sv[rr] = bf_round(bf_round(raw) * 0.07216878364870323f);
                    m = fmaxf(m, sv[rr]);
                }
                ring.skip(NT);
                if (tid == 0 && j == G - 1) TS(14);
                m = fmaxf(m, shx(m, 1));
#pragma unroll
                for (int o = 4; o < 32; o <<= 1) m = fmaxf(m, shx(m, o));
                if (lane == 0) lsum[8 + warp] = m;
                cons_bar();
                {
                    const float4 m0 = reinterpret_cast<const float4*>(lsum)[2], m1 = reinterpret_cast<const float4*>(lsum)[3];
                    m = fmaxf(fmaxf(fmaxf(m0.x, m0.y), fmaxf(m0.z, m0.w)), fmaxf(fmaxf(m1.x, m1.y), fmaxf(m1.z, m1.w)));
                }
                float l = 0.f;
#pragma unroll
                for (int rr = 0; rr < NT / 4; rr++) {
                    const float p = __expf(sv[rr] - m);
                    l += p;
                    *reinterpret_cast<bf16*>(smem + SM_PF + ((j & 1) * NT + rr * 4 + (warp >> 1)) * 64 + frag_off((warp & 1) * 16 + (t & 1) * 8 + g)) =
                        __float2bfloat16_rn(p);
                }
                l += shx(l, 1);
#pragma unroll
                for (int o = 4; o < 32; o <<= 1) l += shx(l, o);
                if (lane == 0) lsum[warp] = l;
                cons_bar();
                if (tid < 4) {
                    const float4 l0 = reinterpret_cast<const float4*>(lsum)[0], l1 = reinterpret_cast<const float4*>(lsum)[1];
                    st_tag2(g_ml + (pair_of(sg, j) * G + r) * 32 + tid * 2, m,
                            ((l0.x + l0.y) + (l0.z + l0.w)) + ((l1.x + l1.y) + (l1.z + l1.w)), tag);
                    if (tid == 0) mbar_arrive(bar_full + B_WTRIG + (j & 1) * 8);
                }
                if (tid == 0 && j == G - 1) TS(13);
                if (j == 0) continue;
            }
            const bool kv = j >= 0;
            const int pair = pair_of(sg, j - 1);
            uint32_t trig = !kv ? bar_full + B_QTRIG : (pair >> 2) == h ? bar_full + B_OTRIG + (pair & 3) * 8 : 0;
            if (tid != 0) trig = 0;
            float4* oacc = g_oacc + pair * 64 + warp * 8 + 2 * t + g;
            uint32_t wrdy = bar_full + B_WRDY + (~j & 1) * 8;
#pragma unroll
            for (int s = 0; s < 3; s++) off[s] = lane * 384 + s * 128 + ((warp ^ ((3 * lane + s) & 7)) << 4);
            asm volatile("" : "+l"(oacc), "+r"(trig), "+r"(wrdy));
            gemv_loop(ring, kv ? NT : 5, kv ? sb + SM_PF + (~j & 1) * (NT * 64) + t * 16 : sb + SM_XF + qd * 5 * 256 + a_lane,
                      kv ? 64 : 256, off, lo, hi, lane);
            if (kv) {
                mbar_wait(wrdy, ((j - 1) >> 1) & 1);
                const float w = lsum[16 + (~j & 1)];
                if (g < 2)
                    asm volatile("red.relaxed.gpu.global.add.v4.f32 [%0], {%1,%2,%3,%4};"
                                 ::"l"(oacc), "f"(w * (g ? lo[0][1] + hi[0][3] : lo[0][0] + hi[0][2])),
                                   "f"(w * (g ? lo[1][1] + hi[1][3] : lo[1][0] + hi[1][2])),
                                   "f"(w * (g ? lo[2][1] + hi[2][3] : lo[2][0] + hi[2][2])), "f"(1.0f) : "memory");
            } else if (g < NB) {
#pragma unroll
                for (int s = 0; s < 3; s++)
                    st_tag2(g_qpart + (cta * NB + g) * VS + warp * 32 + 2 * t + s * 8, lo[s][0] + hi[s][2], lo[s][1] + hi[s][3], tag);
            }
            if (trig) mbar_arrive(trig);
            if (j == G && tid == 0) TS(5);
            if (j >= 0 && j < G && j != P_DRY) continue;
            if (tid == 0 && j < 0) TS(4);

            {
                const bool pass = j == G;
                constexpr int I0 = 5 + NKV + 2;
                const uint32_t done = bar_full + B_QTRIG;
                uint32_t b[6][3][4];
                mbar_wait(pass ? bar_full + B_HRDY : done, 0);
#pragma unroll
                for (int s = 0; s < 3; s++) {
                    const uint32_t w64 = (lane < 24 ? lane : lane - 8) * 320 + (warp + 8 * s) * 16;
                    off[s] = sb + SM_RING + (w64 ^ (((w64 >> 7) & 3) << 4));
#pragma unroll
                    for (int e = 0; e < 4; e++) { lo[s][e] = 0.f; hi[s][e] = 0.f; }
                }
#pragma unroll
                for (int i = 0; i < 2; i++) {
                    uint32_t a[4];
                    lds128(sb + SM_HF + a_lane + i * 256, a);
                    mbar_wait(pass ? bar_full + ((I0 - 2 + i) % NS) * 8 : done, pass ? ((I0 - 2 + i) / NS) & 1 : 0);
#pragma unroll
                    for (int s = 0; s < 3; s++)
                        if (s < 2 || warp < 4) {
                            ldsm_x4_t(off[s] + ((I0 - 2 + i) % NS) * SLOT, b[i][s]);
                            mma16816(lo[s], a, b[i][s][0], b[i][s][1]);
                            mma16816(hi[s], a, b[i][s][2], b[i][s][3]);
                        }
                }
                if (pass && tid == 0) TS(31);
#pragma unroll
                for (int s = 0; s < 3; s++) {
                    const uint32_t w64 = lane * 320 + (warp + 8 * s) * 16;
                    off[s] = sb + SM_RING + (w64 ^ (((w64 >> 7) & 3) << 4));
                }
                const float4* accp = g_acc + (((g & 3) * 4 + qd) * NCW + warp) * ACS + (g >> 2) * 4 + t;
                bf16* outp = out + (g & 3) * DM + qd * 160 + warp * 8 + 2 * t + (g >> 2);
                uint32_t a_addr = sb + SM_OF + a_lane;
                uint32_t ordy = pass ? bar_full + B_ORDY : done, fb[6];
#pragma unroll
                for (int i = 0; i < 6; i++) fb[i] = pass ? bar_full + ((I0 + i) % NS) * 8 : done;
                pin3(off);
                asm volatile("" : "+l"(accp), "+l"(outp), "+r"(a_addr), "+r"(ordy), "+r"(fb[3]), "+r"(fb[4]), "+r"(fb[5]));
                auto project = [&](auto pre) {
                    constexpr int PRE = decltype(pre)::value;
                    uint32_t a[6][4];
#pragma unroll
                    for (int i = 0; i <= 6; i++) {
                        if (i == PRE) {
                            mbar_wait(ordy, 0);
                            if (pass && tid == 0) TS(7);
#pragma unroll
                            for (int k = 0; k < 2; k++) lds128(a_addr + k * 256, a[k]);
                        }
                        if (i < 6) {
                            mbar_wait(fb[i], pass ? ((I0 + i) / NS) & 1 : 0);
#pragma unroll
                            for (int s = 0; s < 3; s++) ldsm_x4_t(off[s] + ((I0 + i) % NS) * SLOT, b[i][s]);
                        }
#pragma unroll
                        for (int k = 0; k < 6; k++)
                            if (i == PRE ? k < i : i > PRE && k == i - 1) {
#pragma unroll
                                for (int s = 0; s < 3; s++)
                                    if (s < 2 || warp < 4) { mma16816(lo[s], a[k], b[k][s][0], b[k][s][1]); mma16816(hi[s], a[k], b[k][s][2], b[k][s][3]); }
                                if (k + 2 < 6) lds128(a_addr + (k + 2) * 256, a[k + 2]);
                            }
                    }
                };
                if (r >= G - 4) project(IntC<P_PRE>()); else project(IntC<P_PRE0>());
                if (pass && tid == 0) TS(8);
                add_out(accp, outp, lo, hi, g >= NB, warp < 4, pass, epoch);
            }
        }
        if (tid == 0) { TS(9); TS_DUMP(3, 32); }
    } else {
        float gate[6][2];
#pragma unroll
        for (int s = 0; s < 3; s++) {
            const uint32_t r128 = (lane & 15) * 6 + 2 * s + (lane >> 4);
            off[s] = r128 * 128 + ((warp ^ (r128 & 7)) << 4);
        }
#pragma unroll 1
        for (int ps = 0; ps < 2; ps++) {
#pragma unroll
            for (int s = 0; s < 3; s++) {
                gate[2 * s][0] = lo[s][0]; gate[2 * s][1] = lo[s][1];
                gate[2 * s + 1][0] = hi[s][0]; gate[2 * s + 1][1] = hi[s][1];
            }
            gemv_loop(ring, 40, sb + SM_XF + a_lane, 256, off, lo, hi, lane);
        }
#pragma unroll
        for (int p = 0; p < 6; p++) {
            float hv[2];
#pragma unroll
            for (int e = 0; e < 2; e++) {
                const float gt = bf_round(gate[p][e]);
                hv[e] = bf_round(bf_round(__fdividef(gt, 1.0f + __expf(-gt))) * bf_round((p & 1) ? hi[p >> 1][e] : lo[p >> 1][e]));
            }
            if (g < NB) st_tag2(g_h + g * FF + qd * 384 + p * 64 + warp * 8 + 2 * t, hv[0], hv[1], tag);
        }
        if (tid == 0) { TS(9); TS_DUMP(3, 10); }
    }
}

typedef CUresult (*EncodeFn)(CUtensorMap*, CUtensorMapDataType, cuuint32_t, void*, const cuuint64_t*, const cuuint64_t*,
                             const cuuint32_t*, const cuuint32_t*, CUtensorMapInterleave, CUtensorMapSwizzle,
                             CUtensorMapL2promotion, CUtensorMapFloatOOBfill);

void make_map(EncodeFn enc, CUtensorMap* m, const void* p, uint64_t rows, uint64_t cols, uint32_t inner, uint32_t parts,
              uint32_t box_rows) {
    const cuuint64_t dims[3] = {inner, cols / inner, rows};
    const cuuint64_t strides[2] = {inner * 2ull, cols * 2ull};
    const cuuint32_t box[3] = {inner, parts, box_rows};
    const cuuint32_t es[3] = {1, 1, 1};
    enc(m, CU_TENSOR_MAP_DATA_TYPE_BFLOAT16, 3, const_cast<void*>(p), dims, strides, box, es, CU_TENSOR_MAP_INTERLEAVE_NONE,
        inner == 64 ? CU_TENSOR_MAP_SWIZZLE_128B : CU_TENSOR_MAP_SWIZZLE_64B, CU_TENSOR_MAP_L2_PROMOTION_NONE,
        CU_TENSOR_MAP_FLOAT_OOB_FILL_NONE);
}

}

extern "C" void kernel_launch(void* const* d_in, const int* in_sizes, int n_in, void* d_out, int out_size) {
    (void)in_sizes; (void)n_in; (void)out_size;
    static EncodeFn enc = nullptr;
    if (!enc) {
        void* fn = nullptr;
        cudaDriverEntryPointQueryResult qr;
        cudaGetDriverEntryPoint("cuTensorMapEncodeTiled", &fn, cudaEnableDefault, &qr);
        enc = (EncodeFn)fn;
        cudaFuncSetAttribute(fused_decode_kernel, cudaFuncAttributeMaxDynamicSharedMemorySize, SM_TOTAL);
    }
    Maps maps;
    make_map(enc, &maps.k, d_in[1], (uint64_t)NB * NH * SK, DH, 64, 3, TK);
    make_map(enc, &maps.v, d_in[2], (uint64_t)NB * NH * SK, DH, 64, 3, TK);
    make_map(enc, &maps.wq, d_in[3], DM, NH * DH, 64, 3, 32);
    make_map(enc, &maps.wo, d_in[4], NH * DH, DM, 32, 5, 32);
    make_map(enc, &maps.w1, d_in[6], DM, FF, 64, 6, 16);
    make_map(enc, &maps.w3, d_in[7], DM, FF, 64, 6, 16);
    make_map(enc, &maps.w2, d_in[8], FF, DM, 32, 5, 24);
    fused_decode_kernel<<<NCTA, NTHR, SM_TOTAL>>>(maps, (const bf16*)d_in[0], (bf16*)d_out);
}
```

```cpp
#include <cuda_runtime.h>
#include <cuda.h>
#include <cuda_bf16.h>
#include <stdint.h>

namespace {

typedef __nv_bfloat16 bf16;

constexpr int NB = 4, DM = 640, NH = 32, DH = 192, SK = 8192, WIN = 2048, FF = 1536;

#define P_G 16
#define P_DEPTH 4
#define P_DEPTH_FFN 5
#define P_GAIN 8
#define P_BIAS 16
#define P_SLEEP 500
#define P_DMIN P_DEPTH
#define P_DMAX 6
#define P_SETTLE 3000
#define P_QDELAY 1600
#define P_NSL 20
#define P_DRY 2
#define P_FLUSH 112
#define P_DEC 6
#define P_WFAST 2
#define P_NS 16

constexpr int G = P_G;
constexpr int TK = 32;
constexpr int NT = WIN / TK / G;
constexpr int NS = P_NS;
constexpr int SLOT = 12288;
constexpr int DEPTH = P_DEPTH;
#define P_D0 5
constexpr int DEPTH0 = P_D0;
static_assert(DEPTH0 <= 5, "DEPTH0");
constexpr int NATT = 128, NFFN = 4, NCTA = NATT + NFFN;
constexpr int NCW = 8;
constexpr int NXW = 2;
constexpr int W_PROD = NCW, W_PACE = NCW + 1 + NXW;
constexpr int NTHR = (W_PACE + 1) * 32;
constexpr int NSRC = NH;
constexpr int VS = 256;
#define P_ACS 16
constexpr int ACS = P_ACS;
static_assert(G == 8 || G == 16, "G");

constexpr int SM_RING = 0;
constexpr int SM_XF = SM_RING + NS * SLOT;
constexpr int SM_QS = SM_XF + 20 * 256;
constexpr int SM_PF = SM_QS + G * DH * 2;
constexpr int SM_HF = SM_PF + 2 * NT * 64;
constexpr int SM_OF = SM_HF + 2 * 256;
constexpr int SM_LS = SM_OF + 6 * 256;
constexpr int SM_ATT_END = SM_LS + 80;
constexpr int SM_FFN_END = SM_XF + 40 * 256;
constexpr int SM_BAR = SM_ATT_END > SM_FFN_END ? SM_ATT_END : SM_FFN_END;
constexpr int B_QRDY = 2 * NS * 8, B_ORDY = B_QRDY + G * 8, B_OTRIG = B_ORDY + 8, B_QTRIG = B_OTRIG + 32,
              B_WTRIG = B_QTRIG + 8, B_WRDY = B_WTRIG + 16, B_HRDY = B_WRDY + 16, NBAR = 2 * NS + G + 11;
constexpr int SM_PACE = SM_BAR + NBAR * 8;
constexpr int SM_TS = SM_PACE + 8;
constexpr int SM_TOTAL = SM_TS + 256;
static_assert(SM_TOTAL <= 232448, "smem");

constexpr int NKV = 2 * NT * G;
constexpr int ITEMS_ATT = 5 + NKV + 2 + 6;
constexpr int ITEMS_FFN = 80;

struct Maps { CUtensorMap k, v, wq, wo, w1, w3, w2; };

struct alignas(32) Sync { unsigned epoch, inits, prog[2]; };
__device__ Sync g_sync;
__device__ __align__(128) float g_qpart[NATT * NB * VS];
__device__ __align__(128) float g_ml[NATT * G * 32];
__device__ __align__(128) float g_h[NB * FF];
__device__ __align__(128) float4 g_oacc[NATT * 64];
__device__ __align__(128) float4 g_acc[NB * 4 * NCW * ACS];
#define TS(i)
#define TS_DUMP(lo, hi)

constexpr unsigned SPIN_LIMIT = 1u << 24;

__device__ __forceinline__ void mbar_init(uint32_t bar, int cnt) {
    asm volatile("mbarrier.init.shared::cta.b64 [%0], %1;" ::"r"(bar), "r"(cnt) : "memory");
}
__device__ __forceinline__ void mbar_expect_tx(uint32_t bar, uint32_t bytes) {
    asm volatile("mbarrier.arrive.expect_tx.shared::cta.b64 _, [%0], %1;" ::"r"(bar), "r"(bytes) : "memory");
}
__device__ __forceinline__ void mbar_arrive(uint32_t bar) {
    asm volatile("mbarrier.arrive.shared::cta.b64 _, [%0];" ::"r"(bar) : "memory");
}
__device__ __forceinline__ void mbar_wait(uint32_t bar, uint32_t parity) {
    asm volatile("{\n.reg .pred p, q;\n.reg .u32 n;\nmov.u32 n, 0;\n"
                 "W: mbarrier.try_wait.parity.shared::cta.b64 p, [%0], %1;\n"
                 "@p bra D;\nadd.u32 n, n, 1;\nsetp.lt.u32 q, n, %2;\n@q bra W;\ntrap;\nD:\n}"
                 ::"r"(bar), "r"(parity), "n"(SPIN_LIMIT) : "memory");
}
__device__ __forceinline__ bool mbar_test(uint32_t bar, uint32_t parity) {
    uint32_t ok;
    asm volatile("{\n.reg .pred p;\nmbarrier.test_wait.parity.shared::cta.b64 p, [%1], %2;\nselp.u32 %0, 1, 0, p;\n}"
                 : "=r"(ok) : "r"(bar), "r"(parity) : "memory");
    return ok;
}
__device__ __forceinline__ void tma3d(uint32_t dst, const CUtensorMap* map, int c1, int c2, uint32_t bar) {
    const uint64_t pol = 0x12F0000000000000ull;
    asm volatile("cp.async.bulk.tensor.3d.shared::cluster.global.mbarrier::complete_tx::bytes.L2::cache_hint "
                 "[%0], [%1, {%2, %3, %4}], [%5], %6;"
                 ::"r"(dst), "l"(map), "r"(0), "r"(c1), "r"(c2), "r"(bar), "l"(pol) : "memory");
}
__device__ __forceinline__ void ldsm_x4(uint32_t addr, uint32_t (&r)[4]) {
    asm volatile("ldmatrix.sync.aligned.m8n8.x4.shared.b16 {%0,%1,%2,%3}, [%4];"
                 : "=r"(r[0]), "=r"(r[1]), "=r"(r[2]), "=r"(r[3]) : "r"(addr) : "memory");
}
__device__ __forceinline__ void ldsm_x4_t(uint32_t addr, uint32_t (&r)[4]) {
    asm volatile("ldmatrix.sync.aligned.m8n8.x4.trans.shared.b16 {%0,%1,%2,%3}, [%4];"
                 : "=r"(r[0]), "=r"(r[1]), "=r"(r[2]), "=r"(r[3]) : "r"(addr) : "memory");
}
__device__ __forceinline__ void lds128(uint32_t addr, uint32_t (&r)[4]) {
    asm volatile("ld.shared.v4.u32 {%0,%1,%2,%3}, [%4];"
                 : "=r"(r[0]), "=r"(r[1]), "=r"(r[2]), "=r"(r[3]) : "r"(addr) : "memory");
}
__device__ __forceinline__ void mma16816(float (&c)[4], const uint32_t (&a)[4], uint32_t b0, uint32_t b1) {
    asm volatile("mma.sync.aligned.m16n8k16.row.col.f32.bf16.bf16.f32 {%0,%1,%2,%3}, {%4,%5,%6,%7}, {%8,%9}, {%0,%1,%2,%3};"
                 : "+f"(c[0]), "+f"(c[1]), "+f"(c[2]), "+f"(c[3])
                 : "r"(a[0]), "r"(a[1]), "r"(a[2]), "r"(a[3]), "r"(b0), "r"(b1));
}
__device__ __forceinline__ void cons_bar() { asm volatile("bar.sync 1, 256;" ::: "memory"); }

__device__ __forceinline__ float bf_round(float v) { return __bfloat162float(__float2bfloat16_rn(v)); }
__device__ __forceinline__ uint32_t pack_bf2(float lo, float hi) {
    __nv_bfloat162 t = __floats2bfloat162_rn(lo, hi);
    return *reinterpret_cast<uint32_t*>(&t);
}
__device__ __forceinline__ float bf_lo(uint32_t u) { return __uint_as_float(u << 16); }
__device__ __forceinline__ float bf_hi(uint32_t u) { return __uint_as_float(u & 0xffff0000u); }
__device__ __forceinline__ float shx(float v, int o) { return __shfl_xor_sync(0xffffffffu, v, o); }

__device__ __forceinline__ uint32_t frag_off(uint32_t k) {
    return ((k >> 1) & 3) * 16 + ((k >> 3) & 1) * 8 + ((k >> 4) & 1) * 4 + (k & 1) * 2;
}

__device__ __forceinline__ void st_tag2(float* p, float a, float b, uint32_t tag) {
    asm volatile("{\n.reg .b64 w;\n.reg .b32 x;\nlop3.b32 x, %1, 0xfffffffe, %3, 0xea;\nmov.b64 w, {x, %2};\n"
                 "st.relaxed.gpu.global.b64 [%0], w;\n}"
                 ::"l"(p), "r"(__float_as_uint(a)), "r"(__float_as_uint(b)), "r"(tag) : "memory");
}
__device__ __forceinline__ void st_fill4(float* p, uint32_t v) {
    asm volatile("{\n.reg .b64 w;\nmov.b64 w, {%1, %1};\nst.relaxed.gpu.global.v2.b64 [%0], {w, w};\n}" ::"l"(p), "r"(v) : "memory");
}
__device__ __forceinline__ uint2 ld_word(const float* p) {
    uint2 v;
    asm volatile("{\n.reg .b64 w;\nld.relaxed.gpu.global.b64 w, [%2];\nmov.b64 {%0,%1}, w;\n}" : "=r"(v.x), "=r"(v.y) : "l"(p) : "memory");
    return v;
}
__device__ __forceinline__ uint4 ld_word2(const float* p) {
    uint4 v;
    asm volatile("{\n.reg .b64 w0, w1;\nld.relaxed.gpu.global.v2.b64 {w0, w1}, [%4];\nmov.b64 {%0,%1}, w0;\nmov.b64 {%2,%3}, w1;\n}"
                 : "=r"(v.x), "=r"(v.y), "=r"(v.z), "=r"(v.w) : "l"(p) : "memory");
    return v;
}

__device__ __forceinline__ void add_out(const float4* acc, bf16* out, const float (&lo)[3][4], const float (&hi)[3][4],
                                        bool odd, bool third, bool live, uint32_t epoch) {
    const float v0 = odd ? lo[0][1] + hi[0][3] : lo[0][0] + hi[0][2];
    const float v1 = odd ? lo[1][1] + hi[1][3] : lo[1][0] + hi[1][2];
    const float v2 = odd ? lo[2][1] + hi[2][3] : lo[2][0] + hi[2][2];
    float o0, o1, o2, n = 0.f;
    asm volatile("{\n.reg .pred p;\nsetp.ne.u32 p, %5, 0;\n"
                 "@p atom.relaxed.gpu.global.add.v4.f32 {%0,%1,%2,%3}, [%4], {%6,%7,%8,%9};\n}"
                 : "=f"(o0), "=f"(o1), "=f"(o2), "+f"(n)
                 : "l"(acc), "r"((uint32_t)live), "f"(v0), "f"(v1), "f"(v2), "f"(1.0f) : "memory");
    asm volatile("{\n.reg .pred p, q;\nsetp.eq.f32 p, %4, %5;\nsetp.ne.and.u32 q, %6, 0, p;\n"
                 "@p st.global.u16 [%0], %1;\n@p st.global.u16 [%0+128], %2;\n@q st.global.u16 [%0+256], %3;\n}"
                 ::"l"(out), "h"(__bfloat16_as_ushort(__float2bfloat16_rn(o0 + v0))),
                   "h"(__bfloat16_as_ushort(__float2bfloat16_rn(o1 + v1))), "h"(__bfloat16_as_ushort(__float2bfloat16_rn(o2 + v2))),
                   "f"(n), "f"((float)(NSRC - 1)), "r"((uint32_t)third) : "memory");
    if (acc == g_acc && n == (float)(NSRC - 1))
        asm volatile("st.relaxed.gpu.global.u32 [%0], %1;" ::"l"(&g_sync.epoch), "r"(epoch + 1u) : "memory");
}

__device__ __forceinline__ int pair_of(int sg, uint32_t j) { return sg * G + (j % (G / 4)) * 4 + j / (G / 4); }

__device__ __forceinline__ void settle(int cycles) {
    const uint32_t t0 = (uint32_t)clock();
    while ((uint32_t)clock() - t0 < (uint32_t)cycles) __nanosleep(P_NSL);
}

struct Ring {
    uint32_t full, addr, phase, first_full;
    __device__ __forceinline__ void wait() const { mbar_wait(full, phase); }
    __device__ __forceinline__ void skip(int n) {
        full += n * 8; addr += n * SLOT;
        if (full >= first_full + NS * 8) { full -= NS * 8; addr -= NS * SLOT; phase ^= 1; }
    }
    __device__ __forceinline__ void release(int lane) {
        __syncwarp();
        if (lane == 0) mbar_arrive(full + NS * 8);
        full += 8; addr += SLOT;
        if (full == first_full + NS * 8) { full = first_full; addr -= NS * SLOT; phase ^= 1; }
    }
};

__device__ __forceinline__ void pin3(uint32_t (&v)[3]) {
    asm volatile("" : "+r"(v[0]), "+r"(v[1]), "+r"(v[2]));
}
__device__ __forceinline__ void gemv_loop(Ring& ring, int n, uint32_t a_addr, uint32_t a_step, uint32_t (&off)[3],
                                          float (&lo)[3][4], float (&hi)[3][4], int lane) {
    pin3(off);
#pragma unroll
    for (int s = 0; s < 3; s++)
#pragma unroll
        for (int e = 0; e < 4; e++) { lo[s][e] = 0.f; hi[s][e] = 0.f; }
#pragma unroll 1
    for (int it = 0; it < n; it++) {
        uint32_t a[4], b[3][4];
        lds128(a_addr, a);
        a_addr += a_step;
        ring.wait();
#pragma unroll
        for (int s = 0; s < 3; s++) ldsm_x4_t(ring.addr + off[s], b[s]);
#pragma unroll
        for (int s = 0; s < 3; s++) { mma16816(lo[s], a, b[s][0], b[s][1]); mma16816(hi[s], a, b[s][2], b[s][3]); }
        ring.release(lane);
    }
}

__global__ void __launch_bounds__(NTHR, 1)
fused_decode_kernel(const __grid_constant__ Maps maps, const bf16* __restrict__ x, bf16* __restrict__ out) {
    extern __shared__ __align__(1024) unsigned char smem[];
    const uint32_t sb = (uint32_t)__cvta_generic_to_shared(smem);
    const uint32_t bar_full = sb + SM_BAR;
    if (threadIdx.x == 0 && blockIdx.x < NATT) {
        TS(0);
#pragma unroll 1
        for (int i = 0; i < DEPTH0; i++) {
            mbar_init(bar_full + i * 8, 1);
            mbar_expect_tx(bar_full + i * 8, 12288);
            tma3d(sb + SM_RING + i * SLOT, &maps.wq, (blockIdx.x >> 2) * 3, (blockIdx.x & 3) * 160 + i * 32, bar_full + i * 8);
        }
        TS(1);
    }
    unsigned ptid, cta;
    asm volatile("mov.u32 %0, %%tid.x;\nmov.u32 %1, %%ctaid.x;" : "=r"(ptid), "=r"(cta));
    const int tid = ptid < 32 ? ptid + NCW * 32 : ptid < (NCW + 1) * 32 ? ptid - 32 : ptid;
    const int warp = tid >> 5, lane = tid & 31;
    const bool is_att = cta < NATT;
    const int h = cta >> 2, qd = cta & 3;
    const int sg = cta / G, r = cta % G;

    if (warp == NCW) {
        volatile int* pace = reinterpret_cast<volatile int*>(smem + SM_PACE);
        if (lane == 0) {
            if (!is_att) { TS(0); TS(1); }
            pace[0] = 0;
            pace[1] = is_att ? DEPTH : P_DEPTH_FFN;
#pragma unroll
            for (int i = 0; i < NBAR; i++)
                if (i >= DEPTH0 || !is_att)
                mbar_init(bar_full + i * 8, i < NS ? 1 : i < 2 * NS ? NCW : i < 2 * NS + G ? NXW : i == 2 * NS + G ? NXW * NB : i == NBAR - 1 ? NXW : 1);
            asm volatile("fence.mbarrier_init.release.cluster;" ::: "memory");
        }
        __syncwarp();
        asm volatile("bar.arrive 2, %0;" ::"n"(NTHR) : "memory");
        if (lane == 0) {
            const int n_items = is_att ? ITEMS_ATT : ITEMS_FFN;

            asm volatile("prefetch.tensormap [%0];" ::"l"(is_att ? &maps.k : &maps.w3) : "memory");
            asm volatile("prefetch.tensormap [%0];" ::"l"(&maps.v) : "memory");
            asm volatile("prefetch.tensormap [%0];" ::"l"(&maps.w2) : "memory");
            asm volatile("prefetch.tensormap [%0];" ::"l"(&maps.wo) : "memory");
#pragma unroll 1
            for (int i = is_att ? DEPTH0 : 0; i < n_items; i++) {
                const CUtensorMap* map;
                int c1, c2;
                uint32_t bytes = 12288;
                if (is_att) {
                    const uint32_t u = i - 5;
                    if (u < NKV) {
                        const uint32_t blk = u / NT;
                        const bool isv = blk == 2 * G - 1 || (blk && !(blk & 1));
                        const int pair = pair_of(sg, isv ? (blk - 1) / 2 : (blk + 1) / 2);
                        map = isv ? &maps.v : &maps.k;
                        c1 = 0;
                        c2 = ((pair & 3) * NH + (pair >> 2)) * SK + (SK - WIN) + ((u % NT) * G + r) * TK;
                    } else if (i < 5) {
                        map = &maps.wq; c1 = h * 3; c2 = qd * 160 + i * 32;
                    } else if (u < NKV + 2) {
                        map = &maps.w2; c1 = qd * 5; c2 = h * 48 + (u - NKV) * 24; bytes = 7680;
                    } else {
                        map = &maps.wo; c1 = qd * 5; c2 = h * DH + (u - NKV - 2) * 32; bytes = 10240;
                    }
                } else {
                    map = i < 40 ? &maps.w1 : &maps.w3; c1 = qd * 6; c2 = (i < 40 ? i : i - 40) * 16;
                }
                const int depth = pace[1];
                const uint32_t slot = (uint32_t)i % NS, landed = i - depth;
                if (i >= NS) mbar_wait(bar_full + (NS + slot) * 8, ((uint32_t)i / NS - 1) & 1);
                mbar_expect_tx(bar_full + slot * 8, bytes);
                uint32_t dst = sb + SM_RING + slot * SLOT, fb = bar_full + slot * 8;
                asm volatile("" : "+r"(dst), "+r"(fb), "+l"(map), "+r"(c1), "+r"(c2));
                if (i >= depth) mbar_wait(bar_full + (landed % NS) * 8, (landed / NS) & 1);
                tma3d(dst, map, c1, c2, fb);
                pace[0] = landed + 1;
            }
            pace[0] = n_items - DEPTH;
        }
        return;
    }

    const int g = lane >> 2, t = lane & 3;
    uint32_t epoch;
    asm volatile("ld.relaxed.gpu.global.u32 %0, [%1];" : "=r"(epoch) : "l"(&g_sync.epoch) : "memory");

    if (warp == W_PACE) {
        const uint32_t tag = (epoch + 1u) & 1u;
        if (is_att && lane < 2 * G) st_fill4(g_ml + ((sg * G + (lane >> 1)) * G + r) * 32 + (lane & 1) * 4, tag ^ 1u);
        asm volatile("bar.sync 2, %0;" ::"n"(NTHR) : "memory");
        if (lane == 0) asm volatile("red.release.gpu.global.add.u32 [%0], 1;" ::"l"(&g_sync.inits) : "memory");
        if (!is_att) return;
        volatile int* pace = reinterpret_cast<volatile int*>(smem + SM_PACE);
        if (cta == 0 && lane == 0) asm volatile("st.relaxed.gpu.global.u32 [%0], %1;" ::"l"(&g_sync.prog[epoch & 1u]), "r"(0u) : "memory");
        int reported = 0, j = 0;
        bool due = false;
#pragma unroll 1
        for (unsigned it = 0;; it++) {
            const int landed = pace[0];
            int sum = 0;
            uint2 ml = make_uint2(~tag, 0u);
            unsigned n = (epoch + 1u) * NCTA;
            if (lane == 0 && reported < ITEMS_ATT - DEPTH)
                asm volatile("atom.relaxed.gpu.global.add.u32 %0, [%1], %2;"
                             : "=r"(sum) : "l"(&g_sync.prog[~epoch & 1u]), "r"(landed - reported) : "memory");
            if (due) {
                ml = ld_word(g_ml + (pair_of(sg, j) * G + lane % G) * 32);
                if (j == 0) asm volatile("ld.acquire.gpu.global.u32 %0, [%1];" : "=r"(n) : "l"(&g_sync.inits) : "memory");
            }
            reported = landed;
            if (lane == 0 && P_GAIN) {
                const int avg16 = sum / (NATT / 16), lag16 = avg16 - landed * 16 + P_BIAS;
                pace[1] = avg16 >= ITEMS_ATT * 16 - P_FLUSH ? 8 : min(max(DEPTH + ((lag16 * P_GAIN + 128) >> 8), P_DMIN), P_DMAX);
            }
            if (__all_sync(0xffffffffu, !((ml.x ^ tag) & 1u) && n == (epoch + 1u) * NCTA)) {
                const float mk = __uint_as_float(ml.x & ~1u);
                float M = mk;
#pragma unroll
                for (int o = G / 2; o; o >>= 1) M = fmaxf(M, shx(M, o));
                const float w = __expf(mk - M);
                float L = w * __uint_as_float(ml.y);
#pragma unroll
                for (int o = G / 2; o; o >>= 1) L += shx(L, o);
                if (lane == r) {
                    reinterpret_cast<float*>(smem + SM_LS)[16 + (j & 1)] = __fdividef(w, L);
                    mbar_arrive(bar_full + B_WRDY + (j & 1) * 8);
                    if (j == G - 1) TS(11);
                }
                j++;
                due = false;
            }
            if (j == G) {
                if (landed >= ITEMS_ATT - DEPTH) return;
            } else {
                if (!due) due = mbar_test(bar_full + B_WTRIG + (j & 1) * 8, (j >> 1) & 1);
                if (j < G - P_WFAST) __nanosleep(P_SLEEP);
            }
            if (it > SPIN_LIMIT) __trap();
        }
    }
    if (warp > W_PROD) {
        const uint32_t tag = (epoch + 1u) & 1u;
        const int e = tid - (W_PROD + 1) * 32;
        if (is_att) {
#pragma unroll 1
            for (int i = e; i < 192; i += NXW * 32)
                st_fill4(g_qpart + (cta * NB + i / 48) * VS + (i % 48) / 6 * 32 + (i % 6) * 4, tag ^ 1u);
            st_fill4(reinterpret_cast<float*>(g_oacc + cta * 64 + e), 0u);
            if (e < 32) *reinterpret_cast<uint32_t*>(smem + SM_HF + e * 16 + 12) = 0u;
        } else {
#pragma unroll 1
            for (int c = e; c < 256; c += NXW * 32) {
                const bf16* xp = x + qd * DM + (c >> 6) * 160 + ((c >> 3) & 7) * 8 + (c & 3) * 2 + ((c >> 2) & 1);
                asm volatile("st.relaxed.gpu.global.v4.f32 [%0], {%1,%2,%3,%4};"
                             ::"l"(g_acc + (qd * 32 + (c >> 3)) * ACS + (c & 7)), "f"(__bfloat162float(xp[0])),
                               "f"(__bfloat162float(xp[64])), "f"((c & 32) ? 0.f : __bfloat162float(xp[128])), "f"(0.f) : "memory");
            }
        }
        asm volatile("bar.sync 2, %0;" ::"n"(NTHR) : "memory");
        if (!is_att) return;
        {
            const uint32_t eq = (e >> 5) * 24 + min(lane, 23), xw = eq / 6, xr = eq % 6;
            mbar_wait(bar_full + B_QTRIG, 0);
            if (e == 0) TS(10);
            settle(P_QDELAY);
#pragma unroll 1
            for (int j = 0; j < G; j++) {
                const int pair = pair_of(sg, j);
                const float* src = g_qpart + ((pair >> 2) * 4 * NB + (pair & 3)) * VS + xw * 32 + xr * 4;
                uint4 v[4];
                uint32_t bad;
                unsigned spin = 0;
                do {
#pragma unroll
                    for (int k = 0; k < 4; k++) v[k] = ld_word2(src + k * NB * VS);
                    bad = 0;
#pragma unroll
                    for (int k = 0; k < 4; k++) bad |= (v[k].x ^ tag) | (v[k].z ^ tag);
                    if (++spin > SPIN_LIMIT) __trap();
                } while (bad & 1u);
#define SUM4(c) ((__uint_as_float(v[0].c) + __uint_as_float(v[1].c)) + (__uint_as_float(v[2].c) + __uint_as_float(v[3].c)))
                unsigned char* dst = smem + SM_QS + j * (DH * 2) + (xr & 1) * 192 + ((xr >> 1) * 8 + xw) * 4;
                *reinterpret_cast<uint32_t*>(dst) = pack_bf2(SUM4(x), SUM4(y));
                *reinterpret_cast<uint32_t*>(dst + 96) = pack_bf2(SUM4(z), SUM4(w));
#undef SUM4
                __syncwarp();
                if (lane == 0) mbar_arrive(bar_full + B_QRDY + j * 8);
                if (e == 0 && j == 0) TS(12);
            }
        }
#pragma unroll 1
        for (int b = 0; b < NB; b++) {
            if (b == NB - 1) {
#pragma unroll 1
                for (int i = e; i < 96; i += NXW * 32) {
                    const int k = (i % 24) * 2;
                    uint2 v;
                    unsigned spin = 0;
                    do {
                        v = ld_word(g_h + i / 24 * FF + h * 48 + k);
                        if (++spin > SPIN_LIMIT) __trap();
                    } while ((v.x ^ tag) & 1u);
                    *reinterpret_cast<uint32_t*>(smem + SM_HF + k / 24 * 256 + i / 24 * 64 + frag_off(k % 24)) = __byte_perm(v.x, v.y, 0x7632);
                }
                __syncwarp();
                if (lane == 0) mbar_arrive(bar_full + B_HRDY);
            }
            const float4* src = g_oacc + (h * NB + b) * 64 + e;
            uint32_t dst = sb + SM_OF + (e >> 5) * 256 + b * 64 + frag_off(lane), ordy = bar_full + B_ORDY;
            asm volatile("" : "+r"(dst), "+l"(src), "+r"(ordy));
            mbar_wait(bar_full + B_OTRIG + b * 8, 0);
            if (h * NB + b != sg * G + G - 1) settle(P_SETTLE);
            unsigned spin = 0;
            float o0, o1, o2, n;
            do {
                asm volatile("atom.relaxed.gpu.global.add.v4.f32 {%0,%1,%2,%3}, [%4], {%5,%5,%5,%5};"
                             : "=f"(o0), "=f"(o1), "=f"(o2), "=f"(n) : "l"(src), "f"(0.f) : "memory");
                asm volatile("st.shared.u16 [%0], %1;\nst.shared.u16 [%0+512], %2;\nst.shared.u16 [%0+1024], %3;"
                             ::"r"(dst), "h"(__bfloat16_as_ushort(__float2bfloat16_rn(o0))),
                               "h"(__bfloat16_as_ushort(__float2bfloat16_rn(o1))), "h"(__bfloat16_as_ushort(__float2bfloat16_rn(o2))) : "memory");
                if (++spin > SPIN_LIMIT) __trap();
            } while (n != (float)G);
            __syncwarp();
            if (lane == 0) mbar_arrive(ordy);
        }
        return;
    }

    if (warp < NB) {
        uint2 raw[5];
#pragma unroll
        for (int i = 0; i < 5; i++) raw[i] = __ldg(reinterpret_cast<const uint2*>(x + warp * DM) + i * 32 + lane);
        float s = 0.f;
#pragma unroll
        for (int i = 0; i < 5; i++) s += (bf_lo(raw[i].x) + bf_hi(raw[i].x)) + (bf_lo(raw[i].y) + bf_hi(raw[i].y));
#pragma unroll
        for (int o = 16; o; o >>= 1) s += shx(s, o);
        const float mean = s * (1.0f / DM);
        float q2 = 0.f;
#pragma unroll
        for (int i = 0; i < 5; i++) {
            const float d0 = bf_lo(raw[i].x) - mean, d1 = bf_hi(raw[i].x) - mean;
            const float d2 = bf_lo(raw[i].y) - mean, d3 = bf_hi(raw[i].y) - mean;
            q2 += (d0 * d0 + d1 * d1) + (d2 * d2 + d3 * d3);
        }
#pragma unroll
        for (int o = 16; o; o >>= 1) q2 += shx(q2, o);
        const float mb = bf_round(mean);
        const float rs = __frcp_rn(bf_round(__fsqrt_rn(bf_round(bf_round(q2 * (1.0f / DM)) + 1e-5f))));
        const uint32_t k = (lane * 4) & 31;
        unsigned char* dst = smem + SM_XF + warp * 64 +
            (is_att ? (lane >> 3) * 256 + frag_off(k) : (lane >> 2) * 256 + frag_off(k & 15));
        const uint32_t step = is_att ? 1024 : 2048;
#pragma unroll
        for (int i = 0; i < 5; i++) {
            const uint32_t d0 = pack_bf2(bf_lo(raw[i].x) - mb, bf_hi(raw[i].x) - mb);
            const uint32_t d1 = pack_bf2(bf_lo(raw[i].y) - mb, bf_hi(raw[i].y) - mb);
            *reinterpret_cast<uint32_t*>(dst + i * step) = pack_bf2(bf_lo(d0) * rs, bf_hi(d0) * rs);
            *reinterpret_cast<uint32_t*>(dst + i * step + 16) = pack_bf2(bf_lo(d1) * rs, bf_hi(d1) * rs);
        }
    }
    asm volatile("bar.sync 2, %0;" ::"n"(NTHR) : "memory");
    uint32_t tag = (epoch + 1u) & 1u;
    asm volatile("" : "+r"(tag));
    if (tid == 0) TS(3);

    Ring ring{bar_full, sb + SM_RING, 0u, bar_full};
    float lo[3][4] = {}, hi[3][4] = {};
    uint32_t off[3];
    const uint32_t a_lane = (g & 3) * 64 + t * 16;

    if (is_att) {
        float* lsum = reinterpret_cast<float*>(smem + SM_LS);
#pragma unroll 1
        for (int j = -1; j <= G; j++) {
            if (j >= 0 && j < G) {
                uint32_t qf[6][4];
                mbar_wait(bar_full + B_QRDY + j * 8, 0);
                if (j == 0 && tid == 0) TS(6);
#pragma unroll
                for (int i = 0; i < 6; i++) lds128(sb + SM_QS + j * (DH * 2) + t * 96 + i * 16, qf[i]);
                const uint32_t key = (warp & 1) * 16 + (lane & 15);
                float sv[NT / 4], m = -INFINITY;
#pragma unroll
                for (int rr = 0; rr < NT / 4; rr++) {
                    const uint32_t item = 5 + max(2 * j - 1, 0) * NT + rr * 4 + (warp >> 1), slot = item % NS;
#pragma unroll
                    for (int s = 0; s < 3; s++)
                        off[s] = sb + SM_RING + slot * SLOT + key * 384 + s * 128 + (((lane >> 4) ^ ((3 * key + s) & 7)) << 4);
                    pin3(off);
                    mbar_wait(bar_full + slot * 8, (item / NS) & 1);
                    float c[3][4] = {};
#pragma unroll
                    for (int dq = 0; dq < 4; dq++)
#pragma unroll
                        for (int s = 0; s < 3; s++) {
                            uint32_t a[4];
                            ldsm_x4(off[s] ^ (dq << 5), a);
                            mma16816(c[s], a, qf[s * 2 + (dq >> 1)][(dq & 1) * 2], qf[s * 2 + (dq >> 1)][(dq & 1) * 2 + 1]);
                        }
                    __syncwarp();
                    if (lane == 0)
                        asm volatile("mbarrier.arrive.shared::cta.b64 _, [%0], %1;" ::"r"(bar_full + (NS + slot) * 8), "n"(NCW / 2) : "memory");
                    const float raw = (t & 1) ? (c[0][2] + c[1][2]) + c[2][2] : (c[0][0] + c[1][0]) + c[2][0];
                    sv[rr] = bf_round(bf_round(raw) * 0.07216878364870323f);
                    m = fmaxf(m, sv[rr]);
                }
                ring.skip(NT);
                if (tid == 0 && j == G - 1) TS(14);
                m = fmaxf(m, shx(m, 1));
#pragma unroll
                for (int o = 4; o < 32; o <<= 1) m = fmaxf(m, shx(m, o));
                if (lane == 0) lsum[8 + warp] = m;
                cons_bar();
                {
                    const float4 m0 = reinterpret_cast<const float4*>(lsum)[2], m1 = reinterpret_cast<const float4*>(lsum)[3];
                    m = fmaxf(fmaxf(fmaxf(m0.x, m0.y), fmaxf(m0.z, m0.w)), fmaxf(fmaxf(m1.x, m1.y), fmaxf(m1.z, m1.w)));
                }
                float l = 0.f;
#pragma unroll
                for (int rr = 0; rr < NT / 4; rr++) {
                    const float p = __expf(sv[rr] - m);
                    l += p;
                    *reinterpret_cast<bf16*>(smem + SM_PF + ((j & 1) * NT + rr * 4 + (warp >> 1)) * 64 + frag_off((warp & 1) * 16 + (t & 1) * 8 + g)) =
                        __float2bfloat16_rn(p);
                }
                l += shx(l, 1);
#pragma unroll
                for (int o = 4; o < 32; o <<= 1) l += shx(l, o);
                if (lane == 0) lsum[warp] = l;
                cons_bar();
                if (tid < 4) {
                    const float4 l0 = reinterpret_cast<const float4*>(lsum)[0], l1 = reinterpret_cast<const float4*>(lsum)[1];
                    st_tag2(g_ml + (pair_of(sg, j) * G + r) * 32 + tid * 2, m,
                            ((l0.x + l0.y) + (l0.z + l0.w)) + ((l1.x + l1.y) + (l1.z + l1.w)), tag);
                    if (tid == 0) mbar_arrive(bar_full + B_WTRIG + (j & 1) * 8);
                }
                if (tid == 0 && j == G - 1) TS(13);
                if (j == 0) continue;
            }
            const bool kv = j >= 0;
            const int pair = pair_of(sg, j - 1);
            uint32_t trig = !kv ? bar_full + B_QTRIG : (pair >> 2) == h ? bar_full + B_OTRIG + (pair & 3) * 8 : 0;
            if (tid != 0) trig = 0;
            float4* oacc = g_oacc + pair * 64 + warp * 8 + 2 * t + g;
            uint32_t wrdy = bar_full + B_WRDY + (~j & 1) * 8;
#pragma unroll
            for (int s = 0; s < 3; s++) off[s] = lane * 384 + s * 128 + ((warp ^ ((3 * lane + s) & 7)) << 4);
            asm volatile("" : "+l"(oacc), "+r"(trig), "+r"(wrdy));
            gemv_loop(ring, kv ? NT : 5, kv ? sb + SM_PF + (~j & 1) * (NT * 64) + t * 16 : sb + SM_XF + qd * 5 * 256 + a_lane,
                      kv ? 64 : 256, off, lo, hi, lane);
            if (kv) {
                mbar_wait(wrdy, ((j - 1) >> 1) & 1);
                const float w = lsum[16 + (~j & 1)];
                if (g < 2)
                    asm volatile("red.relaxed.gpu.global.add.v4.f32 [%0], {%1,%2,%3,%4};"
                                 ::"l"(oacc), "f"(w * (g ? lo[0][1] + hi[0][3] : lo[0][0] + hi[0][2])),
                                   "f"(w * (g ? lo[1][1] + hi[1][3] : lo[1][0] + hi[1][2])),
                                   "f"(w * (g ? lo[2][1] + hi[2][3] : lo[2][0] + hi[2][2])), "f"(1.0f) : "memory");
            } else if (g < NB) {
#pragma unroll
                for (int s = 0; s < 3; s++)
                    st_tag2(g_qpart + (cta * NB + g) * VS + warp * 32 + 2 * t + s * 8, lo[s][0] + hi[s][2], lo[s][1] + hi[s][3], tag);
            }
            if (trig) mbar_arrive(trig);
            if (j == G && tid == 0) TS(5);
            if (j >= 0 && j < G && j != P_DRY) continue;
            if (tid == 0 && j < 0) TS(4);

            {
                const bool pass = j == G;
                constexpr int I0 = 5 + NKV;
                static_assert(((I0 / NS) & 1) == 0 && I0 / NS == (I0 + 7) / NS, "tail items complete an even phase");
                const uint32_t done = bar_full + B_QTRIG;
                uint32_t fb = pass ? bar_full + (I0 % NS) * 8 : done, fs = pass ? 8 : 0, ordy = pass ? bar_full + B_ORDY : done;
                uint32_t off2[3], a[8][4], b[8][3][4], a_addr = sb + SM_HF + a_lane;
#pragma unroll
                for (int s = 0; s < 3; s++) {
                    const uint32_t w64 = lane * 320 + (warp + 8 * s) * 16;
                    off[s] = sb + SM_RING + (I0 % NS) * SLOT + (w64 ^ (((w64 >> 7) & 3) << 4));
                    off2[s] = lane < 24 ? off[s] : off[s] - 8 * 320;
#pragma unroll
                    for (int e = 0; e < 4; e++) { lo[s][e] = 0.f; hi[s][e] = 0.f; }
                }
                const float4* accp = g_acc + (((g & 3) * 4 + qd) * NCW + warp) * ACS + (g >> 2) * 4 + t;
                bf16* outp = out + (g & 3) * DM + qd * 160 + warp * 8 + 2 * t + (g >> 2);
                pin3(off);
                asm volatile("" : "+l"(accp), "+l"(outp), "+r"(a_addr), "+r"(ordy), "+r"(fb), "+r"(fs));
                auto load_b = [&](int i, bool& next) {
                    if (!next) mbar_wait(fb + i * fs, 0);
                    if (i < 7) next = mbar_test(fb + (i + 1) * fs, 0);
#pragma unroll
                    for (int s = 0; s < 3; s++)
                        if (s < 2 || warp < 4) ldsm_x4_t((i < 2 ? off2[s] : off[s]) + i * SLOT, b[i][s]);
                };
                auto mul = [&](int i) {
#pragma unroll
                    for (int s = 0; s < 3; s++)
                        if (s < 2 || warp < 4) { mma16816(lo[s], a[i], b[i][s][0], b[i][s][1]); mma16816(hi[s], a[i], b[i][s][2], b[i][s][3]); }
                };
                bool next = mbar_test(fb, 0);
                mbar_wait(pass ? bar_full + B_HRDY : done, 0);
                lds128(a_addr, a[0]);
                lds128(a_addr + 256, a[1]);
                load_b(0, next);
                load_b(1, next);
                bool early = mbar_test(ordy, 0);
                mul(0);
                mul(1);
                if (pass && tid == 0) TS(31);
                unsigned spin = 0;
                while (!early && !mbar_test(fb + P_DEC * fs, 0)) {
                    early = mbar_test(ordy, 0);
                    if (++spin > SPIN_LIMIT) __trap();
                }
                if (pass ? __all_sync(0xffffffffu, early) : j < 0) {
                    if (pass && tid == 0) TS(7);
#pragma unroll
                    for (int i = 2; i < 8; i++) lds128(a_addr + i * 256, a[i]);
                    load_b(2, next);
#pragma unroll
                    for (int i = 2; i < 7; i++) { load_b(i + 1, next); mul(i); }
                    mul(7);
                } else {
#pragma unroll
                    for (int i = 2; i < 8; i++) load_b(i, next);
                    mbar_wait(ordy, 0);
                    if (pass && tid == 0) TS(7);
#pragma unroll
                    for (int i = 2; i < 8; i++) lds128(a_addr + i * 256, a[i]);
#pragma unroll
                    for (int i = 2; i < 8; i++) mul(i);
                }
                if (pass && tid == 0) TS(8);
                add_out(accp, outp, lo, hi, g >= NB, warp < 4, pass, epoch);
            }
        }
        if (tid == 0) { TS(9); TS_DUMP(3, 32); }
    } else {
        float gate[6][2];
#pragma unroll
        for (int s = 0; s < 3; s++) {
            const uint32_t r128 = (lane & 15) * 6 + 2 * s + (lane >> 4);
            off[s] = r128 * 128 + ((warp ^ (r128 & 7)) << 4);
        }
#pragma unroll 1
        for (int ps = 0; ps < 2; ps++) {
#pragma unroll
            for (int s = 0; s < 3; s++) {
                gate[2 * s][0] = lo[s][0]; gate[2 * s][1] = lo[s][1];
                gate[2 * s + 1][0] = hi[s][0]; gate[2 * s + 1][1] = hi[s][1];
            }
            gemv_loop(ring, 40, sb + SM_XF + a_lane, 256, off, lo, hi, lane);
        }
#pragma unroll
        for (int p = 0; p < 6; p++) {
            float hv[2];
#pragma unroll
            for (int e = 0; e < 2; e++) {
                const float gt = bf_round(gate[p][e]);
                hv[e] = bf_round(bf_round(__fdividef(gt, 1.0f + __expf(-gt))) * bf_round((p & 1) ? hi[p >> 1][e] : lo[p >> 1][e]));
            }
            if (g < NB) st_tag2(g_h + g * FF + qd * 384 + p * 64 + warp * 8 + 2 * t, hv[0], hv[1], tag);
        }
        if (tid == 0) { TS(9); TS_DUMP(3, 10); }
    }
}

typedef CUresult (*EncodeFn)(CUtensorMap*, CUtensorMapDataType, cuuint32_t, void*, const cuuint64_t*, const cuuint64_t*,
                             const cuuint32_t*, const cuuint32_t*, CUtensorMapInterleave, CUtensorMapSwizzle,
                             CUtensorMapL2promotion, CUtensorMapFloatOOBfill);

void make_map(EncodeFn enc, CUtensorMap* m, const void* p, uint64_t rows, uint64_t cols, uint32_t inner, uint32_t parts,
              uint32_t box_rows) {
    const cuuint64_t dims[3] = {inner, cols / inner, rows};
    const cuuint64_t strides[2] = {inner * 2ull, cols * 2ull};
    const cuuint32_t box[3] = {inner, parts, box_rows};
    const cuuint32_t es[3] = {1, 1, 1};
    enc(m, CU_TENSOR_MAP_DATA_TYPE_BFLOAT16, 3, const_cast<void*>(p), dims, strides, box, es, CU_TENSOR_MAP_INTERLEAVE_NONE,
        inner == 64 ? CU_TENSOR_MAP_SWIZZLE_128B : CU_TENSOR_MAP_SWIZZLE_64B, CU_TENSOR_MAP_L2_PROMOTION_NONE,
        CU_TENSOR_MAP_FLOAT_OOB_FILL_NONE);
}

}

extern "C" void kernel_launch(void* const* d_in, const int* in_sizes, int n_in, void* d_out, int out_size) {
    (void)in_sizes; (void)n_in; (void)out_size;
    static EncodeFn enc = nullptr;
    if (!enc) {
        void* fn = nullptr;
        cudaDriverEntryPointQueryResult qr;
        cudaGetDriverEntryPoint("cuTensorMapEncodeTiled", &fn, cudaEnableDefault, &qr);
        enc = (EncodeFn)fn;
        cudaFuncSetAttribute(fused_decode_kernel, cudaFuncAttributeMaxDynamicSharedMemorySize, SM_TOTAL);
    }
    Maps maps;
    make_map(enc, &maps.k, d_in[1], (uint64_t)NB * NH * SK, DH, 64, 3, TK);
    make_map(enc, &maps.v, d_in[2], (uint64_t)NB * NH * SK, DH, 64, 3, TK);
    make_map(enc, &maps.wq, d_in[3], DM, NH * DH, 64, 3, 32);
    make_map(enc, &maps.wo, d_in[4], NH * DH, DM, 32, 5, 32);
    make_map(enc, &maps.w1, d_in[6], DM, FF, 64, 6, 16);
    make_map(enc, &maps.w3, d_in[7], DM, FF, 64, 6, 16);
    make_map(enc, &maps.w2, d_in[8], FF, DM, 32, 5, 24);
    fused_decode_kernel<<<NCTA, NTHR, SM_TOTAL>>>(maps, (const bf16*)d_in[0], (bf16*)d_out);
}
```

```cpp
#include <cuda_runtime.h>
#include <cuda.h>
#include <cuda_bf16.h>
#include <stdint.h>

namespace {

typedef __nv_bfloat16 bf16;

constexpr int NB = 4, DM = 640, NH = 32, DH = 192, SK = 8192, WIN = 2048, FF = 1536;

#define P_G 16
#define P_DEPTH 4
#define P_DEPTH_FFN 5
#define P_GAIN 8
#define P_BIAS 16
#define P_SLEEP 500
#define P_DMIN P_DEPTH
#define P_DMAX 6
#define P_SETTLE 3000
#define P_QDELAY 1600
#define P_NSL 20
#define P_DRY 2
#define P_FLUSH 112
#define P_DEC 6
#define P_WFAST 2
#define P_HEADMAJOR 0
#define P_NS 16

constexpr int G = P_G;
constexpr int TK = 32;
constexpr int NT = WIN / TK / G;
constexpr int NSTEP = 16;
constexpr int WPS = G / NSTEP;
constexpr int HSTEP = 11;
constexpr int NS = P_NS;
constexpr int SLOT = 12288;
constexpr int DEPTH = P_DEPTH;
#define P_D0 5
constexpr int DEPTH0 = P_D0;
static_assert(DEPTH0 <= 5, "DEPTH0");
constexpr int NATT = 128, NFFN = 4, NCTA = NATT + NFFN;
constexpr int NCW = 8;
constexpr int NXW = 2;
constexpr int W_PROD = NCW, W_PACE = NCW + 1 + NXW;
constexpr int NTHR = (W_PACE + 1) * 32;
constexpr int NSRC = NH;
constexpr int VS = 256;
#define P_ACS 16
constexpr int ACS = P_ACS;
static_assert(G == 16 || G == 32, "G");

constexpr int SM_RING = 0;
constexpr int SM_XF = SM_RING + NS * SLOT;
constexpr int SM_QS = SM_XF + 20 * 256;
constexpr int SM_PF = SM_QS + G * DH * 2;
constexpr int SM_HF = SM_PF + 2 * 4 * 64;
constexpr int SM_OF = SM_HF + 2 * 256;
constexpr int SM_LS = SM_OF + 6 * 256;
constexpr int SM_ATT_END = SM_LS + 96;
constexpr int SM_FFN_END = SM_XF + 40 * 256;
constexpr int SM_BAR = SM_ATT_END > SM_FFN_END ? SM_ATT_END : SM_FFN_END;
constexpr int B_QRDY = 2 * NS * 8, B_ORDY = B_QRDY + NSTEP * 8, B_OTRIG = B_ORDY + 8, B_QTRIG = B_OTRIG + 32,
              B_WTRIG = B_QTRIG + 8, B_WRDY = B_WTRIG + 16, B_HTRIG = B_WRDY + 16, B_HRDY = B_HTRIG + 8,
              NBAR = 2 * NS + NSTEP + 12;
constexpr int SM_PACE = SM_BAR + NBAR * 8;
constexpr int SM_TS = SM_PACE + 8;
constexpr int SM_TOTAL = SM_TS + 256;
static_assert(SM_TOTAL <= 232448, "smem");

constexpr int NKV = 2 * NT * G;
constexpr int ITEMS_ATT = 5 + NKV + 2 + 6;
constexpr int ITEMS_FFN = 80;

struct Maps { CUtensorMap k, v, wq, wo, w1, w3, w2; };

struct alignas(32) Sync { unsigned epoch, inits, prog[2]; };
__device__ Sync g_sync;
__device__ __align__(128) float g_qpart[NATT * NB * VS];
__device__ __align__(128) float g_ml[NATT * G * 32];
__device__ __align__(128) float g_h[NB * FF];
__device__ __align__(128) float4 g_oacc[NATT * 64];
__device__ __align__(128) float4 g_acc[NB * 4 * NCW * ACS];
#define TS(i)
#define TS_DUMP(lo, hi)

constexpr unsigned SPIN_LIMIT = 1u << 24;

__device__ __forceinline__ void mbar_init(uint32_t bar, int cnt) {
    asm volatile("mbarrier.init.shared::cta.b64 [%0], %1;" ::"r"(bar), "r"(cnt) : "memory");
}
__device__ __forceinline__ void mbar_expect_tx(uint32_t bar, uint32_t bytes) {
    asm volatile("mbarrier.arrive.expect_tx.shared::cta.b64 _, [%0], %1;" ::"r"(bar), "r"(bytes) : "memory");
}
__device__ __forceinline__ void mbar_arrive(uint32_t bar) {
    asm volatile("mbarrier.arrive.shared::cta.b64 _, [%0];" ::"r"(bar) : "memory");
}
__device__ __forceinline__ void mbar_wait(uint32_t bar, uint32_t parity) {
    asm volatile("{\n.reg .pred p, q;\n.reg .u32 n;\nmov.u32 n, 0;\n"
                 "W: mbarrier.try_wait.parity.shared::cta.b64 p, [%0], %1;\n"
                 "@p bra D;\nadd.u32 n, n, 1;\nsetp.lt.u32 q, n, %2;\n@q bra W;\ntrap;\nD:\n}"
                 ::"r"(bar), "r"(parity), "n"(SPIN_LIMIT) : "memory");
}
__device__ __forceinline__ bool mbar_test(uint32_t bar, uint32_t parity) {
    uint32_t ok;
    asm volatile("{\n.reg .pred p;\nmbarrier.test_wait.parity.shared::cta.b64 p, [%1], %2;\nselp.u32 %0, 1, 0, p;\n}"
                 : "=r"(ok) : "r"(bar), "r"(parity) : "memory");
    return ok;
}
__device__ __forceinline__ void tma3d(uint32_t dst, const CUtensorMap* map, int c1, int c2, uint32_t bar) {
    const uint64_t pol = 0x12F0000000000000ull;
    asm volatile("cp.async.bulk.tensor.3d.shared::cluster.global.mbarrier::complete_tx::bytes.L2::cache_hint "
                 "[%0], [%1, {%2, %3, %4}], [%5], %6;"
                 ::"r"(dst), "l"(map), "r"(0), "r"(c1), "r"(c2), "r"(bar), "l"(pol) : "memory");
}
__device__ __forceinline__ void ldsm_x4(uint32_t addr, uint32_t (&r)[4]) {
    asm volatile("ldmatrix.sync.aligned.m8n8.x4.shared.b16 {%0,%1,%2,%3}, [%4];"
                 : "=r"(r[0]), "=r"(r[1]), "=r"(r[2]), "=r"(r[3]) : "r"(addr) : "memory");
}
__device__ __forceinline__ void ldsm_x4_t(uint32_t addr, uint32_t (&r)[4]) {
    asm volatile("ldmatrix.sync.aligned.m8n8.x4.trans.shared.b16 {%0,%1,%2,%3}, [%4];"
                 : "=r"(r[0]), "=r"(r[1]), "=r"(r[2]), "=r"(r[3]) : "r"(addr) : "memory");
}
__device__ __forceinline__ void lds128(uint32_t addr, uint32_t (&r)[4]) {
    asm volatile("ld.shared.v4.u32 {%0,%1,%2,%3}, [%4];"
                 : "=r"(r[0]), "=r"(r[1]), "=r"(r[2]), "=r"(r[3]) : "r"(addr) : "memory");
}
__device__ __forceinline__ void mma16816(float (&c)[4], const uint32_t (&a)[4], uint32_t b0, uint32_t b1) {
    asm volatile("mma.sync.aligned.m16n8k16.row.col.f32.bf16.bf16.f32 {%0,%1,%2,%3}, {%4,%5,%6,%7}, {%8,%9}, {%0,%1,%2,%3};"
                 : "+f"(c[0]), "+f"(c[1]), "+f"(c[2]), "+f"(c[3])
                 : "r"(a[0]), "r"(a[1]), "r"(a[2]), "r"(a[3]), "r"(b0), "r"(b1));
}
__device__ __forceinline__ void cons_bar() { asm volatile("bar.sync 1, 256;" ::: "memory"); }

__device__ __forceinline__ float bf_round(float v) { return __bfloat162float(__float2bfloat16_rn(v)); }
__device__ __forceinline__ uint32_t pack_bf2(float lo, float hi) {
    __nv_bfloat162 t = __floats2bfloat162_rn(lo, hi);
    return *reinterpret_cast<uint32_t*>(&t);
}
__device__ __forceinline__ float bf_lo(uint32_t u) { return __uint_as_float(u << 16); }
__device__ __forceinline__ float bf_hi(uint32_t u) { return __uint_as_float(u & 0xffff0000u); }
__device__ __forceinline__ float shx(float v, int o) { return __shfl_xor_sync(0xffffffffu, v, o); }

__device__ __forceinline__ uint32_t frag_off(uint32_t k) {
    return ((k >> 1) & 3) * 16 + ((k >> 3) & 1) * 8 + ((k >> 4) & 1) * 4 + (k & 1) * 2;
}

__device__ __forceinline__ void st_tag2(float* p, float a, float b, uint32_t tag) {
    asm volatile("{\n.reg .b64 w;\n.reg .b32 x;\nlop3.b32 x, %1, 0xfffffffe, %3, 0xea;\nmov.b64 w, {x, %2};\n"
                 "st.relaxed.gpu.global.b64 [%0], w;\n}"
                 ::"l"(p), "r"(__float_as_uint(a)), "r"(__float_as_uint(b)), "r"(tag) : "memory");
}
__device__ __forceinline__ void st_fill4(float* p, uint32_t v) {
    asm volatile("{\n.reg .b64 w;\nmov.b64 w, {%1, %1};\nst.relaxed.gpu.global.v2.b64 [%0], {w, w};\n}" ::"l"(p), "r"(v) : "memory");
}
__device__ __forceinline__ uint2 ld_word(const float* p) {
    uint2 v;
    asm volatile("{\n.reg .b64 w;\nld.relaxed.gpu.global.b64 w, [%2];\nmov.b64 {%0,%1}, w;\n}" : "=r"(v.x), "=r"(v.y) : "l"(p) : "memory");
    return v;
}
__device__ __forceinline__ uint4 ld_word2(const float* p) {
    uint4 v;
    asm volatile("{\n.reg .b64 w0, w1;\nld.relaxed.gpu.global.v2.b64 {w0, w1}, [%4];\nmov.b64 {%0,%1}, w0;\nmov.b64 {%2,%3}, w1;\n}"
                 : "=r"(v.x), "=r"(v.y), "=r"(v.z), "=r"(v.w) : "l"(p) : "memory");
    return v;
}

__device__ __forceinline__ void add_out(const float4* acc, bf16* out, const float (&lo)[3][4], const float (&hi)[3][4],
                                        bool odd, bool third, bool live, uint32_t epoch) {
    const float v0 = odd ? lo[0][1] + hi[0][3] : lo[0][0] + hi[0][2];
    const float v1 = odd ? lo[1][1] + hi[1][3] : lo[1][0] + hi[1][2];
    const float v2 = odd ? lo[2][1] + hi[2][3] : lo[2][0] + hi[2][2];
    float o0, o1, o2, n = 0.f;
    asm volatile("{\n.reg .pred p;\nsetp.ne.u32 p, %5, 0;\n"
                 "@p atom.relaxed.gpu.global.add.v4.f32 {%0,%1,%2,%3}, [%4], {%6,%7,%8,%9};\n}"
                 : "=f"(o0), "=f"(o1), "=f"(o2), "+f"(n)
                 : "l"(acc), "r"((uint32_t)live), "f"(v0), "f"(v1), "f"(v2), "f"(1.0f) : "memory");
    asm volatile("{\n.reg .pred p, q;\nsetp.eq.f32 p, %4, %5;\nsetp.ne.and.u32 q, %6, 0, p;\n"
                 "@p st.global.u16 [%0], %1;\n@p st.global.u16 [%0+128], %2;\n@q st.global.u16 [%0+256], %3;\n}"
                 ::"l"(out), "h"(__bfloat16_as_ushort(__float2bfloat16_rn(o0 + v0))),
                   "h"(__bfloat16_as_ushort(__float2bfloat16_rn(o1 + v1))), "h"(__bfloat16_as_ushort(__float2bfloat16_rn(o2 + v2))),
                   "f"(n), "f"((float)(NSRC - 1)), "r"((uint32_t)third) : "memory");
    if (acc == g_acc && n == (float)(NSRC - 1))
        asm volatile("st.relaxed.gpu.global.u32 [%0], %1;" ::"l"(&g_sync.epoch), "r"(epoch + 1u) : "memory");
}

__device__ __forceinline__ int pair_of(int sg, uint32_t j) { return sg * G + (j % (G / 4)) * 4 + j / (G / 4); }
__device__ __forceinline__ int order_of(int r, int b) { return b * (G / 4) + (r >> 2); }

__device__ __forceinline__ void settle(int cycles) {
    const uint32_t t0 = (uint32_t)clock();
    while ((uint32_t)clock() - t0 < (uint32_t)cycles) __nanosleep(P_NSL);
}

struct Ring {
    uint32_t full, addr, phase, first_full;
    __device__ __forceinline__ void wait() const { mbar_wait(full, phase); }
    __device__ __forceinline__ void skip(int n) {
        full += n * 8; addr += n * SLOT;
        if (full >= first_full + NS * 8) { full -= NS * 8; addr -= NS * SLOT; phase ^= 1; }
    }
    __device__ __forceinline__ void release(int lane) {
        __syncwarp();
        if (lane == 0) mbar_arrive(full + NS * 8);
        full += 8; addr += SLOT;
        if (full == first_full + NS * 8) { full = first_full; addr -= NS * SLOT; phase ^= 1; }
    }
};

__device__ __forceinline__ void pin3(uint32_t (&v)[3]) {
    asm volatile("" : "+r"(v[0]), "+r"(v[1]), "+r"(v[2]));
}
__device__ __forceinline__ void gemv_loop(Ring& ring, int n, uint32_t a_addr, uint32_t a_step, uint32_t (&off)[3],
                                          float (&lo)[3][4], float (&hi)[3][4], int lane) {
    pin3(off);
#pragma unroll
    for (int s = 0; s < 3; s++)
#pragma unroll
        for (int e = 0; e < 4; e++) { lo[s][e] = 0.f; hi[s][e] = 0.f; }
#pragma unroll 1
    for (int it = 0; it < n; it++) {
        uint32_t a[4], b[3][4];
        lds128(a_addr, a);
        a_addr += a_step;
        ring.wait();
#pragma unroll
        for (int s = 0; s < 3; s++) ldsm_x4_t(ring.addr + off[s], b[s]);
#pragma unroll
        for (int s = 0; s < 3; s++) { mma16816(lo[s], a, b[s][0], b[s][1]); mma16816(hi[s], a, b[s][2], b[s][3]); }
        ring.release(lane);
    }
}

__global__ void __launch_bounds__(NTHR, 1)
fused_decode_kernel(const __grid_constant__ Maps maps, const bf16* __restrict__ x, bf16* __restrict__ out) {
    extern __shared__ __align__(1024) unsigned char smem[];
    const uint32_t sb = (uint32_t)__cvta_generic_to_shared(smem);
    const uint32_t bar_full = sb + SM_BAR;
    if (threadIdx.x == 0 && blockIdx.x < NATT) {
        TS(0);
#pragma unroll 1
        for (int i = 0; i < DEPTH0; i++) {
            mbar_init(bar_full + i * 8, 1);
            mbar_expect_tx(bar_full + i * 8, 12288);
            tma3d(sb + SM_RING + i * SLOT, &maps.wq, (blockIdx.x >> 2) * 3, (blockIdx.x & 3) * 160 + i * 32, bar_full + i * 8);
        }
        TS(1);
    }
    unsigned ptid, cta;
    asm volatile("mov.u32 %0, %%tid.x;\nmov.u32 %1, %%ctaid.x;" : "=r"(ptid), "=r"(cta));
    const int tid = ptid < 32 ? ptid + NCW * 32 : ptid < (NCW + 1) * 32 ? ptid - 32 : ptid;
    const int warp = tid >> 5, lane = tid & 31;
    const bool is_att = cta < NATT;
    const int h = cta >> 2, qd = cta & 3;
    const int sg = cta / G, r = cta % G;

    if (warp == NCW) {
        volatile int* pace = reinterpret_cast<volatile int*>(smem + SM_PACE);
        if (lane == 0) {
            if (!is_att) { TS(0); TS(1); }
            pace[0] = 0;
            pace[1] = is_att ? DEPTH : P_DEPTH_FFN;
#pragma unroll
            for (int i = 0; i < NBAR; i++)
                if (i >= DEPTH0 || !is_att)
                mbar_init(bar_full + i * 8, i < NS ? 1 : i < 2 * NS ? NCW : i < 2 * NS + NSTEP ? NXW : i == 2 * NS + NSTEP ? NXW * NB : i == NBAR - 1 ? NXW : 1);
            asm volatile("fence.mbarrier_init.release.cluster;" ::: "memory");
        }
        __syncwarp();
        asm volatile("bar.arrive 2, %0;" ::"n"(NTHR) : "memory");
        if (lane == 0) {
            const int n_items = is_att ? ITEMS_ATT : ITEMS_FFN;

            asm volatile("prefetch.tensormap [%0];" ::"l"(is_att ? &maps.k : &maps.w3) : "memory");
            asm volatile("prefetch.tensormap [%0];" ::"l"(&maps.v) : "memory");
            asm volatile("prefetch.tensormap [%0];" ::"l"(&maps.w2) : "memory");
            asm volatile("prefetch.tensormap [%0];" ::"l"(&maps.wo) : "memory");
#pragma unroll 1
            for (int i = is_att ? DEPTH0 : 0; i < n_items; i++) {
                const CUtensorMap* map;
                int c1, c2;
                uint32_t bytes = 12288;
                if (is_att) {
                    const uint32_t u = i - 5;
                    if (u < NKV) {
                        const uint32_t blk = u / 4;
                        const bool isv = blk == 2 * NSTEP - 1 || (blk && !(blk & 1));
                        const int pair = pair_of(sg, (isv ? (blk - 1) / 2 : (blk + 1) / 2) * WPS + (u % 4) / NT);
                        map = isv ? &maps.v : &maps.k;
                        c1 = 0;
                        c2 = ((pair & 3) * NH + (pair >> 2)) * SK + (SK - WIN) + ((u % NT) * G + r) * TK;
                    } else if (i < 5) {
                        map = &maps.wq; c1 = h * 3; c2 = qd * 160 + i * 32;
                    } else if (u < NKV + 2) {
                        map = &maps.w2; c1 = qd * 5; c2 = h * 48 + (u - NKV) * 24; bytes = 7680;
                    } else {
                        map = &maps.wo; c1 = qd * 5; c2 = h * DH + (u - NKV - 2) * 32; bytes = 10240;
                    }
                } else {
                    map = i < 40 ? &maps.w1 : &maps.w3; c1 = qd * 6; c2 = (i < 40 ? i : i - 40) * 16;
                }
                const int depth = pace[1];
                const uint32_t slot = (uint32_t)i % NS, landed = i - depth;
                if (i >= NS) mbar_wait(bar_full + (NS + slot) * 8, ((uint32_t)i / NS - 1) & 1);
                mbar_expect_tx(bar_full + slot * 8, bytes);
                uint32_t dst = sb + SM_RING + slot * SLOT, fb = bar_full + slot * 8;
                asm volatile("" : "+r"(dst), "+r"(fb), "+l"(map), "+r"(c1), "+r"(c2));
                if (i >= depth) mbar_wait(bar_full + (landed % NS) * 8, (landed / NS) & 1);
                tma3d(dst, map, c1, c2, fb);
                pace[0] = landed + 1;
            }
            pace[0] = n_items - DEPTH;
        }
        return;
    }

    const int g = lane >> 2, t = lane & 3;
    uint32_t epoch;
    asm volatile("ld.relaxed.gpu.global.u32 %0, [%1];" : "=r"(epoch) : "l"(&g_sync.epoch) : "memory");

    if (warp == W_PACE) {
        const uint32_t tag = (epoch + 1u) & 1u;
        if (is_att) {
#pragma unroll
            for (int u = 0; u < WPS; u++) st_fill4(g_ml + ((sg * G + u * 16 + (lane >> 1)) * G + r) * 32 + (lane & 1) * 4, tag ^ 1u);
        }
        asm volatile("bar.sync 2, %0;" ::"n"(NTHR) : "memory");
        if (lane == 0) asm volatile("red.release.gpu.global.add.u32 [%0], 1;" ::"l"(&g_sync.inits) : "memory");
        if (!is_att) return;
        volatile int* pace = reinterpret_cast<volatile int*>(smem + SM_PACE);
        if (cta == 0 && lane == 0) asm volatile("st.relaxed.gpu.global.u32 [%0], %1;" ::"l"(&g_sync.prog[epoch & 1u]), "r"(0u) : "memory");
        int reported = 0, j = 0;
        bool due = false;
#pragma unroll 1
        for (unsigned it = 0;; it++) {
            const int landed = pace[0];
            int sum = 0;
            uint2 ml[WPS];
            uint32_t bad = 1u;
            unsigned n = (epoch + 1u) * NCTA;
            if (lane == 0 && reported < ITEMS_ATT - DEPTH)
                asm volatile("atom.relaxed.gpu.global.add.u32 %0, [%1], %2;"
                             : "=r"(sum) : "l"(&g_sync.prog[~epoch & 1u]), "r"(landed - reported) : "memory");
            if (due) {
#pragma unroll
                for (int u = 0; u < WPS; u++) ml[u] = ld_word(g_ml + (pair_of(sg, j * WPS + u) * G + lane % G) * 32);
                if (j == 0) asm volatile("ld.acquire.gpu.global.u32 %0, [%1];" : "=r"(n) : "l"(&g_sync.inits) : "memory");
            }
            reported = landed;
            if (lane == 0 && P_GAIN) {
                const int avg16 = sum / (NATT / 16), lag16 = avg16 - landed * 16 + P_BIAS;
                pace[1] = avg16 >= ITEMS_ATT * 16 - P_FLUSH ? 8 : min(max(DEPTH + ((lag16 * P_GAIN + 128) >> 8), P_DMIN), P_DMAX);
            }
            if (due) {
                bad = 0;
#pragma unroll
                for (int u = 0; u < WPS; u++) bad |= ml[u].x ^ tag;
            }
            if (__all_sync(0xffffffffu, !(bad & 1u) && n == (epoch + 1u) * NCTA)) {
#pragma unroll
                for (int u = 0; u < WPS; u++) {
                    const float mk = __uint_as_float(ml[u].x & ~1u);
                    float M = mk;
#pragma unroll
                    for (int o = G / 2; o; o >>= 1) M = fmaxf(M, shx(M, o));
                    const float w = __expf(mk - M);
                    float L = w * __uint_as_float(ml[u].y);
#pragma unroll
                    for (int o = G / 2; o; o >>= 1) L += shx(L, o);
                    if (lane == r) reinterpret_cast<float*>(smem + SM_LS)[16 + (j & 1) * WPS + u] = __fdividef(w, L);
                }
                if (lane == r) {
                    mbar_arrive(bar_full + B_WRDY + (j & 1) * 8);
                    if (j == NSTEP - 1) TS(11);
                }
                j++;
                due = false;
            }
            if (j == NSTEP) {
                if (landed >= ITEMS_ATT - DEPTH) return;
            } else {
                if (!due) due = mbar_test(bar_full + B_WTRIG + (j & 1) * 8, (j >> 1) & 1);
                if (j < NSTEP - P_WFAST) __nanosleep(P_SLEEP);
            }
            if (it > SPIN_LIMIT) __trap();
        }
    }
    if (warp > W_PROD) {
        const uint32_t tag = (epoch + 1u) & 1u;
        const int e = tid - (W_PROD + 1) * 32;
        if (is_att) {
#pragma unroll 1
            for (int i = e; i < 192; i += NXW * 32)
                st_fill4(g_qpart + (cta * NB + i / 48) * VS + (i % 48) / 6 * 32 + (i % 6) * 4, tag ^ 1u);
            st_fill4(reinterpret_cast<float*>(g_oacc + cta * 64 + e), 0u);
            if (e < 32) *reinterpret_cast<uint32_t*>(smem + SM_HF + e * 16 + 12) = 0u;
        } else {
#pragma unroll 1
            for (int c = e; c < 256; c += NXW * 32) {
                const bf16* xp = x + qd * DM + (c >> 6) * 160 + ((c >> 3) & 7) * 8 + (c & 3) * 2 + ((c >> 2) & 1);
                asm volatile("st.relaxed.gpu.global.v4.f32 [%0], {%1,%2,%3,%4};"
                             ::"l"(g_acc + (qd * 32 + (c >> 3)) * ACS + (c & 7)), "f"(__bfloat162float(xp[0])),
                               "f"(__bfloat162float(xp[64])), "f"((c & 32) ? 0.f : __bfloat162float(xp[128])), "f"(0.f) : "memory");
            }
        }
        asm volatile("bar.sync 2, %0;" ::"n"(NTHR) : "memory");
        if (!is_att) return;
        {
            const uint32_t eq = (e >> 5) * 24 + min(lane, 23), xw = eq / 6, xr = eq % 6;
            mbar_wait(bar_full + B_QTRIG, 0);
            if (e == 0) TS(10);
            settle(P_QDELAY);
#pragma unroll 1
            for (int j = 0; j < NSTEP; j++) {
                uint4 v[WPS][4];
                uint32_t bad;
                unsigned spin = 0;
                do {
#pragma unroll
                    for (int u = 0; u < WPS; u++) {
                        const int pair = pair_of(sg, j * WPS + u);
                        const float* src = g_qpart + ((pair >> 2) * 4 * NB + (pair & 3)) * VS + xw * 32 + xr * 4;
#pragma unroll
                        for (int k = 0; k < 4; k++) v[u][k] = ld_word2(src + k * NB * VS);
                    }
                    bad = 0;
#pragma unroll
                    for (int u = 0; u < WPS; u++)
#pragma unroll
                        for (int k = 0; k < 4; k++) bad |= (v[u][k].x ^ tag) | (v[u][k].z ^ tag);
                    if (++spin > SPIN_LIMIT) __trap();
                } while (bad & 1u);
#define SUM4(c) ((__uint_as_float(v[u][0].c) + __uint_as_float(v[u][1].c)) + (__uint_as_float(v[u][2].c) + __uint_as_float(v[u][3].c)))
#pragma unroll
                for (int u = 0; u < WPS; u++) {
                    unsigned char* dst = smem + SM_QS + (j * WPS + u) * (DH * 2) + (xr & 1) * 192 + ((xr >> 1) * 8 + xw) * 4;
                    *reinterpret_cast<uint32_t*>(dst) = pack_bf2(SUM4(x), SUM4(y));
                    *reinterpret_cast<uint32_t*>(dst + 96) = pack_bf2(SUM4(z), SUM4(w));
                }
#undef SUM4
                __syncwarp();
                if (lane == 0) mbar_arrive(bar_full + B_QRDY + j * 8);
                if (e == 0 && j == 0) TS(12);
            }
        }
        bool have_h = false;
#pragma unroll 1
        for (int b = 0; b <= NB; b++) {
            if (!have_h && (b == NB || order_of(r, b) >= HSTEP * WPS)) {
                have_h = true;
                mbar_wait(bar_full + B_HTRIG, 0);
#pragma unroll 1
                for (int i = e; i < 96; i += NXW * 32) {
                    const int k = (i % 24) * 2;
                    uint2 v;
                    unsigned spin = 0;
                    do {
                        v = ld_word(g_h + i / 24 * FF + h * 48 + k);
                        if (++spin > SPIN_LIMIT) __trap();
                    } while ((v.x ^ tag) & 1u);
                    *reinterpret_cast<uint32_t*>(smem + SM_HF + k / 24 * 256 + i / 24 * 64 + frag_off(k % 24)) = __byte_perm(v.x, v.y, 0x7632);
                }
                __syncwarp();
                if (lane == 0) mbar_arrive(bar_full + B_HRDY);
            }
            if (b == NB) break;
            const float4* src = g_oacc + (h * NB + b) * 64 + e;
            uint32_t dst = sb + SM_OF + (e >> 5) * 256 + b * 64 + frag_off(lane), ordy = bar_full + B_ORDY;
            asm volatile("" : "+r"(dst), "+l"(src), "+r"(ordy));
            mbar_wait(bar_full + B_OTRIG + b * 8, 0);
            if (order_of(r, b) < G - WPS) settle(P_SETTLE);
            unsigned spin = 0;
            float o0, o1, o2, n;
            do {
                asm volatile("atom.relaxed.gpu.global.add.v4.f32 {%0,%1,%2,%3}, [%4], {%5,%5,%5,%5};"
                             : "=f"(o0), "=f"(o1), "=f"(o2), "=f"(n) : "l"(src), "f"(0.f) : "memory");
                asm volatile("st.shared.u16 [%0], %1;\nst.shared.u16 [%0+512], %2;\nst.shared.u16 [%0+1024], %3;"
                             ::"r"(dst), "h"(__bfloat16_as_ushort(__float2bfloat16_rn(o0))),
                               "h"(__bfloat16_as_ushort(__float2bfloat16_rn(o1))), "h"(__bfloat16_as_ushort(__float2bfloat16_rn(o2))) : "memory");
                if (++spin > SPIN_LIMIT) __trap();
            } while (n != (float)G);
            __syncwarp();
            if (lane == 0) mbar_arrive(ordy);
        }
        return;
    }

    if (warp < NB) {
        uint2 raw[5];
#pragma unroll
        for (int i = 0; i < 5; i++) raw[i] = __ldg(reinterpret_cast<const uint2*>(x + warp * DM) + i * 32 + lane);
        float s = 0.f;
#pragma unroll
        for (int i = 0; i < 5; i++) s += (bf_lo(raw[i].x) + bf_hi(raw[i].x)) + (bf_lo(raw[i].y) + bf_hi(raw[i].y));
#pragma unroll
        for (int o = 16; o; o >>= 1) s += shx(s, o);
        const float mean = s * (1.0f / DM);
        float q2 = 0.f;
#pragma unroll
        for (int i = 0; i < 5; i++) {
            const float d0 = bf_lo(raw[i].x) - mean, d1 = bf_hi(raw[i].x) - mean;
            const float d2 = bf_lo(raw[i].y) - mean, d3 = bf_hi(raw[i].y) - mean;
            q2 += (d0 * d0 + d1 * d1) + (d2 * d2 + d3 * d3);
        }
#pragma unroll
        for (int o = 16; o; o >>= 1) q2 += shx(q2, o);
        const float mb = bf_round(mean);
        const float rs = __frcp_rn(bf_round(__fsqrt_rn(bf_round(bf_round(q2 * (1.0f / DM)) + 1e-5f))));
        const uint32_t k = (lane * 4) & 31;
        unsigned char* dst = smem + SM_XF + warp * 64 +
            (is_att ? (lane >> 3) * 256 + frag_off(k) : (lane >> 2) * 256 + frag_off(k & 15));
        const uint32_t step = is_att ? 1024 : 2048;
#pragma unroll
        for (int i = 0; i < 5; i++) {
            const uint32_t d0 = pack_bf2(bf_lo(raw[i].x) - mb, bf_hi(raw[i].x) - mb);
            const uint32_t d1 = pack_bf2(bf_lo(raw[i].y) - mb, bf_hi(raw[i].y) - mb);
            *reinterpret_cast<uint32_t*>(dst + i * step) = pack_bf2(bf_lo(d0) * rs, bf_hi(d0) * rs);
            *reinterpret_cast<uint32_t*>(dst + i * step + 16) = pack_bf2(bf_lo(d1) * rs, bf_hi(d1) * rs);
        }
    }
    asm volatile("bar.sync 2, %0;" ::"n"(NTHR) : "memory");
    uint32_t tag = (epoch + 1u) & 1u;
    asm volatile("" : "+r"(tag));
    if (tid == 0) TS(3);

    Ring ring{bar_full, sb + SM_RING, 0u, bar_full};
    float lo[3][4] = {}, hi[3][4] = {};
    uint32_t off[3];
    const uint32_t a_lane = (g & 3) * 64 + t * 16;

    if (is_att) {
        float* lsum = reinterpret_cast<float*>(smem + SM_LS);
#pragma unroll 1
        for (int j = -1; j <= NSTEP; j++) {
            if (j >= 0 && j < NSTEP) {
                constexpr int WW = NCW / WPS;
                const int win = j * WPS + warp / WW;
                uint32_t qf[6][4];
                mbar_wait(bar_full + B_QRDY + j * 8, 0);
                if (j == 0 && tid == 0) TS(6);
#pragma unroll
                for (int i = 0; i < 6; i++) lds128(sb + SM_QS + win * (DH * 2) + t * 96 + i * 16, qf[i]);
                const uint32_t key = (warp & 1) * 16 + (lane & 15);
                const uint32_t item = 5 + max(2 * j - 1, 0) * 4 + (warp >> 1), slot = item % NS;
#pragma unroll
                for (int s = 0; s < 3; s++)
                    off[s] = sb + SM_RING + slot * SLOT + key * 384 + s * 128 + (((lane >> 4) ^ ((3 * key + s) & 7)) << 4);
                pin3(off);
                mbar_wait(bar_full + slot * 8, (item / NS) & 1);
                float c[3][4] = {};
#pragma unroll
                for (int dq = 0; dq < 4; dq++)
#pragma unroll
                    for (int s = 0; s < 3; s++) {
                        uint32_t a[4];
                        ldsm_x4(off[s] ^ (dq << 5), a);
                        mma16816(c[s], a, qf[s * 2 + (dq >> 1)][(dq & 1) * 2], qf[s * 2 + (dq >> 1)][(dq & 1) * 2 + 1]);
                    }
                __syncwarp();
                if (lane == 0)
                    asm volatile("mbarrier.arrive.shared::cta.b64 _, [%0], %1;" ::"r"(bar_full + (NS + slot) * 8), "n"(NCW / 2) : "memory");
                ring.skip(4);
                const float raw = (t & 1) ? (c[0][2] + c[1][2]) + c[2][2] : (c[0][0] + c[1][0]) + c[2][0];
                const float sv = bf_round(bf_round(raw) * 0.07216878364870323f);
                if (tid == 0 && j == NSTEP - 1) TS(14);
                float m = fmaxf(sv, shx(sv, 1));
#pragma unroll
                for (int o = 4; o < 32; o <<= 1) m = fmaxf(m, shx(m, o));
                if (lane == 0) lsum[8 + warp] = m;
                cons_bar();
#pragma unroll
                for (int i = 0; i < WW / 4; i++) {
                    const float4 m4 = reinterpret_cast<const float4*>(lsum)[2 + warp / WW * (WW / 4) + i];
                    m = fmaxf(m, fmaxf(fmaxf(m4.x, m4.y), fmaxf(m4.z, m4.w)));
                }
                float l = __expf(sv - m);
                *reinterpret_cast<bf16*>(smem + SM_PF + ((j & 1) * 4 + (warp >> 1)) * 64 + frag_off((warp & 1) * 16 + (t & 1) * 8 + g)) =
                    __float2bfloat16_rn(l);
                l += shx(l, 1);
#pragma unroll
                for (int o = 4; o < 32; o <<= 1) l += shx(l, o);
                if (lane == 0) lsum[warp] = l;
                cons_bar();
                if (tid % (WW * 32) < 4) {
                    l = 0.f;
#pragma unroll
                    for (int i = 0; i < WW / 4; i++) {
                        const float4 l4 = reinterpret_cast<const float4*>(lsum)[warp / 4 + i];
                        l += (l4.x + l4.y) + (l4.z + l4.w);
                    }
                    st_tag2(g_ml + (pair_of(sg, win) * G + r) * 32 + lane * 2, m, l, tag);
                    if (tid == 0) {
                        mbar_arrive(bar_full + B_WTRIG + (j & 1) * 8);
                        if (j == HSTEP) mbar_arrive(bar_full + B_HTRIG);
                    }
                }
                if (tid == 0 && j == NSTEP - 1) TS(13);
                if (j == 0) continue;
            }
            const bool kv = j >= 0;
#pragma unroll
            for (int s = 0; s < 3; s++) off[s] = lane * 384 + s * 128 + ((warp ^ ((3 * lane + s) & 7)) << 4);
#pragma unroll 1
            for (int u = 0; u < (kv ? WPS : 1); u++) {
                const int pair = pair_of(sg, (j - 1) * WPS + u);
                uint32_t trig = !kv ? bar_full + B_QTRIG : (pair >> 2) == h ? bar_full + B_OTRIG + (pair & 3) * 8 : 0;
                if (tid != 0) trig = 0;
                float4* oacc = g_oacc + pair * 64 + warp * 8 + 2 * t + g;
                uint32_t wrdy = bar_full + B_WRDY + (~j & 1) * 8;
                asm volatile("" : "+l"(oacc), "+r"(trig), "+r"(wrdy));
                gemv_loop(ring, kv ? NT : 5,
                          kv ? sb + SM_PF + ((~j & 1) * 4 + u * NT) * 64 + t * 16 : sb + SM_XF + qd * 5 * 256 + a_lane,
                          kv ? 64 : 256, off, lo, hi, lane);
                if (kv) {
                    mbar_wait(wrdy, ((j - 1) >> 1) & 1);
                    const float w = lsum[16 + (~j & 1) * WPS + u];
                    if (g < 2)
                        asm volatile("red.relaxed.gpu.global.add.v4.f32 [%0], {%1,%2,%3,%4};"
                                     ::"l"(oacc), "f"(w * (g ? lo[0][1] + hi[0][3] : lo[0][0] + hi[0][2])),
                                       "f"(w * (g ? lo[1][1] + hi[1][3] : lo[1][0] + hi[1][2])),
                                       "f"(w * (g ? lo[2][1] + hi[2][3] : lo[2][0] + hi[2][2])), "f"(1.0f) : "memory");
                } else if (g < NB) {
#pragma unroll
                    for (int s = 0; s < 3; s++)
                        st_tag2(g_qpart + (cta * NB + g) * VS + warp * 32 + 2 * t + s * 8, lo[s][0] + hi[s][2], lo[s][1] + hi[s][3], tag);
                }
                if (trig) mbar_arrive(trig);
            }
            if (j == NSTEP && tid == 0) TS(5);
            if (j >= 0 && j < NSTEP && j != P_DRY) continue;
            if (tid == 0 && j < 0) TS(4);

            {
                const bool pass = j == NSTEP;
                constexpr int I0 = 5 + NKV;
                static_assert(((I0 / NS) & 1) == 0 && I0 / NS == (I0 + 7) / NS, "tail items complete an even phase");
                const uint32_t done = bar_full + B_QTRIG;
                uint32_t fb = pass ? bar_full + (I0 % NS) * 8 : done, fs = pass ? 8 : 0, ordy = pass ? bar_full + B_ORDY : done;
                uint32_t off2[3], a[8][4], b[8][3][4], a_addr = sb + SM_HF + a_lane;
#pragma unroll
                for (int s = 0; s < 3; s++) {
                    const uint32_t w64 = lane * 320 + (warp + 8 * s) * 16;
                    off[s] = sb + SM_RING + (I0 % NS) * SLOT + (w64 ^ (((w64 >> 7) & 3) << 4));
                    off2[s] = lane < 24 ? off[s] : off[s] - 8 * 320;
#pragma unroll
                    for (int e = 0; e < 4; e++) { lo[s][e] = 0.f; hi[s][e] = 0.f; }
                }
                const float4* accp = g_acc + (((g & 3) * 4 + qd) * NCW + warp) * ACS + (g >> 2) * 4 + t;
                bf16* outp = out + (g & 3) * DM + qd * 160 + warp * 8 + 2 * t + (g >> 2);
                pin3(off);
                asm volatile("" : "+l"(accp), "+l"(outp), "+r"(a_addr), "+r"(ordy), "+r"(fb), "+r"(fs));
                auto load_b = [&](int i, bool& next) {
                    if (!next) mbar_wait(fb + i * fs, 0);
                    if (i < 7) next = mbar_test(fb + (i + 1) * fs, 0);
#pragma unroll
                    for (int s = 0; s < 3; s++)
                        if (s < 2 || warp < 4) ldsm_x4_t((i < 2 ? off2[s] : off[s]) + i * SLOT, b[i][s]);
                };
                auto mul = [&](int i) {
#pragma unroll
                    for (int s = 0; s < 3; s++)
                        if (s < 2 || warp < 4) { mma16816(lo[s], a[i], b[i][s][0], b[i][s][1]); mma16816(hi[s], a[i], b[i][s][2], b[i][s][3]); }
                };
                bool next = mbar_test(fb, 0);
                mbar_wait(pass ? bar_full + B_HRDY : done, 0);
                lds128(a_addr, a[0]);
                lds128(a_addr + 256, a[1]);
                load_b(0, next);
                load_b(1, next);
                bool early = mbar_test(ordy, 0);
                mul(0);
                mul(1);
                if (pass && tid == 0) TS(31);
                unsigned spin = 0;
                while (!early && !mbar_test(fb + P_DEC * fs, 0)) {
                    early = mbar_test(ordy, 0);
                    if (++spin > SPIN_LIMIT) __trap();
                }
                if (pass ? __all_sync(0xffffffffu, early) : j < 0) {
                    if (pass && tid == 0) TS(7);
#pragma unroll
                    for (int i = 2; i < 8; i++) lds128(a_addr + i * 256, a[i]);
                    load_b(2, next);
#pragma unroll
                    for (int i = 2; i < 7; i++) { load_b(i + 1, next); mul(i); }
                    mul(7);
                } else {
#pragma unroll
                    for (int i = 2; i < 8; i++) load_b(i, next);
                    mbar_wait(ordy, 0);
                    if (pass && tid == 0) TS(7);
#pragma unroll
                    for (int i = 2; i < 8; i++) lds128(a_addr + i * 256, a[i]);
#pragma unroll
                    for (int i = 2; i < 8; i++) mul(i);
                }
                if (pass && tid == 0) TS(8);
                add_out(accp, outp, lo, hi, g >= NB, warp < 4, pass, epoch);
            }
        }
        if (tid == 0) { TS(9); TS_DUMP(3, 32); }
    } else {
        float gate[6][2];
#pragma unroll
        for (int s = 0; s < 3; s++) {
            const uint32_t r128 = (lane & 15) * 6 + 2 * s + (lane >> 4);
            off[s] = r128 * 128 + ((warp ^ (r128 & 7)) << 4);
        }
#pragma unroll 1
        for (int ps = 0; ps < 2; ps++) {
#pragma unroll
            for (int s = 0; s < 3; s++) {
                gate[2 * s][0] = lo[s][0]; gate[2 * s][1] = lo[s][1];
                gate[2 * s + 1][0] = hi[s][0]; gate[2 * s + 1][1] = hi[s][1];
            }
            gemv_loop(ring, 40, sb + SM_XF + a_lane, 256, off, lo, hi, lane);
        }
#pragma unroll
        for (int p = 0; p < 6; p++) {
            float hv[2];
#pragma unroll
            for (int e = 0; e < 2; e++) {
                const float gt = bf_round(gate[p][e]);
                hv[e] = bf_round(bf_round(__fdividef(gt, 1.0f + __expf(-gt))) * bf_round((p & 1) ? hi[p >> 1][e] : lo[p >> 1][e]));
            }
            if (g < NB) st_tag2(g_h + g * FF + qd * 384 + p * 64 + warp * 8 + 2 * t, hv[0], hv[1], tag);
        }
        if (tid == 0) { TS(9); TS_DUMP(3, 10); }
    }
}

typedef CUresult (*EncodeFn)(CUtensorMap*, CUtensorMapDataType, cuuint32_t, void*, const cuuint64_t*, const cuuint64_t*,
                             const cuuint32_t*, const cuuint32_t*, CUtensorMapInterleave, CUtensorMapSwizzle,
                             CUtensorMapL2promotion, CUtensorMapFloatOOBfill);

void make_map(EncodeFn enc, CUtensorMap* m, const void* p, uint64_t rows, uint64_t cols, uint32_t inner, uint32_t parts,
              uint32_t box_rows) {
    const cuuint64_t dims[3] = {inner, cols / inner, rows};
    const cuuint64_t strides[2] = {inner * 2ull, cols * 2ull};
    const cuuint32_t box[3] = {inner, parts, box_rows};
    const cuuint32_t es[3] = {1, 1, 1};
    enc(m, CU_TENSOR_MAP_DATA_TYPE_BFLOAT16, 3, const_cast<void*>(p), dims, strides, box, es, CU_TENSOR_MAP_INTERLEAVE_NONE,
        inner == 64 ? CU_TENSOR_MAP_SWIZZLE_128B : CU_TENSOR_MAP_SWIZZLE_64B, CU_TENSOR_MAP_L2_PROMOTION_NONE,
        CU_TENSOR_MAP_FLOAT_OOB_FILL_NONE);
}

}

extern "C" void kernel_launch(void* const* d_in, const int* in_sizes, int n_in, void* d_out, int out_size) {
    (void)in_sizes; (void)n_in; (void)out_size;
    static EncodeFn enc = nullptr;
    if (!enc) {
        void* fn = nullptr;
        cudaDriverEntryPointQueryResult qr;
        cudaGetDriverEntryPoint("cuTensorMapEncodeTiled", &fn, cudaEnableDefault, &qr);
        enc = (EncodeFn)fn;
        cudaFuncSetAttribute(fused_decode_kernel, cudaFuncAttributeMaxDynamicSharedMemorySize, SM_TOTAL);
    }
    Maps maps;
    make_map(enc, &maps.k, d_in[1], (uint64_t)NB * NH * SK, DH, 64, 3, TK);
    make_map(enc, &maps.v, d_in[2], (uint64_t)NB * NH * SK, DH, 64, 3, TK);
    make_map(enc, &maps.wq, d_in[3], DM, NH * DH, 64, 3, 32);
    make_map(enc, &maps.wo, d_in[4], NH * DH, DM, 32, 5, 32);
    make_map(enc, &maps.w1, d_in[6], DM, FF, 64, 6, 16);
    make_map(enc, &maps.w3, d_in[7], DM, FF, 64, 6, 16);
    make_map(enc, &maps.w2, d_in[8], FF, DM, 32, 5, 24);
    fused_decode_kernel<<<NCTA, NTHR, SM_TOTAL>>>(maps, (const bf16*)d_in[0], (bf16*)d_out);
}
```

```cpp
#include <cuda_runtime.h>
#include <cuda.h>
#include <cuda_bf16.h>
#include <stdint.h>

namespace {

typedef __nv_bfloat16 bf16;

constexpr int NB = 4, DM = 640, NH = 32, DH = 192, SK = 8192, WIN = 2048, FF = 1536;

#define P_G 16
#define P_DEPTH 4
#define P_DEPTH_FFN 5
#define P_GAIN 8
#define P_BIAS 16
#define P_SLEEP 500
#define P_DMIN P_DEPTH
#define P_DMAX 6
#define P_SETTLE 3000
#define P_QDELAY 1600
#define P_NSL 20
#define P_DRY 2
#define P_FLUSH 112
#define P_DEC 6
#define P_WFAST 2
#define P_HEADMAJOR 0
#define P_MLATOM 1
#define P_MLWAIT 0
#define P_MLS 32
#define P_OAL 8
#define P_OAS 2
#define P_NS 16

constexpr int G = P_G;
constexpr int TK = 32;
constexpr int NT = WIN / TK / G;
constexpr int NSTEP = 16;
constexpr int WPS = G / NSTEP;
constexpr int MLS = P_MLS;
constexpr int OAL = P_OAL, OAS = P_OAS;
constexpr int HSTEP = 11;
constexpr int NS = P_NS;
constexpr int SLOT = 12288;
constexpr int DEPTH = P_DEPTH;
#define P_D0 5
constexpr int DEPTH0 = P_D0;
static_assert(DEPTH0 <= 5, "DEPTH0");
constexpr int NATT = 128, NFFN = 4, NCTA = NATT + NFFN;
constexpr int NCW = 8;
constexpr int NXW = 2;
constexpr int W_PROD = NCW, W_PACE = NCW + 1 + NXW;
constexpr int NTHR = (W_PACE + 1) * 32;
constexpr int NSRC = NH;
constexpr int VS = 256;
#define P_ACS 16
constexpr int ACS = P_ACS;
static_assert(G == 16 || G == 32, "G");

constexpr int SM_RING = 0;
constexpr int SM_XF = SM_RING + NS * SLOT;
constexpr int SM_QS = SM_XF + 20 * 256;
constexpr int SM_PF = SM_QS + G * DH * 2;
constexpr int SM_HF = SM_PF + 2 * 4 * 64;
constexpr int SM_OF = SM_HF + 2 * 256;
constexpr int SM_LS = SM_OF + 6 * 256;
constexpr int SM_ATT_END = SM_LS + 96;
constexpr int SM_FFN_END = SM_XF + 40 * 256;
constexpr int SM_BAR = SM_ATT_END > SM_FFN_END ? SM_ATT_END : SM_FFN_END;
constexpr int B_QRDY = 2 * NS * 8, B_ORDY = B_QRDY + NSTEP * 8, B_OTRIG = B_ORDY + 8, B_QTRIG = B_OTRIG + 32,
              B_WTRIG = B_QTRIG + 8, B_WRDY = B_WTRIG + 16, B_HTRIG = B_WRDY + 16, B_HRDY = B_HTRIG + 8,
              NBAR = 2 * NS + NSTEP + 12;
constexpr int SM_PACE = SM_BAR + NBAR * 8;
constexpr int SM_TS = SM_PACE + 8;
constexpr int SM_TOTAL = SM_TS + 256;
static_assert(SM_TOTAL <= 232448, "smem");

constexpr int NKV = 2 * NT * G;
constexpr int ITEMS_ATT = 5 + NKV + 2 + 6;
constexpr int ITEMS_FFN = 80;

struct Maps { CUtensorMap k, v, wq, wo, w1, w3, w2; };

struct alignas(32) Sync { unsigned epoch, inits, prog[2]; };
__device__ Sync g_sync;
__device__ __align__(128) float g_qpart[NATT * NB * VS];
__device__ __align__(128) float g_ml[NATT * G * MLS];
__device__ __align__(128) float g_h[NB * FF];
__device__ __align__(128) float4 g_oacc[NATT * 8 * OAL];
__device__ __align__(128) float4 g_acc[NB * 4 * NCW * ACS];
#define TS(i)
#define TS_DUMP(lo, hi)

constexpr unsigned SPIN_LIMIT = 1u << 24;

__device__ __forceinline__ void mbar_init(uint32_t bar, int cnt) {
    asm volatile("mbarrier.init.shared::cta.b64 [%0], %1;" ::"r"(bar), "r"(cnt) : "memory");
}
__device__ __forceinline__ void mbar_expect_tx(uint32_t bar, uint32_t bytes) {
    asm volatile("mbarrier.arrive.expect_tx.shared::cta.b64 _, [%0], %1;" ::"r"(bar), "r"(bytes) : "memory");
}
__device__ __forceinline__ void mbar_arrive(uint32_t bar) {
    asm volatile("mbarrier.arrive.shared::cta.b64 _, [%0];" ::"r"(bar) : "memory");
}
__device__ __forceinline__ void mbar_wait(uint32_t bar, uint32_t parity) {
    asm volatile("{\n.reg .pred p, q;\n.reg .u32 n;\nmov.u32 n, 0;\n"
                 "W: mbarrier.try_wait.parity.shared::cta.b64 p, [%0], %1;\n"
                 "@p bra D;\nadd.u32 n, n, 1;\nsetp.lt.u32 q, n, %2;\n@q bra W;\ntrap;\nD:\n}"
                 ::"r"(bar), "r"(parity), "n"(SPIN_LIMIT) : "memory");
}
__device__ __forceinline__ bool mbar_test(uint32_t bar, uint32_t parity) {
    uint32_t ok;
    asm volatile("{\n.reg .pred p;\nmbarrier.test_wait.parity.shared::cta.b64 p, [%1], %2;\nselp.u32 %0, 1, 0, p;\n}"
                 : "=r"(ok) : "r"(bar), "r"(parity) : "memory");
    return ok;
}
__device__ __forceinline__ void tma3d(uint32_t dst, const CUtensorMap* map, int c1, int c2, uint32_t bar) {
    const uint64_t pol = 0x12F0000000000000ull;
    asm volatile("cp.async.bulk.tensor.3d.shared::cluster.global.mbarrier::complete_tx::bytes.L2::cache_hint "
                 "[%0], [%1, {%2, %3, %4}], [%5], %6;"
                 ::"r"(dst), "l"(map), "r"(0), "r"(c1), "r"(c2), "r"(bar), "l"(pol) : "memory");
}
__device__ __forceinline__ void ldsm_x4(uint32_t addr, uint32_t (&r)[4]) {
    asm volatile("ldmatrix.sync.aligned.m8n8.x4.shared.b16 {%0,%1,%2,%3}, [%4];"
                 : "=r"(r[0]), "=r"(r[1]), "=r"(r[2]), "=r"(r[3]) : "r"(addr) : "memory");
}
__device__ __forceinline__ void ldsm_x4_t(uint32_t addr, uint32_t (&r)[4]) {
    asm volatile("ldmatrix.sync.aligned.m8n8.x4.trans.shared.b16 {%0,%1,%2,%3}, [%4];"
                 : "=r"(r[0]), "=r"(r[1]), "=r"(r[2]), "=r"(r[3]) : "r"(addr) : "memory");
}
__device__ __forceinline__ void lds128(uint32_t addr, uint32_t (&r)[4]) {
    asm volatile("ld.shared.v4.u32 {%0,%1,%2,%3}, [%4];"
                 : "=r"(r[0]), "=r"(r[1]), "=r"(r[2]), "=r"(r[3]) : "r"(addr) : "memory");
}
__device__ __forceinline__ void mma16816(float (&c)[4], const uint32_t (&a)[4], uint32_t b0, uint32_t b1) {
    asm volatile("mma.sync.aligned.m16n8k16.row.col.f32.bf16.bf16.f32 {%0,%1,%2,%3}, {%4,%5,%6,%7}, {%8,%9}, {%0,%1,%2,%3};"
                 : "+f"(c[0]), "+f"(c[1]), "+f"(c[2]), "+f"(c[3])
                 : "r"(a[0]), "r"(a[1]), "r"(a[2]), "r"(a[3]), "r"(b0), "r"(b1));
}
__device__ __forceinline__ void cons_bar() { asm volatile("bar.sync 1, 256;" ::: "memory"); }

__device__ __forceinline__ float bf_round(float v) { return __bfloat162float(__float2bfloat16_rn(v)); }
__device__ __forceinline__ uint32_t pack_bf2(float lo, float hi) {
    __nv_bfloat162 t = __floats2bfloat162_rn(lo, hi);
    return *reinterpret_cast<uint32_t*>(&t);
}
__device__ __forceinline__ float bf_lo(uint32_t u) { return __uint_as_float(u << 16); }
__device__ __forceinline__ float bf_hi(uint32_t u) { return __uint_as_float(u & 0xffff0000u); }
__device__ __forceinline__ float shx(float v, int o) { return __shfl_xor_sync(0xffffffffu, v, o); }

__device__ __forceinline__ uint32_t frag_off(uint32_t k) {
    return ((k >> 1) & 3) * 16 + ((k >> 3) & 1) * 8 + ((k >> 4) & 1) * 4 + (k & 1) * 2;
}

__device__ __forceinline__ void st_tag2(float* p, float a, float b, uint32_t tag) {
    asm volatile("{\n.reg .b64 w;\n.reg .b32 x;\nlop3.b32 x, %1, 0xfffffffe, %3, 0xea;\nmov.b64 w, {x, %2};\n"
                 "st.relaxed.gpu.global.b64 [%0], w;\n}"
                 ::"l"(p), "r"(__float_as_uint(a)), "r"(__float_as_uint(b)), "r"(tag) : "memory");
}
__device__ __forceinline__ void st_fill4(float* p, uint32_t v) {
    asm volatile("{\n.reg .b64 w;\nmov.b64 w, {%1, %1};\nst.relaxed.gpu.global.v2.b64 [%0], {w, w};\n}" ::"l"(p), "r"(v) : "memory");
}
__device__ __forceinline__ uint2 ld_word(const float* p) {
    uint2 v;
    asm volatile("{\n.reg .b64 w;\nld.relaxed.gpu.global.b64 w, [%2];\nmov.b64 {%0,%1}, w;\n}" : "=r"(v.x), "=r"(v.y) : "l"(p) : "memory");
    return v;
}
__device__ __forceinline__ uint2 atom_word(const float* p) {
    uint2 v;
    asm volatile("{\n.reg .b64 w;\natom.relaxed.gpu.global.or.b64 w, [%2], 0;\nmov.b64 {%0,%1}, w;\n}" : "=r"(v.x), "=r"(v.y) : "l"(p) : "memory");
    return v;
}
__device__ __forceinline__ uint4 ld_word2(const float* p) {
    uint4 v;
    asm volatile("{\n.reg .b64 w0, w1;\nld.relaxed.gpu.global.v2.b64 {w0, w1}, [%4];\nmov.b64 {%0,%1}, w0;\nmov.b64 {%2,%3}, w1;\n}"
                 : "=r"(v.x), "=r"(v.y), "=r"(v.z), "=r"(v.w) : "l"(p) : "memory");
    return v;
}

__device__ __forceinline__ void add_out(const float4* acc, bf16* out, const float (&lo)[3][4], const float (&hi)[3][4],
                                        bool odd, bool third, bool live, uint32_t epoch) {
    const float v0 = odd ? lo[0][1] + hi[0][3] : lo[0][0] + hi[0][2];
    const float v1 = odd ? lo[1][1] + hi[1][3] : lo[1][0] + hi[1][2];
    const float v2 = odd ? lo[2][1] + hi[2][3] : lo[2][0] + hi[2][2];
    float o0, o1, o2, n = 0.f;
    asm volatile("{\n.reg .pred p;\nsetp.ne.u32 p, %5, 0;\n"
                 "@p atom.relaxed.gpu.global.add.v4.f32 {%0,%1,%2,%3}, [%4], {%6,%7,%8,%9};\n}"
                 : "=f"(o0), "=f"(o1), "=f"(o2), "+f"(n)
                 : "l"(acc), "r"((uint32_t)live), "f"(v0), "f"(v1), "f"(v2), "f"(1.0f) : "memory");
    asm volatile("{\n.reg .pred p, q;\nsetp.eq.f32 p, %4, %5;\nsetp.ne.and.u32 q, %6, 0, p;\n"
                 "@p st.global.u16 [%0], %1;\n@p st.global.u16 [%0+128], %2;\n@q st.global.u16 [%0+256], %3;\n}"
                 ::"l"(out), "h"(__bfloat16_as_ushort(__float2bfloat16_rn(o0 + v0))),
                   "h"(__bfloat16_as_ushort(__float2bfloat16_rn(o1 + v1))), "h"(__bfloat16_as_ushort(__float2bfloat16_rn(o2 + v2))),
                   "f"(n), "f"((float)(NSRC - 1)), "r"((uint32_t)third) : "memory");
    if (acc == g_acc && n == (float)(NSRC - 1))
        asm volatile("st.relaxed.gpu.global.u32 [%0], %1;" ::"l"(&g_sync.epoch), "r"(epoch + 1u) : "memory");
}

__device__ __forceinline__ int pair_of(int sg, uint32_t j) { return sg * G + (j % (G / 4)) * 4 + j / (G / 4); }
__device__ __forceinline__ int order_of(int r, int b) { return b * (G / 4) + (r >> 2); }

__device__ __forceinline__ float4* ocell(int pair, uint32_t i) {
    return g_oacc + (pair * 8 + (i >> 3)) * OAL + ((i >> 1) & 3) * OAS + (i & 1);
}

__device__ __forceinline__ void settle(int cycles) {
    const uint32_t t0 = (uint32_t)clock();
    while ((uint32_t)clock() - t0 < (uint32_t)cycles) __nanosleep(P_NSL);
}

struct Ring {
    uint32_t full, addr, phase, first_full;
    __device__ __forceinline__ void wait() const { mbar_wait(full, phase); }
    __device__ __forceinline__ void skip(int n) {
        full += n * 8; addr += n * SLOT;
        if (full >= first_full + NS * 8) { full -= NS * 8; addr -= NS * SLOT; phase ^= 1; }
    }
    __device__ __forceinline__ void release(int lane) {
        __syncwarp();
        if (lane == 0) mbar_arrive(full + NS * 8);
        full += 8; addr += SLOT;
        if (full == first_full + NS * 8) { full = first_full; addr -= NS * SLOT; phase ^= 1; }
    }
};

__device__ __forceinline__ void pin3(uint32_t (&v)[3]) {
    asm volatile("" : "+r"(v[0]), "+r"(v[1]), "+r"(v[2]));
}
__device__ __forceinline__ void gemv_loop(Ring& ring, int n, uint32_t a_addr, uint32_t a_step, uint32_t (&off)[3],
                                          float (&lo)[3][4], float (&hi)[3][4], int lane) {
    pin3(off);
#pragma unroll
    for (int s = 0; s < 3; s++)
#pragma unroll
        for (int e = 0; e < 4; e++) { lo[s][e] = 0.f; hi[s][e] = 0.f; }
#pragma unroll 1
    for (int it = 0; it < n; it++) {
        uint32_t a[4], b[3][4];
        lds128(a_addr, a);
        a_addr += a_step;
        ring.wait();
#pragma unroll
        for (int s = 0; s < 3; s++) ldsm_x4_t(ring.addr + off[s], b[s]);
#pragma unroll
        for (int s = 0; s < 3; s++) { mma16816(lo[s], a, b[s][0], b[s][1]); mma16816(hi[s], a, b[s][2], b[s][3]); }
        ring.release(lane);
    }
}

__global__ void __launch_bounds__(NTHR, 1)
fused_decode_kernel(const __grid_constant__ Maps maps, const bf16* __restrict__ x, bf16* __restrict__ out) {
    extern __shared__ __align__(1024) unsigned char smem[];
    const uint32_t sb = (uint32_t)__cvta_generic_to_shared(smem);
    const uint32_t bar_full = sb + SM_BAR;
    if (threadIdx.x == 0 && blockIdx.x < NATT) {
        TS(0);
#pragma unroll 1
        for (int i = 0; i < DEPTH0; i++) {
            mbar_init(bar_full + i * 8, 1);
            mbar_expect_tx(bar_full + i * 8, 12288);
            tma3d(sb + SM_RING + i * SLOT, &maps.wq, (blockIdx.x >> 2) * 3, (blockIdx.x & 3) * 160 + i * 32, bar_full + i * 8);
        }
        TS(1);
    }
    unsigned ptid, cta;
    asm volatile("mov.u32 %0, %%tid.x;\nmov.u32 %1, %%ctaid.x;" : "=r"(ptid), "=r"(cta));
    const int tid = ptid < 32 ? ptid + NCW * 32 : ptid < (NCW + 1) * 32 ? ptid - 32 : ptid;
    const int warp = tid >> 5, lane = tid & 31;
    const bool is_att = cta < NATT;
    const int h = cta >> 2, qd = cta & 3;
    const int sg = cta / G, r = cta % G;

    if (warp == NCW) {
        volatile int* pace = reinterpret_cast<volatile int*>(smem + SM_PACE);
        if (lane == 0) {
            if (!is_att) { TS(0); TS(1); }
            pace[0] = 0;
            pace[1] = is_att ? DEPTH : P_DEPTH_FFN;
#pragma unroll
            for (int i = 0; i < NBAR; i++)
                if (i >= DEPTH0 || !is_att)
                mbar_init(bar_full + i * 8, i < NS ? 1 : i < 2 * NS ? NCW : i < 2 * NS + NSTEP ? NXW : i == 2 * NS + NSTEP ? NXW * NB : i == NBAR - 1 ? NXW : 1);
            asm volatile("fence.mbarrier_init.release.cluster;" ::: "memory");
        }
        __syncwarp();
        asm volatile("bar.arrive 2, %0;" ::"n"(NTHR) : "memory");
        if (lane == 0) {
            const int n_items = is_att ? ITEMS_ATT : ITEMS_FFN;

            asm volatile("prefetch.tensormap [%0];" ::"l"(is_att ? &maps.k : &maps.w3) : "memory");
            asm volatile("prefetch.tensormap [%0];" ::"l"(&maps.v) : "memory");
            asm volatile("prefetch.tensormap [%0];" ::"l"(&maps.w2) : "memory");
            asm volatile("prefetch.tensormap [%0];" ::"l"(&maps.wo) : "memory");
#pragma unroll 1
            for (int i = is_att ? DEPTH0 : 0; i < n_items; i++) {
                const CUtensorMap* map;
                int c1, c2;
                uint32_t bytes = 12288;
                if (is_att) {
                    const uint32_t u = i - 5;
                    if (u < NKV) {
                        const uint32_t blk = u / 4;
                        const bool isv = blk == 2 * NSTEP - 1 || (blk && !(blk & 1));
                        const int pair = pair_of(sg, (isv ? (blk - 1) / 2 : (blk + 1) / 2) * WPS + (u % 4) / NT);
                        map = isv ? &maps.v : &maps.k;
                        c1 = 0;
                        c2 = ((pair & 3) * NH + (pair >> 2)) * SK + (SK - WIN) + ((u % NT) * G + r) * TK;
                    } else if (i < 5) {
                        map = &maps.wq; c1 = h * 3; c2 = qd * 160 + i * 32;
                    } else if (u < NKV + 2) {
                        map = &maps.w2; c1 = qd * 5; c2 = h * 48 + (u - NKV) * 24; bytes = 7680;
                    } else {
                        map = &maps.wo; c1 = qd * 5; c2 = h * DH + (u - NKV - 2) * 32; bytes = 10240;
                    }
                } else {
                    map = i < 40 ? &maps.w1 : &maps.w3; c1 = qd * 6; c2 = (i < 40 ? i : i - 40) * 16;
                }
                const int depth = pace[1];
                const uint32_t slot = (uint32_t)i % NS, landed = i - depth;
                if (i >= NS) mbar_wait(bar_full + (NS + slot) * 8, ((uint32_t)i / NS - 1) & 1);
                mbar_expect_tx(bar_full + slot * 8, bytes);
                uint32_t dst = sb + SM_RING + slot * SLOT, fb = bar_full + slot * 8;
                asm volatile("" : "+r"(dst), "+r"(fb), "+l"(map), "+r"(c1), "+r"(c2));
                if (i >= depth) mbar_wait(bar_full + (landed % NS) * 8, (landed / NS) & 1);
                tma3d(dst, map, c1, c2, fb);
                pace[0] = landed + 1;
            }
            pace[0] = n_items - DEPTH;
        }
        return;
    }

    const int g = lane >> 2, t = lane & 3;
    uint32_t epoch;
    asm volatile("ld.relaxed.gpu.global.u32 %0, [%1];" : "=r"(epoch) : "l"(&g_sync.epoch) : "memory");

    if (warp == W_PACE) {
        const uint32_t tag = (epoch + 1u) & 1u;
        if (is_att) {
#pragma unroll
            for (int u = 0; u < WPS; u++) st_fill4(g_ml + ((sg * G + u * 16 + (lane >> 1)) * G + r) * MLS + (lane & 1) * 4, tag ^ 1u);
        }
        asm volatile("bar.sync 2, %0;" ::"n"(NTHR) : "memory");
        if (lane == 0) asm volatile("red.release.gpu.global.add.u32 [%0], 1;" ::"l"(&g_sync.inits) : "memory");
        if (!is_att) return;
        volatile int* pace = reinterpret_cast<volatile int*>(smem + SM_PACE);
        if (cta == 0 && lane == 0) asm volatile("st.relaxed.gpu.global.u32 [%0], %1;" ::"l"(&g_sync.prog[epoch & 1u]), "r"(0u) : "memory");
        int reported = 0, j = 0;
        bool seen = false;
        bool due = false;
#pragma unroll 1
        for (unsigned it = 0;; it++) {
            const int landed = pace[0];
            int sum = 0;
            uint2 ml[WPS];
            uint32_t bad = 1u;
            unsigned n = (epoch + 1u) * NCTA;
            if (lane == 0 && reported < ITEMS_ATT - DEPTH)
                asm volatile("atom.relaxed.gpu.global.add.u32 %0, [%1], %2;"
                             : "=r"(sum) : "l"(&g_sync.prog[~epoch & 1u]), "r"(landed - reported) : "memory");
            if (due) {
#pragma unroll
                for (int u = 0; u < WPS; u++) {
                    const float* src = g_ml + (pair_of(sg, j * WPS + u) * G + lane % G) * MLS;
                    if (P_MLATOM) { if (lane < G) ml[u] = atom_word(src); else ml[u] = make_uint2(0xff000000u | tag, 0u); }
                    else ml[u] = ld_word(src);
                }
                if (j == 0) asm volatile("ld.acquire.gpu.global.u32 %0, [%1];" : "=r"(n) : "l"(&g_sync.inits) : "memory");
            }
            reported = landed;
            if (lane == 0 && P_GAIN) {
                const int avg16 = sum / (NATT / 16), lag16 = avg16 - landed * 16 + P_BIAS;
                pace[1] = avg16 >= ITEMS_ATT * 16 - P_FLUSH ? 8 : min(max(DEPTH + ((lag16 * P_GAIN + 128) >> 8), P_DMIN), P_DMAX);
            }
            if (due) {
                bad = 0;
#pragma unroll
                for (int u = 0; u < WPS; u++) bad |= ml[u].x ^ tag;
            }
            if (__all_sync(0xffffffffu, !(bad & 1u) && n == (epoch + 1u) * NCTA)) {
#pragma unroll
                for (int u = 0; u < WPS; u++) {
                    const float mk = __uint_as_float(ml[u].x & ~1u);
                    float M = mk;
#pragma unroll
                    for (int o = G / 2; o; o >>= 1) M = fmaxf(M, shx(M, o));
                    const float w = __expf(mk - M);
                    float L = w * __uint_as_float(ml[u].y);
#pragma unroll
                    for (int o = G / 2; o; o >>= 1) L += shx(L, o);
                    if (lane == r) reinterpret_cast<float*>(smem + SM_LS)[16 + (j & 1) * WPS + u] = __fdividef(w, L);
                }
                if (lane == r) {
                    mbar_arrive(bar_full + B_WRDY + (j & 1) * 8);
                    if (j == NSTEP - 1) TS(11);
                }
                j++;
                due = false;
            }
            if (j == NSTEP) {
                if (landed >= ITEMS_ATT - DEPTH) return;
            } else {
                if (P_MLWAIT == 1 && !due) due = mbar_test(bar_full + B_WTRIG + (j & 1) * 8, (j >> 1) & 1);
                if (P_MLWAIT == 2 && !due) { due = seen; seen = !due && mbar_test(bar_full + B_WTRIG + (j & 1) * 8, (j >> 1) & 1); }
                if (j < NSTEP - P_WFAST) __nanosleep(P_SLEEP);
                if (P_MLWAIT == 0 && !due) due = mbar_test(bar_full + B_WTRIG + (j & 1) * 8, (j >> 1) & 1);
            }
            if (it > SPIN_LIMIT) __trap();
        }
    }
    if (warp > W_PROD) {
        const uint32_t tag = (epoch + 1u) & 1u;
        const int e = tid - (W_PROD + 1) * 32;
        if (is_att) {
#pragma unroll 1
            for (int i = e; i < 192; i += NXW * 32)
                st_fill4(g_qpart + (cta * NB + i / 48) * VS + (i % 48) / 6 * 32 + (i % 6) * 4, tag ^ 1u);
            st_fill4(reinterpret_cast<float*>(ocell(cta, e)), 0u);
            if (e < 32) *reinterpret_cast<uint32_t*>(smem + SM_HF + e * 16 + 12) = 0u;
        } else {
#pragma unroll 1
            for (int c = e; c < 256; c += NXW * 32) {
                const bf16* xp = x + qd * DM + (c >> 6) * 160 + ((c >> 3) & 7) * 8 + (c & 3) * 2 + ((c >> 2) & 1);
                asm volatile("st.relaxed.gpu.global.v4.f32 [%0], {%1,%2,%3,%4};"
                             ::"l"(g_acc + (qd * 32 + (c >> 3)) * ACS + (c & 7)), "f"(__bfloat162float(xp[0])),
                               "f"(__bfloat162float(xp[64])), "f"((c & 32) ? 0.f : __bfloat162float(xp[128])), "f"(0.f) : "memory");
            }
        }
        asm volatile("bar.sync 2, %0;" ::"n"(NTHR) : "memory");
        if (!is_att) return;
        {
            const uint32_t eq = (e >> 5) * 24 + min(lane, 23), xw = eq / 6, xr = eq % 6;
            mbar_wait(bar_full + B_QTRIG, 0);
            if (e == 0) TS(10);
            settle(P_QDELAY);
#pragma unroll 1
            for (int j = 0; j < NSTEP; j++) {
                uint4 v[WPS][4];
                uint32_t bad;
                unsigned spin = 0;
                do {
#pragma unroll
                    for (int u = 0; u < WPS; u++) {
                        const int pair = pair_of(sg, j * WPS + u);
                        const float* src = g_qpart + ((pair >> 2) * 4 * NB + (pair & 3)) * VS + xw * 32 + xr * 4;
#pragma unroll
                        for (int k = 0; k < 4; k++) v[u][k] = ld_word2(src + k * NB * VS);
                    }
                    bad = 0;
#pragma unroll
                    for (int u = 0; u < WPS; u++)
#pragma unroll
                        for (int k = 0; k < 4; k++) bad |= (v[u][k].x ^ tag) | (v[u][k].z ^ tag);
                    if (++spin > SPIN_LIMIT) __trap();
                } while (bad & 1u);
#define SUM4(c) ((__uint_as_float(v[u][0].c) + __uint_as_float(v[u][1].c)) + (__uint_as_float(v[u][2].c) + __uint_as_float(v[u][3].c)))
#pragma unroll
                for (int u = 0; u < WPS; u++) {
                    unsigned char* dst = smem + SM_QS + (j * WPS + u) * (DH * 2) + (xr & 1) * 192 + ((xr >> 1) * 8 + xw) * 4;
                    *reinterpret_cast<uint32_t*>(dst) = pack_bf2(SUM4(x), SUM4(y));
                    *reinterpret_cast<uint32_t*>(dst + 96) = pack_bf2(SUM4(z), SUM4(w));
                }
#undef SUM4
                __syncwarp();
                if (lane == 0) mbar_arrive(bar_full + B_QRDY + j * 8);
                if (e == 0 && j == 0) TS(12);
            }
        }
        bool have_h = false;
#pragma unroll 1
        for (int b = 0; b <= NB; b++) {
            if (!have_h && (b == NB || order_of(r, b) >= HSTEP * WPS)) {
                have_h = true;
                mbar_wait(bar_full + B_HTRIG, 0);
#pragma unroll 1
                for (int i = e; i < 96; i += NXW * 32) {
                    const int k = (i % 24) * 2;
                    uint2 v;
                    unsigned spin = 0;
                    do {
                        v = ld_word(g_h + i / 24 * FF + h * 48 + k);
                        if (++spin > SPIN_LIMIT) __trap();
                    } while ((v.x ^ tag) & 1u);
                    *reinterpret_cast<uint32_t*>(smem + SM_HF + k / 24 * 256 + i / 24 * 64 + frag_off(k % 24)) = __byte_perm(v.x, v.y, 0x7632);
                }
                __syncwarp();
                if (lane == 0) mbar_arrive(bar_full + B_HRDY);
            }
            if (b == NB) break;
            const float4* src = ocell(h * NB + b, e);
            uint32_t dst = sb + SM_OF + (e >> 5) * 256 + b * 64 + frag_off(lane), ordy = bar_full + B_ORDY;
            asm volatile("" : "+r"(dst), "+l"(src), "+r"(ordy));
            mbar_wait(bar_full + B_OTRIG + b * 8, 0);
            if (order_of(r, b) < G - WPS) settle(P_SETTLE);
            unsigned spin = 0;
            float o0, o1, o2, n;
            do {
                asm volatile("atom.relaxed.gpu.global.add.v4.f32 {%0,%1,%2,%3}, [%4], {%5,%5,%5,%5};"
                             : "=f"(o0), "=f"(o1), "=f"(o2), "=f"(n) : "l"(src), "f"(0.f) : "memory");
                asm volatile("st.shared.u16 [%0], %1;\nst.shared.u16 [%0+512], %2;\nst.shared.u16 [%0+1024], %3;"
                             ::"r"(dst), "h"(__bfloat16_as_ushort(__float2bfloat16_rn(o0))),
                               "h"(__bfloat16_as_ushort(__float2bfloat16_rn(o1))), "h"(__bfloat16_as_ushort(__float2bfloat16_rn(o2))) : "memory");
                if (++spin > SPIN_LIMIT) __trap();
            } while (n != (float)G);
            __syncwarp();
            if (lane == 0) mbar_arrive(ordy);
        }
        return;
    }

    if (warp < NB) {
        uint2 raw[5];
#pragma unroll
        for (int i = 0; i < 5; i++) raw[i] = __ldg(reinterpret_cast<const uint2*>(x + warp * DM) + i * 32 + lane);
        float s = 0.f;
#pragma unroll
        for (int i = 0; i < 5; i++) s += (bf_lo(raw[i].x) + bf_hi(raw[i].x)) + (bf_lo(raw[i].y) + bf_hi(raw[i].y));
#pragma unroll
        for (int o = 16; o; o >>= 1) s += shx(s, o);
        const float mean = s * (1.0f / DM);
        float q2 = 0.f;
#pragma unroll
        for (int i = 0; i < 5; i++) {
            const float d0 = bf_lo(raw[i].x) - mean, d1 = bf_hi(raw[i].x) - mean;
            const float d2 = bf_lo(raw[i].y) - mean, d3 = bf_hi(raw[i].y) - mean;
            q2 += (d0 * d0 + d1 * d1) + (d2 * d2 + d3 * d3);
        }
#pragma unroll
        for (int o = 16; o; o >>= 1) q2 += shx(q2, o);
        const float mb = bf_round(mean);
        const float rs = __frcp_rn(bf_round(__fsqrt_rn(bf_round(bf_round(q2 * (1.0f / DM)) + 1e-5f))));
        const uint32_t k = (lane * 4) & 31;
        unsigned char* dst = smem + SM_XF + warp * 64 +
            (is_att ? (lane >> 3) * 256 + frag_off(k) : (lane >> 2) * 256 + frag_off(k & 15));
        const uint32_t step = is_att ? 1024 : 2048;
#pragma unroll
        for (int i = 0; i < 5; i++) {
            const uint32_t d0 = pack_bf2(bf_lo(raw[i].x) - mb, bf_hi(raw[i].x) - mb);
            const uint32_t d1 = pack_bf2(bf_lo(raw[i].y) - mb, bf_hi(raw[i].y) - mb);
            *reinterpret_cast<uint32_t*>(dst + i * step) = pack_bf2(bf_lo(d0) * rs, bf_hi(d0) * rs);
            *reinterpret_cast<uint32_t*>(dst + i * step + 16) = pack_bf2(bf_lo(d1) * rs, bf_hi(d1) * rs);
        }
    }
    asm volatile("bar.sync 2, %0;" ::"n"(NTHR) : "memory");
    uint32_t tag = (epoch + 1u) & 1u;
    asm volatile("" : "+r"(tag));
    if (tid == 0) TS(3);

    Ring ring{bar_full, sb + SM_RING, 0u, bar_full};
    float lo[3][4] = {}, hi[3][4] = {};
    uint32_t off[3];
    const uint32_t a_lane = (g & 3) * 64 + t * 16;

    if (is_att) {
        float* lsum = reinterpret_cast<float*>(smem + SM_LS);
#pragma unroll 1
        for (int j = -1; j <= NSTEP; j++) {
            if (j >= 0 && j < NSTEP) {
                constexpr int WW = NCW / WPS;
                const int win = j * WPS + warp / WW;
                uint32_t qf[6][4];
                mbar_wait(bar_full + B_QRDY + j * 8, 0);
                if (j == 0 && tid == 0) TS(6);
#pragma unroll
                for (int i = 0; i < 6; i++) lds128(sb + SM_QS + win * (DH * 2) + t * 96 + i * 16, qf[i]);
                const uint32_t key = (warp & 1) * 16 + (lane & 15);
                const uint32_t item = 5 + max(2 * j - 1, 0) * 4 + (warp >> 1), slot = item % NS;
#pragma unroll
                for (int s = 0; s < 3; s++)
                    off[s] = sb + SM_RING + slot * SLOT + key * 384 + s * 128 + (((lane >> 4) ^ ((3 * key + s) & 7)) << 4);
                pin3(off);
                mbar_wait(bar_full + slot * 8, (item / NS) & 1);
                float c[3][4] = {};
#pragma unroll
                for (int dq = 0; dq < 4; dq++)
#pragma unroll
                    for (int s = 0; s < 3; s++) {
                        uint32_t a[4];
                        ldsm_x4(off[s] ^ (dq << 5), a);
                        mma16816(c[s], a, qf[s * 2 + (dq >> 1)][(dq & 1) * 2], qf[s * 2 + (dq >> 1)][(dq & 1) * 2 + 1]);
                    }
                __syncwarp();
                if (lane == 0)
                    asm volatile("mbarrier.arrive.shared::cta.b64 _, [%0], %1;" ::"r"(bar_full + (NS + slot) * 8), "n"(NCW / 2) : "memory");
                ring.skip(4);
                const float raw = (t & 1) ? (c[0][2] + c[1][2]) + c[2][2] : (c[0][0] + c[1][0]) + c[2][0];
                const float sv = bf_round(bf_round(raw) * 0.07216878364870323f);
                if (tid == 0 && j == NSTEP - 1) TS(14);
                float m = fmaxf(sv, shx(sv, 1));
#pragma unroll
                for (int o = 4; o < 32; o <<= 1) m = fmaxf(m, shx(m, o));
                if (lane == 0) lsum[8 + warp] = m;
                cons_bar();
#pragma unroll
                for (int i = 0; i < WW / 4; i++) {
                    const float4 m4 = reinterpret_cast<const float4*>(lsum)[2 + warp / WW * (WW / 4) + i];
                    m = fmaxf(m, fmaxf(fmaxf(m4.x, m4.y), fmaxf(m4.z, m4.w)));
                }
                float l = __expf(sv - m);
                *reinterpret_cast<bf16*>(smem + SM_PF + ((j & 1) * 4 + (warp >> 1)) * 64 + frag_off((warp & 1) * 16 + (t & 1) * 8 + g)) =
                    __float2bfloat16_rn(l);
                l += shx(l, 1);
#pragma unroll
                for (int o = 4; o < 32; o <<= 1) l += shx(l, o);
                if (lane == 0) lsum[warp] = l;
                cons_bar();
                if (tid % (WW * 32) < 4) {
                    l = 0.f;
#pragma unroll
                    for (int i = 0; i < WW / 4; i++) {
                        const float4 l4 = reinterpret_cast<const float4*>(lsum)[warp / 4 + i];
                        l += (l4.x + l4.y) + (l4.z + l4.w);
                    }
                    st_tag2(g_ml + (pair_of(sg, win) * G + r) * MLS + lane * 2, m, l, tag);
                    if (tid == 0) {
                        mbar_arrive(bar_full + B_WTRIG + (j & 1) * 8);
                        if (j == HSTEP) mbar_arrive(bar_full + B_HTRIG);
                    }
                }
                if (tid == 0 && j == NSTEP - 1) TS(13);
                if (j == 0) continue;
            }
            const bool kv = j >= 0;
#pragma unroll
            for (int s = 0; s < 3; s++) off[s] = lane * 384 + s * 128 + ((warp ^ ((3 * lane + s) & 7)) << 4);
#pragma unroll 1
            for (int u = 0; u < (kv ? WPS : 1); u++) {
                const int pair = pair_of(sg, (j - 1) * WPS + u);
                uint32_t trig = !kv ? bar_full + B_QTRIG : (pair >> 2) == h ? bar_full + B_OTRIG + (pair & 3) * 8 : 0;
                if (tid != 0) trig = 0;
                float4* oacc = ocell(pair, warp * 8 + 2 * t + (g & 1));
                uint32_t wrdy = bar_full + B_WRDY + (~j & 1) * 8;
                asm volatile("" : "+l"(oacc), "+r"(trig), "+r"(wrdy));
                gemv_loop(ring, kv ? NT : 5,
                          kv ? sb + SM_PF + ((~j & 1) * 4 + u * NT) * 64 + t * 16 : sb + SM_XF + qd * 5 * 256 + a_lane,
                          kv ? 64 : 256, off, lo, hi, lane);
                if (kv) {
                    mbar_wait(wrdy, ((j - 1) >> 1) & 1);
                    const float w = lsum[16 + (~j & 1) * WPS + u];
                    if (g < 2)
                        asm volatile("red.relaxed.gpu.global.add.v4.f32 [%0], {%1,%2,%3,%4};"
                                     ::"l"(oacc), "f"(w * (g ? lo[0][1] + hi[0][3] : lo[0][0] + hi[0][2])),
                                       "f"(w * (g ? lo[1][1] + hi[1][3] : lo[1][0] + hi[1][2])),
                                       "f"(w * (g ? lo[2][1] + hi[2][3] : lo[2][0] + hi[2][2])), "f"(1.0f) : "memory");
                } else if (g < NB) {
#pragma unroll
                    for (int s = 0; s < 3; s++)
                        st_tag2(g_qpart + (cta * NB + g) * VS + warp * 32 + 2 * t + s * 8, lo[s][0] + hi[s][2], lo[s][1] + hi[s][3], tag);
                }
                if (trig) mbar_arrive(trig);
            }
            if (j == NSTEP && tid == 0) TS(5);
            if (j >= 0 && j < NSTEP && j != P_DRY) continue;
            if (tid == 0 && j < 0) TS(4);

            {
                const bool pass = j == NSTEP;
                constexpr int I0 = 5 + NKV;
                static_assert(((I0 / NS) & 1) == 0 && I0 / NS == (I0 + 7) / NS, "tail items complete an even phase");
                const uint32_t done = bar_full + B_QTRIG;
                uint32_t fb = pass ? bar_full + (I0 % NS) * 8 : done, fs = pass ? 8 : 0, ordy = pass ? bar_full + B_ORDY : done;
                uint32_t off2[3], a[8][4], b[8][3][4], a_addr = sb + SM_HF + a_lane;
#pragma unroll
                for (int s = 0; s < 3; s++) {
                    const uint32_t w64 = lane * 320 + (warp + 8 * s) * 16;
                    off[s] = sb + SM_RING + (I0 % NS) * SLOT + (w64 ^ (((w64 >> 7) & 3) << 4));
                    off2[s] = lane < 24 ? off[s] : off[s] - 8 * 320;
#pragma unroll
                    for (int e = 0; e < 4; e++) { lo[s][e] = 0.f; hi[s][e] = 0.f; }
                }
                const float4* accp = g_acc + (((g & 3) * 4 + qd) * NCW + warp) * ACS + (g >> 2) * 4 + t;
                bf16* outp = out + (g & 3) * DM + qd * 160 + warp * 8 + 2 * t + (g >> 2);
                pin3(off);
                asm volatile("" : "+l"(accp), "+l"(outp), "+r"(a_addr), "+r"(ordy), "+r"(fb), "+r"(fs));
                auto load_b = [&](int i, bool& next) {
                    if (!next) mbar_wait(fb + i * fs, 0);
                    if (i < 7) next = mbar_test(fb + (i + 1) * fs, 0);
#pragma unroll
                    for (int s = 0; s < 3; s++)
                        if (s < 2 || warp < 4) ldsm_x4_t((i < 2 ? off2[s] : off[s]) + i * SLOT, b[i][s]);
                };
                auto mul = [&](int i) {
#pragma unroll
                    for (int s = 0; s < 3; s++)
                        if (s < 2 || warp < 4) { mma16816(lo[s], a[i], b[i][s][0], b[i][s][1]); mma16816(hi[s], a[i], b[i][s][2], b[i][s][3]); }
                };
                bool next = mbar_test(fb, 0);
                mbar_wait(pass ? bar_full + B_HRDY : done, 0);
                lds128(a_addr, a[0]);
                lds128(a_addr + 256, a[1]);
                load_b(0, next);
                load_b(1, next);
                bool early = mbar_test(ordy, 0);
                mul(0);
                mul(1);
                if (pass && tid == 0) TS(31);
                unsigned spin = 0;
                while (!early && !mbar_test(fb + P_DEC * fs, 0)) {
                    early = mbar_test(ordy, 0);
                    if (++spin > SPIN_LIMIT) __trap();
                }
                if (pass ? __all_sync(0xffffffffu, early) : j < 0) {
                    if (pass && tid == 0) TS(7);
#pragma unroll
                    for (int i = 2; i < 8; i++) lds128(a_addr + i * 256, a[i]);
                    load_b(2, next);
#pragma unroll
                    for (int i = 2; i < 7; i++) { load_b(i + 1, next); mul(i); }
                    mul(7);
                } else {
#pragma unroll
                    for (int i = 2; i < 8; i++) load_b(i, next);
                    mbar_wait(ordy, 0);
                    if (pass && tid == 0) TS(7);
#pragma unroll
                    for (int i = 2; i < 8; i++) lds128(a_addr + i * 256, a[i]);
#pragma unroll
                    for (int i = 2; i < 8; i++) mul(i);
                }
                if (pass && tid == 0) TS(8);
                add_out(accp, outp, lo, hi, g >= NB, warp < 4, pass, epoch);
            }
        }
        if (tid == 0) { TS(9); TS_DUMP(3, 32); }
    } else {
        float gate[6][2];
#pragma unroll
        for (int s = 0; s < 3; s++) {
            const uint32_t r128 = (lane & 15) * 6 + 2 * s + (lane >> 4);
            off[s] = r128 * 128 + ((warp ^ (r128 & 7)) << 4);
        }
#pragma unroll 1
        for (int ps = 0; ps < 2; ps++) {
#pragma unroll
            for (int s = 0; s < 3; s++) {
                gate[2 * s][0] = lo[s][0]; gate[2 * s][1] = lo[s][1];
                gate[2 * s + 1][0] = hi[s][0]; gate[2 * s + 1][1] = hi[s][1];
            }
            gemv_loop(ring, 40, sb + SM_XF + a_lane, 256, off, lo, hi, lane);
        }
#pragma unroll
        for (int p = 0; p < 6; p++) {
            float hv[2];
#pragma unroll
            for (int e = 0; e < 2; e++) {
                const float gt = bf_round(gate[p][e]);
                hv[e] = bf_round(bf_round(__fdividef(gt, 1.0f + __expf(-gt))) * bf_round((p & 1) ? hi[p >> 1][e] : lo[p >> 1][e]));
            }
            if (g < NB) st_tag2(g_h + g * FF + qd * 384 + p * 64 + warp * 8 + 2 * t, hv[0], hv[1], tag);
        }
        if (tid == 0) { TS(9); TS_DUMP(3, 10); }
    }
}

typedef CUresult (*EncodeFn)(CUtensorMap*, CUtensorMapDataType, cuuint32_t, void*, const cuuint64_t*, const cuuint64_t*,
                             const cuuint32_t*, const cuuint32_t*, CUtensorMapInterleave, CUtensorMapSwizzle,
                             CUtensorMapL2promotion, CUtensorMapFloatOOBfill);

void make_map(EncodeFn enc, CUtensorMap* m, const void* p, uint64_t rows, uint64_t cols, uint32_t inner, uint32_t parts,
              uint32_t box_rows) {
    const cuuint64_t dims[3] = {inner, cols / inner, rows};
    const cuuint64_t strides[2] = {inner * 2ull, cols * 2ull};
    const cuuint32_t box[3] = {inner, parts, box_rows};
    const cuuint32_t es[3] = {1, 1, 1};
    enc(m, CU_TENSOR_MAP_DATA_TYPE_BFLOAT16, 3, const_cast<void*>(p), dims, strides, box, es, CU_TENSOR_MAP_INTERLEAVE_NONE,
        inner == 64 ? CU_TENSOR_MAP_SWIZZLE_128B : CU_TENSOR_MAP_SWIZZLE_64B, CU_TENSOR_MAP_L2_PROMOTION_NONE,
        CU_TENSOR_MAP_FLOAT_OOB_FILL_NONE);
}

}

extern "C" void kernel_launch(void* const* d_in, const int* in_sizes, int n_in, void* d_out, int out_size) {
    (void)in_sizes; (void)n_in; (void)out_size;
    static EncodeFn enc = nullptr;
    if (!enc) {
        void* fn = nullptr;
        cudaDriverEntryPointQueryResult qr;
        cudaGetDriverEntryPoint("cuTensorMapEncodeTiled", &fn, cudaEnableDefault, &qr);
        enc = (EncodeFn)fn;
        cudaFuncSetAttribute(fused_decode_kernel, cudaFuncAttributeMaxDynamicSharedMemorySize, SM_TOTAL);
    }
    Maps maps;
    make_map(enc, &maps.k, d_in[1], (uint64_t)NB * NH * SK, DH, 64, 3, TK);
    make_map(enc, &maps.v, d_in[2], (uint64_t)NB * NH * SK, DH, 64, 3, TK);
    make_map(enc, &maps.wq, d_in[3], DM, NH * DH, 64, 3, 32);
    make_map(enc, &maps.wo, d_in[4], NH * DH, DM, 32, 5, 32);
    make_map(enc, &maps.w1, d_in[6], DM, FF, 64, 6, 16);
    make_map(enc, &maps.w3, d_in[7], DM, FF, 64, 6, 16);
    make_map(enc, &maps.w2, d_in[8], FF, DM, 32, 5, 24);
    fused_decode_kernel<<<NCTA, NTHR, SM_TOTAL>>>(maps, (const bf16*)d_in[0], (bf16*)d_out);
}
```

```cpp
#include <cuda_runtime.h>
#include <cuda.h>
#include <cuda_bf16.h>
#include <stdint.h>

namespace {

typedef __nv_bfloat16 bf16;

constexpr int NB = 4, DM = 640, NH = 32, DH = 192, SK = 8192, WIN = 2048, FF = 1536;

#define P_G 16
#define P_DEPTH 4
#define P_DEPTH_FFN 5
#define P_GAIN 8
#define P_BIAS 16
#define P_SLEEP 500
#define P_DMIN P_DEPTH
#define P_DMAX 6
#define P_SETTLE 3000
#define P_QDELAY 1600
#define P_NSL 20
#define P_DRY 4
#define P_FLUSH 112
#define P_DEC 6
#define P_FAST 24
#define P_LA 1
#define P_HEADMAJOR 0
#define P_MLATOM 0
#define P_MLWAIT 1
#define P_MLS 32
#define P_OAL 8
#define P_OAS 2
#define P_NS 16

constexpr int G = P_G;
constexpr int TK = 32;
constexpr int NT = WIN / TK / G;
constexpr int NSTEP = 16;
constexpr int WPS = G / NSTEP;
constexpr int LA = P_LA;
constexpr int MLS = P_MLS;
constexpr int OAL = P_OAL, OAS = P_OAS;
constexpr int HSTEP = 11;
constexpr int NS = P_NS;
constexpr int SLOT = 12288;
constexpr int DEPTH = P_DEPTH;
#define P_D0 5
constexpr int DEPTH0 = P_D0;
static_assert(DEPTH0 <= 5, "DEPTH0");
constexpr int NATT = 128, NFFN = 4, NCTA = NATT + NFFN;
constexpr int NCW = 8;
constexpr int NXW = 2;
constexpr int W_PROD = NCW, W_PACE = NCW + 1 + NXW;
constexpr int NTHR = (W_PACE + 1) * 32;
constexpr int NSRC = NH;
constexpr int VS = 256;
#define P_ACS 16
constexpr int ACS = P_ACS;
static_assert(G == 16 || G == 32, "G");

constexpr int SM_RING = 0;
constexpr int SM_XF = SM_RING + NS * SLOT;
constexpr int SM_QS = SM_XF + 20 * 256;
constexpr int SM_PF = SM_QS + G * DH * 2;
constexpr int SM_HF = SM_PF + 4 * 4 * 64;
constexpr int SM_OF = SM_HF + 2 * 256;
constexpr int SM_LS = SM_OF + 6 * 256;
constexpr int SM_ATT_END = SM_LS + 96;
constexpr int SM_FFN_END = SM_XF + 40 * 256;
constexpr int SM_BAR = SM_ATT_END > SM_FFN_END ? SM_ATT_END : SM_FFN_END;
constexpr int B_QRDY = 2 * NS * 8, B_ORDY = B_QRDY + NSTEP * 8, B_OTRIG = B_ORDY + 8, B_QTRIG = B_OTRIG + 32,
              B_WTRIG = B_QTRIG + 8, B_WRDY = B_WTRIG + 32, B_HTRIG = B_WRDY + 32, B_HRDY = B_HTRIG + 8,
              NBAR = 2 * NS + NSTEP + 16;
constexpr int SM_PACE = SM_BAR + NBAR * 8;
constexpr int SM_TS = SM_PACE + 8;
constexpr int SM_TOTAL = SM_TS + 256;
static_assert(SM_TOTAL <= 232448, "smem");

constexpr int NKV = 2 * NT * G;
constexpr int ITEMS_ATT = 5 + NKV + 2 + 6;
constexpr int ITEMS_FFN = 80;

struct Maps { CUtensorMap k, v, wq, wo, w1, w3, w2; };

struct alignas(32) Sync { unsigned epoch, inits, prog[2]; };
__device__ Sync g_sync;
__device__ __align__(128) float g_qpart[NATT * NB * VS];
__device__ __align__(128) float g_ml[NATT * G * MLS];
__device__ __align__(128) float g_h[NB * FF];
__device__ __align__(128) float4 g_oacc[NATT * 8 * OAL];
__device__ __align__(128) float4 g_acc[NB * 4 * NCW * ACS];
#define TS(i)
#define TS_DUMP(lo, hi)

constexpr unsigned SPIN_LIMIT = 1u << 24;

__device__ __forceinline__ void mbar_init(uint32_t bar, int cnt) {
    asm volatile("mbarrier.init.shared::cta.b64 [%0], %1;" ::"r"(bar), "r"(cnt) : "memory");
}
__device__ __forceinline__ void mbar_expect_tx(uint32_t bar, uint32_t bytes) {
    asm volatile("mbarrier.arrive.expect_tx.shared::cta.b64 _, [%0], %1;" ::"r"(bar), "r"(bytes) : "memory");
}
__device__ __forceinline__ void mbar_arrive(uint32_t bar) {
    asm volatile("mbarrier.arrive.shared::cta.b64 _, [%0];" ::"r"(bar) : "memory");
}
__device__ __forceinline__ void mbar_wait(uint32_t bar, uint32_t parity) {
    asm volatile("{\n.reg .pred p, q;\n.reg .u32 n;\nmov.u32 n, 0;\n"
                 "W: mbarrier.try_wait.parity.shared::cta.b64 p, [%0], %1;\n"
                 "@p bra D;\nadd.u32 n, n, 1;\nsetp.lt.u32 q, n, %2;\n@q bra W;\ntrap;\nD:\n}"
                 ::"r"(bar), "r"(parity), "n"(SPIN_LIMIT) : "memory");
}
__device__ __forceinline__ bool mbar_test(uint32_t bar, uint32_t parity) {
    uint32_t ok;
    asm volatile("{\n.reg .pred p;\nmbarrier.test_wait.parity.shared::cta.b64 p, [%1], %2;\nselp.u32 %0, 1, 0, p;\n}"
                 : "=r"(ok) : "r"(bar), "r"(parity) : "memory");
    return ok;
}
__device__ __forceinline__ void tma3d(uint32_t dst, const CUtensorMap* map, int c1, int c2, uint32_t bar) {
    const uint64_t pol = 0x12F0000000000000ull;
    asm volatile("cp.async.bulk.tensor.3d.shared::cluster.global.mbarrier::complete_tx::bytes.L2::cache_hint "
                 "[%0], [%1, {%2, %3, %4}], [%5], %6;"
                 ::"r"(dst), "l"(map), "r"(0), "r"(c1), "r"(c2), "r"(bar), "l"(pol) : "memory");
}
__device__ __forceinline__ void ldsm_x4(uint32_t addr, uint32_t (&r)[4]) {
    asm volatile("ldmatrix.sync.aligned.m8n8.x4.shared.b16 {%0,%1,%2,%3}, [%4];"
                 : "=r"(r[0]), "=r"(r[1]), "=r"(r[2]), "=r"(r[3]) : "r"(addr) : "memory");
}
__device__ __forceinline__ void ldsm_x4_t(uint32_t addr, uint32_t (&r)[4]) {
    asm volatile("ldmatrix.sync.aligned.m8n8.x4.trans.shared.b16 {%0,%1,%2,%3}, [%4];"
                 : "=r"(r[0]), "=r"(r[1]), "=r"(r[2]), "=r"(r[3]) : "r"(addr) : "memory");
}
__device__ __forceinline__ void lds128(uint32_t addr, uint32_t (&r)[4]) {
    asm volatile("ld.shared.v4.u32 {%0,%1,%2,%3}, [%4];"
                 : "=r"(r[0]), "=r"(r[1]), "=r"(r[2]), "=r"(r[3]) : "r"(addr) : "memory");
}
__device__ __forceinline__ void mma16816(float (&c)[4], const uint32_t (&a)[4], uint32_t b0, uint32_t b1) {
    asm volatile("mma.sync.aligned.m16n8k16.row.col.f32.bf16.bf16.f32 {%0,%1,%2,%3}, {%4,%5,%6,%7}, {%8,%9}, {%0,%1,%2,%3};"
                 : "+f"(c[0]), "+f"(c[1]), "+f"(c[2]), "+f"(c[3])
                 : "r"(a[0]), "r"(a[1]), "r"(a[2]), "r"(a[3]), "r"(b0), "r"(b1));
}
__device__ __forceinline__ void cons_bar() { asm volatile("bar.sync 1, 256;" ::: "memory"); }

__device__ __forceinline__ float bf_round(float v) { return __bfloat162float(__float2bfloat16_rn(v)); }
__device__ __forceinline__ uint32_t pack_bf2(float lo, float hi) {
    __nv_bfloat162 t = __floats2bfloat162_rn(lo, hi);
    return *reinterpret_cast<uint32_t*>(&t);
}
__device__ __forceinline__ float bf_lo(uint32_t u) { return __uint_as_float(u << 16); }
__device__ __forceinline__ float bf_hi(uint32_t u) { return __uint_as_float(u & 0xffff0000u); }
__device__ __forceinline__ float shx(float v, int o) { return __shfl_xor_sync(0xffffffffu, v, o); }

__device__ __forceinline__ uint32_t frag_off(uint32_t k) {
    return ((k >> 1) & 3) * 16 + ((k >> 3) & 1) * 8 + ((k >> 4) & 1) * 4 + (k & 1) * 2;
}

__device__ __forceinline__ void st_tag2(float* p, float a, float b, uint32_t tag) {
    asm volatile("{\n.reg .b64 w;\n.reg .b32 x;\nlop3.b32 x, %1, 0xfffffffe, %3, 0xea;\nmov.b64 w, {x, %2};\n"
                 "st.relaxed.gpu.global.b64 [%0], w;\n}"
                 ::"l"(p), "r"(__float_as_uint(a)), "r"(__float_as_uint(b)), "r"(tag) : "memory");
}
__device__ __forceinline__ void st_fill4(float* p, uint32_t v) {
    asm volatile("{\n.reg .b64 w;\nmov.b64 w, {%1, %1};\nst.relaxed.gpu.global.v2.b64 [%0], {w, w};\n}" ::"l"(p), "r"(v) : "memory");
}
__device__ __forceinline__ uint2 ld_word(const float* p) {
    uint2 v;
    asm volatile("{\n.reg .b64 w;\nld.relaxed.gpu.global.b64 w, [%2];\nmov.b64 {%0,%1}, w;\n}" : "=r"(v.x), "=r"(v.y) : "l"(p) : "memory");
    return v;
}
__device__ __forceinline__ uint2 atom_word(const float* p) {
    uint2 v;
    asm volatile("{\n.reg .b64 w;\natom.relaxed.gpu.global.or.b64 w, [%2], 0;\nmov.b64 {%0,%1}, w;\n}" : "=r"(v.x), "=r"(v.y) : "l"(p) : "memory");
    return v;
}
__device__ __forceinline__ uint4 ld_word2(const float* p) {
    uint4 v;
    asm volatile("{\n.reg .b64 w0, w1;\nld.relaxed.gpu.global.v2.b64 {w0, w1}, [%4];\nmov.b64 {%0,%1}, w0;\nmov.b64 {%2,%3}, w1;\n}"
                 : "=r"(v.x), "=r"(v.y), "=r"(v.z), "=r"(v.w) : "l"(p) : "memory");
    return v;
}

__device__ __forceinline__ void add_out(const float4* acc, bf16* out, const float (&lo)[3][4], const float (&hi)[3][4],
                                        bool odd, bool third, bool live, uint32_t epoch) {
    const float v0 = odd ? lo[0][1] + hi[0][3] : lo[0][0] + hi[0][2];
    const float v1 = odd ? lo[1][1] + hi[1][3] : lo[1][0] + hi[1][2];
    const float v2 = odd ? lo[2][1] + hi[2][3] : lo[2][0] + hi[2][2];
    float o0, o1, o2, n = 0.f;
    asm volatile("{\n.reg .pred p;\nsetp.ne.u32 p, %5, 0;\n"
                 "@p atom.relaxed.gpu.global.add.v4.f32 {%0,%1,%2,%3}, [%4], {%6,%7,%8,%9};\n}"
                 : "=f"(o0), "=f"(o1), "=f"(o2), "+f"(n)
                 : "l"(acc), "r"((uint32_t)live), "f"(v0), "f"(v1), "f"(v2), "f"(1.0f) : "memory");
    asm volatile("{\n.reg .pred p, q;\nsetp.eq.f32 p, %4, %5;\nsetp.ne.and.u32 q, %6, 0, p;\n"
                 "@p st.global.u16 [%0], %1;\n@p st.global.u16 [%0+128], %2;\n@q st.global.u16 [%0+256], %3;\n}"
                 ::"l"(out), "h"(__bfloat16_as_ushort(__float2bfloat16_rn(o0 + v0))),
                   "h"(__bfloat16_as_ushort(__float2bfloat16_rn(o1 + v1))), "h"(__bfloat16_as_ushort(__float2bfloat16_rn(o2 + v2))),
                   "f"(n), "f"((float)(NSRC - 1)), "r"((uint32_t)third) : "memory");
    if (acc == g_acc && n == (float)(NSRC - 1))
        asm volatile("st.relaxed.gpu.global.u32 [%0], %1;" ::"l"(&g_sync.epoch), "r"(epoch + 1u) : "memory");
}

__device__ __forceinline__ int pair_of(int sg, uint32_t j) { return sg * G + (j % (G / 4)) * 4 + j / (G / 4); }
__device__ __forceinline__ int order_of(int r, int b) { return b * (G / 4) + (r >> 2); }

__device__ __forceinline__ float4* ocell(int pair, uint32_t i) {
    return g_oacc + (pair * 8 + (i >> 3)) * OAL + ((i >> 1) & 3) * OAS + (i & 1);
}

__device__ __forceinline__ void settle(int cycles) {
    const uint32_t t0 = (uint32_t)clock();
    while ((uint32_t)clock() - t0 < (uint32_t)cycles) __nanosleep(P_NSL);
}

struct Ring {
    uint32_t full, addr, phase, first_full;
    __device__ __forceinline__ void wait() const { mbar_wait(full, phase); }
    __device__ __forceinline__ void skip(int n) {
        full += n * 8; addr += n * SLOT;
        if (full >= first_full + NS * 8) { full -= NS * 8; addr -= NS * SLOT; phase ^= 1; }
    }
    __device__ __forceinline__ void release(int lane) {
        __syncwarp();
        if (lane == 0) mbar_arrive(full + NS * 8);
        full += 8; addr += SLOT;
        if (full == first_full + NS * 8) { full = first_full; addr -= NS * SLOT; phase ^= 1; }
    }
};

__device__ __forceinline__ void pin3(uint32_t (&v)[3]) {
    asm volatile("" : "+r"(v[0]), "+r"(v[1]), "+r"(v[2]));
}
__device__ __forceinline__ void gemv_loop(Ring& ring, int n, uint32_t a_addr, uint32_t a_step, uint32_t (&off)[3],
                                          float (&lo)[3][4], float (&hi)[3][4], int lane) {
    pin3(off);
#pragma unroll
    for (int s = 0; s < 3; s++)
#pragma unroll
        for (int e = 0; e < 4; e++) { lo[s][e] = 0.f; hi[s][e] = 0.f; }
#pragma unroll 1
    for (int it = 0; it < n; it++) {
        uint32_t a[4], b[3][4];
        lds128(a_addr, a);
        a_addr += a_step;
        ring.wait();
#pragma unroll
        for (int s = 0; s < 3; s++) ldsm_x4_t(ring.addr + off[s], b[s]);
#pragma unroll
        for (int s = 0; s < 3; s++) { mma16816(lo[s], a, b[s][0], b[s][1]); mma16816(hi[s], a, b[s][2], b[s][3]); }
        ring.release(lane);
    }
}

__global__ void __launch_bounds__(NTHR, 1)
fused_decode_kernel(const __grid_constant__ Maps maps, const bf16* __restrict__ x, bf16* __restrict__ out) {
    extern __shared__ __align__(1024) unsigned char smem[];
    const uint32_t sb = (uint32_t)__cvta_generic_to_shared(smem);
    const uint32_t bar_full = sb + SM_BAR;
    if (threadIdx.x == 0 && blockIdx.x < NATT) {
        TS(0);
#pragma unroll 1
        for (int i = 0; i < DEPTH0; i++) {
            mbar_init(bar_full + i * 8, 1);
            mbar_expect_tx(bar_full + i * 8, 12288);
            tma3d(sb + SM_RING + i * SLOT, &maps.wq, (blockIdx.x >> 2) * 3, (blockIdx.x & 3) * 160 + i * 32, bar_full + i * 8);
        }
        TS(1);
    }
    unsigned ptid, cta;
    asm volatile("mov.u32 %0, %%tid.x;\nmov.u32 %1, %%ctaid.x;" : "=r"(ptid), "=r"(cta));
    const int tid = ptid < 32 ? ptid + NCW * 32 : ptid < (NCW + 1) * 32 ? ptid - 32 : ptid;
    const int warp = tid >> 5, lane = tid & 31;
    const bool is_att = cta < NATT;
    const int h = cta >> 2, qd = cta & 3;
    const int sg = cta / G, r = cta % G;

    if (warp == NCW) {
        volatile int* pace = reinterpret_cast<volatile int*>(smem + SM_PACE);
        if (lane == 0) {
            if (!is_att) { TS(0); TS(1); }
            pace[0] = 0;
            pace[1] = is_att ? DEPTH : P_DEPTH_FFN;
#pragma unroll
            for (int i = 0; i < NBAR; i++)
                if (i >= DEPTH0 || !is_att)
                mbar_init(bar_full + i * 8, i < NS ? 1 : i < 2 * NS ? NCW : i < 2 * NS + NSTEP ? NXW : i == 2 * NS + NSTEP ? NXW * NB : i == NBAR - 1 ? NXW : 1);
            asm volatile("fence.mbarrier_init.release.cluster;" ::: "memory");
        }
        __syncwarp();
        asm volatile("bar.arrive 2, %0;" ::"n"(NTHR) : "memory");
        if (lane == 0) {
            const int n_items = is_att ? ITEMS_ATT : ITEMS_FFN;

            asm volatile("prefetch.tensormap [%0];" ::"l"(is_att ? &maps.k : &maps.w3) : "memory");
            asm volatile("prefetch.tensormap [%0];" ::"l"(&maps.v) : "memory");
            asm volatile("prefetch.tensormap [%0];" ::"l"(&maps.w2) : "memory");
            asm volatile("prefetch.tensormap [%0];" ::"l"(&maps.wo) : "memory");
#pragma unroll 1
            for (int i = is_att ? DEPTH0 : 0; i < n_items; i++) {
                const CUtensorMap* map;
                int c1, c2;
                uint32_t bytes = 12288;
                if (is_att) {
                    const uint32_t u = i - 5;
                    if (u < NKV) {
                        const uint32_t blk = u / 4;
                        const bool isv = blk >= 2 * NSTEP - LA || (blk >= LA && ((blk - LA) & 1));
                        const uint32_t step = blk < LA ? blk : blk >= 2 * NSTEP - LA ? blk - NSTEP : (blk - LA) / 2 + (isv ? 0 : LA);
                        const int pair = pair_of(sg, step * WPS + (u % 4) / NT);
                        map = isv ? &maps.v : &maps.k;
                        c1 = 0;
                        c2 = ((pair & 3) * NH + (pair >> 2)) * SK + (SK - WIN) + ((u % NT) * G + r) * TK;
                    } else if (i < 5) {
                        map = &maps.wq; c1 = h * 3; c2 = qd * 160 + i * 32;
                    } else if (u < NKV + 2) {
                        map = &maps.w2; c1 = qd * 5; c2 = h * 48 + (u - NKV) * 24; bytes = 7680;
                    } else {
                        map = &maps.wo; c1 = qd * 5; c2 = h * DH + (u - NKV - 2) * 32; bytes = 10240;
                    }
                } else {
                    map = i < 40 ? &maps.w1 : &maps.w3; c1 = qd * 6; c2 = (i < 40 ? i : i - 40) * 16;
                }
                const int depth = pace[1];
                const uint32_t slot = (uint32_t)i % NS, landed = i - depth;
                if (i >= NS) mbar_wait(bar_full + (NS + slot) * 8, ((uint32_t)i / NS - 1) & 1);
                mbar_expect_tx(bar_full + slot * 8, bytes);
                uint32_t dst = sb + SM_RING + slot * SLOT, fb = bar_full + slot * 8;
                asm volatile("" : "+r"(dst), "+r"(fb), "+l"(map), "+r"(c1), "+r"(c2));
                if (i >= depth) mbar_wait(bar_full + (landed % NS) * 8, (landed / NS) & 1);
                tma3d(dst, map, c1, c2, fb);
                pace[0] = landed + 1;
            }
            pace[0] = n_items - DEPTH;
        }
        return;
    }

    const int g = lane >> 2, t = lane & 3;
    uint32_t epoch;
    asm volatile("ld.relaxed.gpu.global.u32 %0, [%1];" : "=r"(epoch) : "l"(&g_sync.epoch) : "memory");

    if (warp == W_PACE) {
        const uint32_t tag = (epoch + 1u) & 1u;
        if (is_att) {
#pragma unroll
            for (int u = 0; u < WPS; u++) st_fill4(g_ml + ((sg * G + u * 16 + (lane >> 1)) * G + r) * MLS + (lane & 1) * 4, tag ^ 1u);
        }
        asm volatile("bar.sync 2, %0;" ::"n"(NTHR) : "memory");
        if (lane == 0) asm volatile("red.release.gpu.global.add.u32 [%0], 1;" ::"l"(&g_sync.inits) : "memory");
        if (!is_att) return;
        volatile int* pace = reinterpret_cast<volatile int*>(smem + SM_PACE);
        if (cta == 0 && lane == 0) asm volatile("st.relaxed.gpu.global.u32 [%0], %1;" ::"l"(&g_sync.prog[epoch & 1u]), "r"(0u) : "memory");
        int reported = 0, j = 0;
        bool due = false;
#pragma unroll 1
        for (unsigned it = 0;; it++) {
            const int landed = pace[0];
            int sum = 0;
            uint2 ml[WPS];
            uint32_t bad = 1u;
            unsigned n = (epoch + 1u) * NCTA;
            if (lane == 0 && reported < ITEMS_ATT - DEPTH)
                asm volatile("atom.relaxed.gpu.global.add.u32 %0, [%1], %2;"
                             : "=r"(sum) : "l"(&g_sync.prog[~epoch & 1u]), "r"(landed - reported) : "memory");
            if (due) {
#pragma unroll
                for (int u = 0; u < WPS; u++) {
                    const float* src = g_ml + (pair_of(sg, j * WPS + u) * G + lane % G) * MLS;
                    if (P_MLATOM) { if (lane < G) ml[u] = atom_word(src); else ml[u] = make_uint2(0xff000000u | tag, 0u); }
                    else ml[u] = ld_word(src);
                }
                if (j == 0) asm volatile("ld.acquire.gpu.global.u32 %0, [%1];" : "=r"(n) : "l"(&g_sync.inits) : "memory");
            }
            reported = landed;
            if (lane == 0 && P_GAIN) {
                const int avg16 = sum / (NATT / 16), lag16 = avg16 - landed * 16 + P_BIAS;
                pace[1] = avg16 >= ITEMS_ATT * 16 - P_FLUSH ? 8 : min(max(DEPTH + ((lag16 * P_GAIN + 128) >> 8), P_DMIN), P_DMAX);
            }
            if (due) {
                bad = 0;
#pragma unroll
                for (int u = 0; u < WPS; u++) bad |= ml[u].x ^ tag;
            }
            if (__all_sync(0xffffffffu, !(bad & 1u) && n == (epoch + 1u) * NCTA)) {
#pragma unroll
                for (int u = 0; u < WPS; u++) {
                    const float mk = __uint_as_float(ml[u].x & ~1u);
                    float M = mk;
#pragma unroll
                    for (int o = G / 2; o; o >>= 1) M = fmaxf(M, shx(M, o));
                    const float w = __expf(mk - M);
                    float L = w * __uint_as_float(ml[u].y);
#pragma unroll
                    for (int o = G / 2; o; o >>= 1) L += shx(L, o);
                    if (lane == r) reinterpret_cast<float*>(smem + SM_LS)[16 + (j & 3) * WPS + u] = __fdividef(w, L);
                }
                if (lane == r) {
                    mbar_arrive(bar_full + B_WRDY + (j & 3) * 8);
                    if (j == NSTEP - 1) TS(11);
                }
                j++;
                due = false;
            }
            if (j == NSTEP && landed >= ITEMS_ATT - DEPTH) return;
            if (P_MLWAIT == 1 && !due && j < NSTEP) due = mbar_test(bar_full + B_WTRIG + (j & 3) * 8, (j >> 2) & 1);
            if (landed < ITEMS_ATT - P_FAST) __nanosleep(P_SLEEP);
            if (P_MLWAIT == 0 && !due && j < NSTEP) due = mbar_test(bar_full + B_WTRIG + (j & 3) * 8, (j >> 2) & 1);
            if (it > SPIN_LIMIT) __trap();
        }
    }
    if (warp > W_PROD) {
        const uint32_t tag = (epoch + 1u) & 1u;
        const int e = tid - (W_PROD + 1) * 32;
        if (is_att) {
#pragma unroll 1
            for (int i = e; i < 192; i += NXW * 32)
                st_fill4(g_qpart + (cta * NB + i / 48) * VS + (i % 48) / 6 * 32 + (i % 6) * 4, tag ^ 1u);
            st_fill4(reinterpret_cast<float*>(ocell(cta, e)), 0u);
            if (e < 32) *reinterpret_cast<uint32_t*>(smem + SM_HF + e * 16 + 12) = 0u;
        } else {
#pragma unroll 1
            for (int c = e; c < 256; c += NXW * 32) {
                const bf16* xp = x + qd * DM + (c >> 6) * 160 + ((c >> 3) & 7) * 8 + (c & 3) * 2 + ((c >> 2) & 1);
                asm volatile("st.relaxed.gpu.global.v4.f32 [%0], {%1,%2,%3,%4};"
                             ::"l"(g_acc + (qd * 32 + (c >> 3)) * ACS + (c & 7)), "f"(__bfloat162float(xp[0])),
                               "f"(__bfloat162float(xp[64])), "f"((c & 32) ? 0.f : __bfloat162float(xp[128])), "f"(0.f) : "memory");
            }
        }
        asm volatile("bar.sync 2, %0;" ::"n"(NTHR) : "memory");
        if (!is_att) return;
        {
            const uint32_t eq = (e >> 5) * 24 + min(lane, 23), xw = eq / 6, xr = eq % 6;
            mbar_wait(bar_full + B_QTRIG, 0);
            if (e == 0) TS(10);
            settle(P_QDELAY);
#pragma unroll 1
            for (int j = 0; j < NSTEP; j++) {
                uint4 v[WPS][4];
                uint32_t bad;
                unsigned spin = 0;
                do {
#pragma unroll
                    for (int u = 0; u < WPS; u++) {
                        const int pair = pair_of(sg, j * WPS + u);
                        const float* src = g_qpart + ((pair >> 2) * 4 * NB + (pair & 3)) * VS + xw * 32 + xr * 4;
#pragma unroll
                        for (int k = 0; k < 4; k++) v[u][k] = ld_word2(src + k * NB * VS);
                    }
                    bad = 0;
#pragma unroll
                    for (int u = 0; u < WPS; u++)
#pragma unroll
                        for (int k = 0; k < 4; k++) bad |= (v[u][k].x ^ tag) | (v[u][k].z ^ tag);
                    if (++spin > SPIN_LIMIT) __trap();
                } while (bad & 1u);
#define SUM4(c) ((__uint_as_float(v[u][0].c) + __uint_as_float(v[u][1].c)) + (__uint_as_float(v[u][2].c) + __uint_as_float(v[u][3].c)))
#pragma unroll
                for (int u = 0; u < WPS; u++) {
                    unsigned char* dst = smem + SM_QS + (j * WPS + u) * (DH * 2) + (xr & 1) * 192 + ((xr >> 1) * 8 + xw) * 4;
                    *reinterpret_cast<uint32_t*>(dst) = pack_bf2(SUM4(x), SUM4(y));
                    *reinterpret_cast<uint32_t*>(dst + 96) = pack_bf2(SUM4(z), SUM4(w));
                }
#undef SUM4
                __syncwarp();
                if (lane == 0) mbar_arrive(bar_full + B_QRDY + j * 8);
                if (e == 0 && j == 0) TS(12);
            }
        }
        bool have_h = false;
#pragma unroll 1
        for (int b = 0; b <= NB; b++) {
            if (!have_h && (b == NB || order_of(r, b) >= HSTEP * WPS)) {
                have_h = true;
                mbar_wait(bar_full + B_HTRIG, 0);
#pragma unroll 1
                for (int i = e; i < 96; i += NXW * 32) {
                    const int k = (i % 24) * 2;
                    uint2 v;
                    unsigned spin = 0;
                    do {
                        v = ld_word(g_h + i / 24 * FF + h * 48 + k);
                        if (++spin > SPIN_LIMIT) __trap();
                    } while ((v.x ^ tag) & 1u);
                    *reinterpret_cast<uint32_t*>(smem + SM_HF + k / 24 * 256 + i / 24 * 64 + frag_off(k % 24)) = __byte_perm(v.x, v.y, 0x7632);
                }
                __syncwarp();
                if (lane == 0) mbar_arrive(bar_full + B_HRDY);
            }
            if (b == NB) break;
            const float4* src = ocell(h * NB + b, e);
            uint32_t dst = sb + SM_OF + (e >> 5) * 256 + b * 64 + frag_off(lane), ordy = bar_full + B_ORDY;
            asm volatile("" : "+r"(dst), "+l"(src), "+r"(ordy));
            mbar_wait(bar_full + B_OTRIG + b * 8, 0);
            if (order_of(r, b) < G - WPS) settle(P_SETTLE);
            unsigned spin = 0;
            float o0, o1, o2, n;
            do {
                asm volatile("atom.relaxed.gpu.global.add.v4.f32 {%0,%1,%2,%3}, [%4], {%5,%5,%5,%5};"
                             : "=f"(o0), "=f"(o1), "=f"(o2), "=f"(n) : "l"(src), "f"(0.f) : "memory");
                asm volatile("st.shared.u16 [%0], %1;\nst.shared.u16 [%0+512], %2;\nst.shared.u16 [%0+1024], %3;"
                             ::"r"(dst), "h"(__bfloat16_as_ushort(__float2bfloat16_rn(o0))),
                               "h"(__bfloat16_as_ushort(__float2bfloat16_rn(o1))), "h"(__bfloat16_as_ushort(__float2bfloat16_rn(o2))) : "memory");
                if (++spin > SPIN_LIMIT) __trap();
            } while (n != (float)G);
            __syncwarp();
            if (lane == 0) mbar_arrive(ordy);
        }
        return;
    }

    if (warp < NB) {
        uint2 raw[5];
#pragma unroll
        for (int i = 0; i < 5; i++) raw[i] = __ldg(reinterpret_cast<const uint2*>(x + warp * DM) + i * 32 + lane);
        float s = 0.f;
#pragma unroll
        for (int i = 0; i < 5; i++) s += (bf_lo(raw[i].x) + bf_hi(raw[i].x)) + (bf_lo(raw[i].y) + bf_hi(raw[i].y));
#pragma unroll
        for (int o = 16; o; o >>= 1) s += shx(s, o);
        const float mean = s * (1.0f / DM);
        float q2 = 0.f;
#pragma unroll
        for (int i = 0; i < 5; i++) {
            const float d0 = bf_lo(raw[i].x) - mean, d1 = bf_hi(raw[i].x) - mean;
            const float d2 = bf_lo(raw[i].y) - mean, d3 = bf_hi(raw[i].y) - mean;
            q2 += (d0 * d0 + d1 * d1) + (d2 * d2 + d3 * d3);
        }
#pragma unroll
        for (int o = 16; o; o >>= 1) q2 += shx(q2, o);
        const float mb = bf_round(mean);
        const float rs = __frcp_rn(bf_round(__fsqrt_rn(bf_round(bf_round(q2 * (1.0f / DM)) + 1e-5f))));
        const uint32_t k = (lane * 4) & 31;
        unsigned char* dst = smem + SM_XF + warp * 64 +
            (is_att ? (lane >> 3) * 256 + frag_off(k) : (lane >> 2) * 256 + frag_off(k & 15));
        const uint32_t step = is_att ? 1024 : 2048;
#pragma unroll
        for (int i = 0; i < 5; i++) {
            const uint32_t d0 = pack_bf2(bf_lo(raw[i].x) - mb, bf_hi(raw[i].x) - mb);
            const uint32_t d1 = pack_bf2(bf_lo(raw[i].y) - mb, bf_hi(raw[i].y) - mb);
            *reinterpret_cast<uint32_t*>(dst + i * step) = pack_bf2(bf_lo(d0) * rs, bf_hi(d0) * rs);
            *reinterpret_cast<uint32_t*>(dst + i * step + 16) = pack_bf2(bf_lo(d1) * rs, bf_hi(d1) * rs);
        }
    }
    asm volatile("bar.sync 2, %0;" ::"n"(NTHR) : "memory");
    uint32_t tag = (epoch + 1u) & 1u;
    asm volatile("" : "+r"(tag));
    if (tid == 0) TS(3);

    Ring ring{bar_full, sb + SM_RING, 0u, bar_full};
    float lo[3][4] = {}, hi[3][4] = {};
    uint32_t off[3];
    const uint32_t a_lane = (g & 3) * 64 + t * 16;

    if (is_att) {
        float* lsum = reinterpret_cast<float*>(smem + SM_LS);
#pragma unroll 1
        for (int j = -1; j < NSTEP + LA; j++) {
            if (j >= 0 && j < NSTEP) {
                constexpr int WW = NCW / WPS;
                const int win = j * WPS + warp / WW;
                uint32_t qf[6][4];
                mbar_wait(bar_full + B_QRDY + j * 8, 0);
                if (j == 0 && tid == 0) TS(6);
#pragma unroll
                for (int i = 0; i < 6; i++) lds128(sb + SM_QS + win * (DH * 2) + t * 96 + i * 16, qf[i]);
                const uint32_t key = (warp & 1) * 16 + (lane & 15);
                const uint32_t item = 5 + (j + max(j - LA, 0)) * 4 + (warp >> 1), slot = item % NS;
#pragma unroll
                for (int s = 0; s < 3; s++)
                    off[s] = sb + SM_RING + slot * SLOT + key * 384 + s * 128 + (((lane >> 4) ^ ((3 * key + s) & 7)) << 4);
                pin3(off);
                mbar_wait(bar_full + slot * 8, (item / NS) & 1);
                float c[3][4] = {};
#pragma unroll
                for (int dq = 0; dq < 4; dq++)
#pragma unroll
                    for (int s = 0; s < 3; s++) {
                        uint32_t a[4];
                        ldsm_x4(off[s] ^ (dq << 5), a);
                        mma16816(c[s], a, qf[s * 2 + (dq >> 1)][(dq & 1) * 2], qf[s * 2 + (dq >> 1)][(dq & 1) * 2 + 1]);
                    }
                __syncwarp();
                if (lane == 0)
                    asm volatile("mbarrier.arrive.shared::cta.b64 _, [%0], %1;" ::"r"(bar_full + (NS + slot) * 8), "n"(NCW / 2) : "memory");
                ring.skip(4);
                const float raw = (t & 1) ? (c[0][2] + c[1][2]) + c[2][2] : (c[0][0] + c[1][0]) + c[2][0];
                const float sv = bf_round(bf_round(raw) * 0.07216878364870323f);
                if (tid == 0 && j == NSTEP - 1) TS(14);
                float m = fmaxf(sv, shx(sv, 1));
#pragma unroll
                for (int o = 4; o < 32; o <<= 1) m = fmaxf(m, shx(m, o));
                if (lane == 0) lsum[8 + warp] = m;
                cons_bar();
#pragma unroll
                for (int i = 0; i < WW / 4; i++) {
                    const float4 m4 = reinterpret_cast<const float4*>(lsum)[2 + warp / WW * (WW / 4) + i];
                    m = fmaxf(m, fmaxf(fmaxf(m4.x, m4.y), fmaxf(m4.z, m4.w)));
                }
                float l = __expf(sv - m);
                *reinterpret_cast<bf16*>(smem + SM_PF + ((j & 3) * 4 + (warp >> 1)) * 64 + frag_off((warp & 1) * 16 + (t & 1) * 8 + g)) =
                    __float2bfloat16_rn(l);
                l += shx(l, 1);
#pragma unroll
                for (int o = 4; o < 32; o <<= 1) l += shx(l, o);
                if (lane == 0) lsum[warp] = l;
                cons_bar();
                if (tid % (WW * 32) < 4) {
                    l = 0.f;
#pragma unroll
                    for (int i = 0; i < WW / 4; i++) {
                        const float4 l4 = reinterpret_cast<const float4*>(lsum)[warp / 4 + i];
                        l += (l4.x + l4.y) + (l4.z + l4.w);
                    }
                    st_tag2(g_ml + (pair_of(sg, win) * G + r) * MLS + lane * 2, m, l, tag);
                    if (tid == 0) {
                        mbar_arrive(bar_full + B_WTRIG + (j & 3) * 8);
                        if (j == HSTEP) mbar_arrive(bar_full + B_HTRIG);
                    }
                }
                if (tid == 0 && j == NSTEP - 1) TS(13);
                if (j < LA) continue;
            }
            const bool kv = j >= 0;
            const uint32_t jv = j - LA;
#pragma unroll
            for (int s = 0; s < 3; s++) off[s] = lane * 384 + s * 128 + ((warp ^ ((3 * lane + s) & 7)) << 4);
#pragma unroll 1
            for (int u = 0; u < (kv ? WPS : 1); u++) {
                const int pair = pair_of(sg, jv * WPS + u);
                uint32_t trig = !kv ? bar_full + B_QTRIG : (pair >> 2) == h ? bar_full + B_OTRIG + (pair & 3) * 8 : 0;
                if (tid != 0) trig = 0;
                float4* oacc = ocell(pair, warp * 8 + 2 * t + (g & 1));
                uint32_t wrdy = bar_full + B_WRDY + (jv & 3) * 8;
                asm volatile("" : "+l"(oacc), "+r"(trig), "+r"(wrdy));
                gemv_loop(ring, kv ? NT : 5,
                          kv ? sb + SM_PF + ((jv & 3) * 4 + u * NT) * 64 + t * 16 : sb + SM_XF + qd * 5 * 256 + a_lane,
                          kv ? 64 : 256, off, lo, hi, lane);
                if (kv) {
                    mbar_wait(wrdy, (jv >> 2) & 1);
                    const float w = lsum[16 + (jv & 3) * WPS + u];
                    if (g < 2)
                        asm volatile("red.relaxed.gpu.global.add.v4.f32 [%0], {%1,%2,%3,%4};"
                                     ::"l"(oacc), "f"(w * (g ? lo[0][1] + hi[0][3] : lo[0][0] + hi[0][2])),
                                       "f"(w * (g ? lo[1][1] + hi[1][3] : lo[1][0] + hi[1][2])),
                                       "f"(w * (g ? lo[2][1] + hi[2][3] : lo[2][0] + hi[2][2])), "f"(1.0f) : "memory");
                } else if (g < NB) {
#pragma unroll
                    for (int s = 0; s < 3; s++)
                        st_tag2(g_qpart + (cta * NB + g) * VS + warp * 32 + 2 * t + s * 8, lo[s][0] + hi[s][2], lo[s][1] + hi[s][3], tag);
                }
                if (trig) mbar_arrive(trig);
            }
            const bool pass = j == NSTEP + LA - 1;
            if (pass && tid == 0) TS(5);
            if (kv && !pass && j != P_DRY) continue;
            if (tid == 0 && j < 0) TS(4);

            {
                constexpr int I0 = 5 + NKV;
                static_assert(((I0 / NS) & 1) == 0 && I0 / NS == (I0 + 7) / NS, "tail items complete an even phase");
                const uint32_t done = bar_full + B_QTRIG;
                uint32_t fb = pass ? bar_full + (I0 % NS) * 8 : done, fs = pass ? 8 : 0, ordy = pass ? bar_full + B_ORDY : done;
                uint32_t off2[3], a[8][4], b[8][3][4], a_addr = sb + SM_HF + a_lane;
#pragma unroll
                for (int s = 0; s < 3; s++) {
                    const uint32_t w64 = lane * 320 + (warp + 8 * s) * 16;
                    off[s] = sb + SM_RING + (I0 % NS) * SLOT + (w64 ^ (((w64 >> 7) & 3) << 4));
                    off2[s] = lane < 24 ? off[s] : off[s] - 8 * 320;
#pragma unroll
                    for (int e = 0; e < 4; e++) { lo[s][e] = 0.f; hi[s][e] = 0.f; }
                }
                const float4* accp = g_acc + (((g & 3) * 4 + qd) * NCW + warp) * ACS + (g >> 2) * 4 + t;
                bf16* outp = out + (g & 3) * DM + qd * 160 + warp * 8 + 2 * t + (g >> 2);
                pin3(off);
                asm volatile("" : "+l"(accp), "+l"(outp), "+r"(a_addr), "+r"(ordy), "+r"(fb), "+r"(fs));
                auto load_b = [&](int i, bool& next) {
                    if (!next) mbar_wait(fb + i * fs, 0);
                    if (i < 7) next = mbar_test(fb + (i + 1) * fs, 0);
#pragma unroll
                    for (int s = 0; s < 3; s++)
                        if (s < 2 || warp < 4) ldsm_x4_t((i < 2 ? off2[s] : off[s]) + i * SLOT, b[i][s]);
                };
                auto mul = [&](int i) {
#pragma unroll
                    for (int s = 0; s < 3; s++)
                        if (s < 2 || warp < 4) { mma16816(lo[s], a[i], b[i][s][0], b[i][s][1]); mma16816(hi[s], a[i], b[i][s][2], b[i][s][3]); }
                };
                bool next = mbar_test(fb, 0);
                mbar_wait(pass ? bar_full + B_HRDY : done, 0);
                lds128(a_addr, a[0]);
                lds128(a_addr + 256, a[1]);
                load_b(0, next);
                load_b(1, next);
                bool early = mbar_test(ordy, 0);
                mul(0);
                mul(1);
                if (pass && tid == 0) TS(31);
                unsigned spin = 0;
                while (!early && !mbar_test(fb + P_DEC * fs, 0)) {
                    early = mbar_test(ordy, 0);
                    if (++spin > SPIN_LIMIT) __trap();
                }
                if (pass ? __all_sync(0xffffffffu, early) : j < 0) {
                    if (pass && tid == 0) TS(7);
#pragma unroll
                    for (int i = 2; i < 8; i++) lds128(a_addr + i * 256, a[i]);
                    load_b(2, next);
#pragma unroll
                    for (int i = 2; i < 7; i++) { load_b(i + 1, next); mul(i); }
                    mul(7);
                } else {
#pragma unroll
                    for (int i = 2; i < 8; i++) load_b(i, next);
                    mbar_wait(ordy, 0);
                    if (pass && tid == 0) TS(7);
#pragma unroll
                    for (int i = 2; i < 8; i++) lds128(a_addr + i * 256, a[i]);
#pragma unroll
                    for (int i = 2; i < 8; i++) mul(i);
                }
                if (pass && tid == 0) TS(8);
                add_out(accp, outp, lo, hi, g >= NB, warp < 4, pass, epoch);
            }
        }
        if (tid == 0) { TS(9); TS_DUMP(3, 32); }
    } else {
        float gate[6][2];
#pragma unroll
        for (int s = 0; s < 3; s++) {
            const uint32_t r128 = (lane & 15) * 6 + 2 * s + (lane >> 4);
            off[s] = r128 * 128 + ((warp ^ (r128 & 7)) << 4);
        }
#pragma unroll 1
        for (int ps = 0; ps < 2; ps++) {
#pragma unroll
            for (int s = 0; s < 3; s++) {
                gate[2 * s][0] = lo[s][0]; gate[2 * s][1] = lo[s][1];
                gate[2 * s + 1][0] = hi[s][0]; gate[2 * s + 1][1] = hi[s][1];
            }
            gemv_loop(ring, 40, sb + SM_XF + a_lane, 256, off, lo, hi, lane);
        }
#pragma unroll
        for (int p = 0; p < 6; p++) {
            float hv[2];
#pragma unroll
            for (int e = 0; e < 2; e++) {
                const float gt = bf_round(gate[p][e]);
                hv[e] = bf_round(bf_round(__fdividef(gt, 1.0f + __expf(-gt))) * bf_round((p & 1) ? hi[p >> 1][e] : lo[p >> 1][e]));
            }
            if (g < NB) st_tag2(g_h + g * FF + qd * 384 + p * 64 + warp * 8 + 2 * t, hv[0], hv[1], tag);
        }
        if (tid == 0) { TS(9); TS_DUMP(3, 10); }
    }
}

typedef CUresult (*EncodeFn)(CUtensorMap*, CUtensorMapDataType, cuuint32_t, void*, const cuuint64_t*, const cuuint64_t*,
                             const cuuint32_t*, const cuuint32_t*, CUtensorMapInterleave, CUtensorMapSwizzle,
                             CUtensorMapL2promotion, CUtensorMapFloatOOBfill);

void make_map(EncodeFn enc, CUtensorMap* m, const void* p, uint64_t rows, uint64_t cols, uint32_t inner, uint32_t parts,
              uint32_t box_rows) {
    const cuuint64_t dims[3] = {inner, cols / inner, rows};
    const cuuint64_t strides[2] = {inner * 2ull, cols * 2ull};
    const cuuint32_t box[3] = {inner, parts, box_rows};
    const cuuint32_t es[3] = {1, 1, 1};
    enc(m, CU_TENSOR_MAP_DATA_TYPE_BFLOAT16, 3, const_cast<void*>(p), dims, strides, box, es, CU_TENSOR_MAP_INTERLEAVE_NONE,
        inner == 64 ? CU_TENSOR_MAP_SWIZZLE_128B : CU_TENSOR_MAP_SWIZZLE_64B, CU_TENSOR_MAP_L2_PROMOTION_NONE,
        CU_TENSOR_MAP_FLOAT_OOB_FILL_NONE);
}

}

extern "C" void kernel_launch(void* const* d_in, const int* in_sizes, int n_in, void* d_out, int out_size) {
    (void)in_sizes; (void)n_in; (void)out_size;
    static EncodeFn enc = nullptr;
    if (!enc) {
        void* fn = nullptr;
        cudaDriverEntryPointQueryResult qr;
        cudaGetDriverEntryPoint("cuTensorMapEncodeTiled", &fn, cudaEnableDefault, &qr);
        enc = (EncodeFn)fn;
        cudaFuncSetAttribute(fused_decode_kernel, cudaFuncAttributeMaxDynamicSharedMemorySize, SM_TOTAL);
    }
    Maps maps;
    make_map(enc, &maps.k, d_in[1], (uint64_t)NB * NH * SK, DH, 64, 3, TK);
    make_map(enc, &maps.v, d_in[2], (uint64_t)NB * NH * SK, DH, 64, 3, TK);
    make_map(enc, &maps.wq, d_in[3], DM, NH * DH, 64, 3, 32);
    make_map(enc, &maps.wo, d_in[4], NH * DH, DM, 32, 5, 32);
    make_map(enc, &maps.w1, d_in[6], DM, FF, 64, 6, 16);
    make_map(enc, &maps.w3, d_in[7], DM, FF, 64, 6, 16);
    make_map(enc, &maps.w2, d_in[8], FF, DM, 32, 5, 24);
    fused_decode_kernel<<<NCTA, NTHR, SM_TOTAL>>>(maps, (const bf16*)d_in[0], (bf16*)d_out);
}
```

```cpp
#include <cuda_runtime.h>
#include <cuda.h>
#include <cuda_bf16.h>
#include <stdint.h>

namespace {

typedef __nv_bfloat16 bf16;

constexpr int NB = 4, DM = 640, NH = 32, DH = 192, SK = 8192, WIN = 2048, FF = 1536;

#define P_G 32
#define P_DEPTH 4
#define P_DEPTH_FFN 5
#define P_GAIN 8
#define P_BIAS 16
#define P_SLEEP 500
#define P_DMIN P_DEPTH
#define P_DMAX 6
#define P_SETTLE 3000
#define P_QDELAY 1600
#define P_NSL 20
#define P_DRY 4
#define P_FLUSH 112
#define P_DEC 6
#define P_FAST 24
#define P_LA 2
#define P_HEADMAJOR 0
#define P_MLATOM 0
#define P_MLWAIT 1
#define P_MLS 8
#define P_OAL 72
#define P_OAS 2
#define P_URG 1
#define P_SETTLE0 0
#define P_NS 16

constexpr int G = P_G;
constexpr int TK = 32;
constexpr int NT = WIN / TK / G;
constexpr int NSTEP = 16;
constexpr int WPS = G / NSTEP;
constexpr int LA = P_LA;
constexpr int MLS = P_MLS;
constexpr int OAL = P_OAL, OAS = P_OAS;
constexpr int HSTEP = 11;
constexpr int NS = P_NS;
constexpr int SLOT = 12288;
constexpr int DEPTH = P_DEPTH;
#define P_D0 5
constexpr int DEPTH0 = P_D0;
static_assert(DEPTH0 <= 5, "DEPTH0");
constexpr int NATT = 128, NFFN = 4, NCTA = NATT + NFFN;
constexpr int NCW = 8;
constexpr int NXW = 2;
constexpr int W_PROD = NCW, W_PACE = NCW + 1 + NXW;
constexpr int NTHR = (W_PACE + 1) * 32;
constexpr int NSRC = NH;
constexpr int VS = 256;
#define P_ACS 16
constexpr int ACS = P_ACS;
static_assert(G == 16 || G == 32, "G");

constexpr int SM_RING = 0;
constexpr int SM_XF = SM_RING + NS * SLOT;
constexpr int SM_QS = SM_XF + 20 * 256;
constexpr int SM_PF = SM_QS + G * DH * 2;
constexpr int SM_HF = SM_PF + 4 * 4 * 64;
constexpr int SM_OF = SM_HF + 2 * 256;
constexpr int SM_LS = SM_OF + 6 * 256;
constexpr int SM_ATT_END = SM_LS + 96;
constexpr int SM_FFN_END = SM_XF + 40 * 256;
constexpr int SM_BAR = SM_ATT_END > SM_FFN_END ? SM_ATT_END : SM_FFN_END;
constexpr int B_QRDY = 2 * NS * 8, B_ORDY = B_QRDY + NSTEP * 8, B_OTRIG = B_ORDY + 8, B_QTRIG = B_OTRIG + 32,
              B_WTRIG = B_QTRIG + 8, B_WRDY = B_WTRIG + 32, B_HTRIG = B_WRDY + 32, B_HRDY = B_HTRIG + 8,
              NBAR = 2 * NS + NSTEP + 16;
constexpr int SM_PACE = SM_BAR + NBAR * 8;
constexpr int SM_TS = SM_PACE + 8;
constexpr int SM_TOTAL = SM_TS + 256;
static_assert(SM_TOTAL <= 232448, "smem");

constexpr int NKV = 2 * NT * G;
constexpr int ITEMS_ATT = 5 + NKV + 2 + 6;
constexpr int ITEMS_FFN = 80;

struct Maps { CUtensorMap k, v, wq, wo, w1, w3, w2; };

struct alignas(32) Sync { unsigned epoch, inits, prog[2]; };
__device__ Sync g_sync;
__device__ __align__(128) float g_qpart[NATT * NB * VS];
__device__ __align__(128) float g_ml[NATT * G * MLS];
__device__ __align__(128) float g_h[NB * FF];
__device__ __align__(128) float4 g_oacc[NATT * 8 * OAL];
__device__ __align__(128) float4 g_acc[NB * 4 * NCW * ACS];
#define TS(i)
#define TS_DUMP(lo, hi)

constexpr unsigned SPIN_LIMIT = 1u << 24;

__device__ __forceinline__ void mbar_init(uint32_t bar, int cnt) {
    asm volatile("mbarrier.init.shared::cta.b64 [%0], %1;" ::"r"(bar), "r"(cnt) : "memory");
}
__device__ __forceinline__ void mbar_expect_tx(uint32_t bar, uint32_t bytes) {
    asm volatile("mbarrier.arrive.expect_tx.shared::cta.b64 _, [%0], %1;" ::"r"(bar), "r"(bytes) : "memory");
}
__device__ __forceinline__ void mbar_arrive(uint32_t bar) {
    asm volatile("mbarrier.arrive.shared::cta.b64 _, [%0];" ::"r"(bar) : "memory");
}
__device__ __forceinline__ void mbar_wait(uint32_t bar, uint32_t parity) {
    asm volatile("{\n.reg .pred p, q;\n.reg .u32 n;\nmov.u32 n, 0;\n"
                 "W: mbarrier.try_wait.parity.shared::cta.b64 p, [%0], %1;\n"
                 "@p bra D;\nadd.u32 n, n, 1;\nsetp.lt.u32 q, n, %2;\n@q bra W;\ntrap;\nD:\n}"
                 ::"r"(bar), "r"(parity), "n"(SPIN_LIMIT) : "memory");
}
__device__ __forceinline__ bool mbar_test(uint32_t bar, uint32_t parity) {
    uint32_t ok;
    asm volatile("{\n.reg .pred p;\nmbarrier.test_wait.parity.shared::cta.b64 p, [%1], %2;\nselp.u32 %0, 1, 0, p;\n}"
                 : "=r"(ok) : "r"(bar), "r"(parity) : "memory");
    return ok;
}
__device__ __forceinline__ void tma3d(uint32_t dst, const CUtensorMap* map, int c1, int c2, uint32_t bar) {
    const uint64_t pol = 0x12F0000000000000ull;
    asm volatile("cp.async.bulk.tensor.3d.shared::cluster.global.mbarrier::complete_tx::bytes.L2::cache_hint "
                 "[%0], [%1, {%2, %3, %4}], [%5], %6;"
                 ::"r"(dst), "l"(map), "r"(0), "r"(c1), "r"(c2), "r"(bar), "l"(pol) : "memory");
}
__device__ __forceinline__ void ldsm_x4(uint32_t addr, uint32_t (&r)[4]) {
    asm volatile("ldmatrix.sync.aligned.m8n8.x4.shared.b16 {%0,%1,%2,%3}, [%4];"
                 : "=r"(r[0]), "=r"(r[1]), "=r"(r[2]), "=r"(r[3]) : "r"(addr) : "memory");
}
__device__ __forceinline__ void ldsm_x4_t(uint32_t addr, uint32_t (&r)[4]) {
    asm volatile("ldmatrix.sync.aligned.m8n8.x4.trans.shared.b16 {%0,%1,%2,%3}, [%4];"
                 : "=r"(r[0]), "=r"(r[1]), "=r"(r[2]), "=r"(r[3]) : "r"(addr) : "memory");
}
__device__ __forceinline__ void lds128(uint32_t addr, uint32_t (&r)[4]) {
    asm volatile("ld.shared.v4.u32 {%0,%1,%2,%3}, [%4];"
                 : "=r"(r[0]), "=r"(r[1]), "=r"(r[2]), "=r"(r[3]) : "r"(addr) : "memory");
}
__device__ __forceinline__ void mma16816(float (&c)[4], const uint32_t (&a)[4], uint32_t b0, uint32_t b1) {
    asm volatile("mma.sync.aligned.m16n8k16.row.col.f32.bf16.bf16.f32 {%0,%1,%2,%3}, {%4,%5,%6,%7}, {%8,%9}, {%0,%1,%2,%3};"
                 : "+f"(c[0]), "+f"(c[1]), "+f"(c[2]), "+f"(c[3])
                 : "r"(a[0]), "r"(a[1]), "r"(a[2]), "r"(a[3]), "r"(b0), "r"(b1));
}
__device__ __forceinline__ void cons_bar() { asm volatile("bar.sync 1, 256;" ::: "memory"); }

__device__ __forceinline__ float bf_round(float v) { return __bfloat162float(__float2bfloat16_rn(v)); }
__device__ __forceinline__ uint32_t pack_bf2(float lo, float hi) {
    __nv_bfloat162 t = __floats2bfloat162_rn(lo, hi);
    return *reinterpret_cast<uint32_t*>(&t);
}
__device__ __forceinline__ float bf_lo(uint32_t u) { return __uint_as_float(u << 16); }
__device__ __forceinline__ float bf_hi(uint32_t u) { return __uint_as_float(u & 0xffff0000u); }
__device__ __forceinline__ float shx(float v, int o) { return __shfl_xor_sync(0xffffffffu, v, o); }

__device__ __forceinline__ uint32_t frag_off(uint32_t k) {
    return ((k >> 1) & 3) * 16 + ((k >> 3) & 1) * 8 + ((k >> 4) & 1) * 4 + (k & 1) * 2;
}

__device__ __forceinline__ void st_tag2(float* p, float a, float b, uint32_t tag) {
    asm volatile("{\n.reg .b64 w;\n.reg .b32 x;\nlop3.b32 x, %1, 0xfffffffe, %3, 0xea;\nmov.b64 w, {x, %2};\n"
                 "st.relaxed.gpu.global.b64 [%0], w;\n}"
                 ::"l"(p), "r"(__float_as_uint(a)), "r"(__float_as_uint(b)), "r"(tag) : "memory");
}
__device__ __forceinline__ void st_fill4(float* p, uint32_t v) {
    asm volatile("{\n.reg .b64 w;\nmov.b64 w, {%1, %1};\nst.relaxed.gpu.global.v2.b64 [%0], {w, w};\n}" ::"l"(p), "r"(v) : "memory");
}
__device__ __forceinline__ uint2 ld_word(const float* p) {
    uint2 v;
    asm volatile("{\n.reg .b64 w;\nld.relaxed.gpu.global.b64 w, [%2];\nmov.b64 {%0,%1}, w;\n}" : "=r"(v.x), "=r"(v.y) : "l"(p) : "memory");
    return v;
}
__device__ __forceinline__ uint2 atom_word(const float* p) {
    uint2 v;
    asm volatile("{\n.reg .b64 w;\natom.relaxed.gpu.global.or.b64 w, [%2], 0;\nmov.b64 {%0,%1}, w;\n}" : "=r"(v.x), "=r"(v.y) : "l"(p) : "memory");
    return v;
}
__device__ __forceinline__ uint4 ld_word2(const float* p) {
    uint4 v;
    asm volatile("{\n.reg .b64 w0, w1;\nld.relaxed.gpu.global.v2.b64 {w0, w1}, [%4];\nmov.b64 {%0,%1}, w0;\nmov.b64 {%2,%3}, w1;\n}"
                 : "=r"(v.x), "=r"(v.y), "=r"(v.z), "=r"(v.w) : "l"(p) : "memory");
    return v;
}

__device__ __forceinline__ void add_out(const float4* acc, bf16* out, const float (&lo)[3][4], const float (&hi)[3][4],
                                        bool odd, bool third, bool live, uint32_t epoch) {
    const float v0 = odd ? lo[0][1] + hi[0][3] : lo[0][0] + hi[0][2];
    const float v1 = odd ? lo[1][1] + hi[1][3] : lo[1][0] + hi[1][2];
    const float v2 = odd ? lo[2][1] + hi[2][3] : lo[2][0] + hi[2][2];
    float o0, o1, o2, n = 0.f;
    asm volatile("{\n.reg .pred p;\nsetp.ne.u32 p, %5, 0;\n"
                 "@p atom.relaxed.gpu.global.add.v4.f32 {%0,%1,%2,%3}, [%4], {%6,%7,%8,%9};\n}"
                 : "=f"(o0), "=f"(o1), "=f"(o2), "+f"(n)
                 : "l"(acc), "r"((uint32_t)live), "f"(v0), "f"(v1), "f"(v2), "f"(1.0f) : "memory");
    asm volatile("{\n.reg .pred p, q;\nsetp.eq.f32 p, %4, %5;\nsetp.ne.and.u32 q, %6, 0, p;\n"
                 "@p st.global.u16 [%0], %1;\n@p st.global.u16 [%0+128], %2;\n@q st.global.u16 [%0+256], %3;\n}"
                 ::"l"(out), "h"(__bfloat16_as_ushort(__float2bfloat16_rn(o0 + v0))),
                   "h"(__bfloat16_as_ushort(__float2bfloat16_rn(o1 + v1))), "h"(__bfloat16_as_ushort(__float2bfloat16_rn(o2 + v2))),
                   "f"(n), "f"((float)(NSRC - 1)), "r"((uint32_t)third) : "memory");
    if (acc == g_acc && n == (float)(NSRC - 1))
        asm volatile("st.relaxed.gpu.global.u32 [%0], %1;" ::"l"(&g_sync.epoch), "r"(epoch + 1u) : "memory");
}

__device__ __forceinline__ int pair_of(int sg, uint32_t j) { return sg * G + (j % (G / 4)) * 4 + j / (G / 4); }
__device__ __forceinline__ int order_of(int r, int b) { return b * (G / 4) + (r >> 2); }

__device__ __forceinline__ float4* ocell(int pair, uint32_t i) {
    return g_oacc + (pair * 8 + (i >> 3)) * OAL + ((i >> 1) & 3) * OAS + (i & 1);
}

__device__ __forceinline__ void settle(int cycles) {
    const uint32_t t0 = (uint32_t)clock();
    while ((uint32_t)clock() - t0 < (uint32_t)cycles) __nanosleep(P_NSL);
}

struct Ring {
    uint32_t full, addr, phase, first_full;
    __device__ __forceinline__ void wait() const { mbar_wait(full, phase); }
    __device__ __forceinline__ void skip(int n) {
        full += n * 8; addr += n * SLOT;
        if (full >= first_full + NS * 8) { full -= NS * 8; addr -= NS * SLOT; phase ^= 1; }
    }
    __device__ __forceinline__ void release(int lane) {
        __syncwarp();
        if (lane == 0) mbar_arrive(full + NS * 8);
        full += 8; addr += SLOT;
        if (full == first_full + NS * 8) { full = first_full; addr -= NS * SLOT; phase ^= 1; }
    }
};

__device__ __forceinline__ void pin3(uint32_t (&v)[3]) {
    asm volatile("" : "+r"(v[0]), "+r"(v[1]), "+r"(v[2]));
}
__device__ __forceinline__ void gemv_loop(Ring& ring, int n, uint32_t a_addr, uint32_t a_step, uint32_t (&off)[3],
                                          float (&lo)[3][4], float (&hi)[3][4], int lane) {
    pin3(off);
#pragma unroll
    for (int s = 0; s < 3; s++)
#pragma unroll
        for (int e = 0; e < 4; e++) { lo[s][e] = 0.f; hi[s][e] = 0.f; }
#pragma unroll 1
    for (int it = 0; it < n; it++) {
        uint32_t a[4], b[3][4];
        lds128(a_addr, a);
        a_addr += a_step;
        ring.wait();
#pragma unroll
        for (int s = 0; s < 3; s++) ldsm_x4_t(ring.addr + off[s], b[s]);
#pragma unroll
        for (int s = 0; s < 3; s++) { mma16816(lo[s], a, b[s][0], b[s][1]); mma16816(hi[s], a, b[s][2], b[s][3]); }
        ring.release(lane);
    }
}

__global__ void __launch_bounds__(NTHR, 1)
fused_decode_kernel(const __grid_constant__ Maps maps, const bf16* __restrict__ x, bf16* __restrict__ out) {
    extern __shared__ __align__(1024) unsigned char smem[];
    const uint32_t sb = (uint32_t)__cvta_generic_to_shared(smem);
    const uint32_t bar_full = sb + SM_BAR;
    if (threadIdx.x == 0 && blockIdx.x < NATT) {
        TS(0);
#pragma unroll 1
        for (int i = 0; i < DEPTH0; i++) {
            mbar_init(bar_full + i * 8, 1);
            mbar_expect_tx(bar_full + i * 8, 12288);
            tma3d(sb + SM_RING + i * SLOT, &maps.wq, (blockIdx.x >> 2) * 3, (blockIdx.x & 3) * 160 + i * 32, bar_full + i * 8);
        }
        TS(1);
    }
    unsigned ptid, cta;
    asm volatile("mov.u32 %0, %%tid.x;\nmov.u32 %1, %%ctaid.x;" : "=r"(ptid), "=r"(cta));
    const int tid = ptid < 32 ? ptid + NCW * 32 : ptid < (NCW + 1) * 32 ? ptid - 32 : ptid;
    const int warp = tid >> 5, lane = tid & 31;
    const bool is_att = cta < NATT;
    const int h = cta >> 2, qd = cta & 3;
    const int sg = cta / G, r = cta % G;

    if (warp == NCW) {
        volatile int* pace = reinterpret_cast<volatile int*>(smem + SM_PACE);
        if (lane == 0) {
            if (!is_att) { TS(0); TS(1); }
            pace[0] = 0;
            pace[1] = is_att ? DEPTH : P_DEPTH_FFN;
#pragma unroll
            for (int i = 0; i < NBAR; i++)
                if (i >= DEPTH0 || !is_att)
                mbar_init(bar_full + i * 8, i < NS ? 1 : i < 2 * NS ? NCW : i < 2 * NS + NSTEP ? NXW : i == 2 * NS + NSTEP ? NXW * NB : i == NBAR - 1 ? NXW : 1);
            asm volatile("fence.mbarrier_init.release.cluster;" ::: "memory");
        }
        __syncwarp();
        asm volatile("bar.arrive 2, %0;" ::"n"(NTHR) : "memory");
        if (lane == 0) {
            const int n_items = is_att ? ITEMS_ATT : ITEMS_FFN;

            asm volatile("prefetch.tensormap [%0];" ::"l"(is_att ? &maps.k : &maps.w3) : "memory");
            asm volatile("prefetch.tensormap [%0];" ::"l"(&maps.v) : "memory");
            asm volatile("prefetch.tensormap [%0];" ::"l"(&maps.w2) : "memory");
            asm volatile("prefetch.tensormap [%0];" ::"l"(&maps.wo) : "memory");
#pragma unroll 1
            for (int i = is_att ? DEPTH0 : 0; i < n_items; i++) {
                const CUtensorMap* map;
                int c1, c2;
                uint32_t bytes = 12288;
                if (is_att) {
                    const uint32_t u = i - 5;
                    if (u < NKV) {
                        const uint32_t blk = u / 4;
                        const bool isv = blk >= 2 * NSTEP - LA || (blk >= LA && ((blk - LA) & 1));
                        const uint32_t step = blk < LA ? blk : blk >= 2 * NSTEP - LA ? blk - NSTEP : (blk - LA) / 2 + (isv ? 0 : LA);
                        const int pair = pair_of(sg, step * WPS + (u % 4) / NT);
                        map = isv ? &maps.v : &maps.k;
                        c1 = 0;
                        c2 = ((pair & 3) * NH + (pair >> 2)) * SK + (SK - WIN) + ((u % NT) * G + r) * TK;
                    } else if (i < 5) {
                        map = &maps.wq; c1 = h * 3; c2 = qd * 160 + i * 32;
                    } else if (u < NKV + 2) {
                        map = &maps.w2; c1 = qd * 5; c2 = h * 48 + (u - NKV) * 24; bytes = 7680;
                    } else {
                        map = &maps.wo; c1 = qd * 5; c2 = h * DH + (u - NKV - 2) * 32; bytes = 10240;
                    }
                } else {
                    map = i < 40 ? &maps.w1 : &maps.w3; c1 = qd * 6; c2 = (i < 40 ? i : i - 40) * 16;
                }
                const int depth = pace[1];
                const uint32_t slot = (uint32_t)i % NS, landed = i - depth;
                if (i >= NS) mbar_wait(bar_full + (NS + slot) * 8, ((uint32_t)i / NS - 1) & 1);
                mbar_expect_tx(bar_full + slot * 8, bytes);
                uint32_t dst = sb + SM_RING + slot * SLOT, fb = bar_full + slot * 8;
                asm volatile("" : "+r"(dst), "+r"(fb), "+l"(map), "+r"(c1), "+r"(c2));
                if (i >= depth) mbar_wait(bar_full + (landed % NS) * 8, (landed / NS) & 1);
                tma3d(dst, map, c1, c2, fb);
                pace[0] = landed + 1;
            }
            pace[0] = n_items - DEPTH;
        }
        return;
    }

    const int g = lane >> 2, t = lane & 3;
    uint32_t epoch;
    asm volatile("ld.relaxed.gpu.global.u32 %0, [%1];" : "=r"(epoch) : "l"(&g_sync.epoch) : "memory");

    if (warp == W_PACE) {
        const uint32_t tag = (epoch + 1u) & 1u;
        if (is_att) {
#pragma unroll
            for (int u = 0; u < WPS; u++) st_fill4(g_ml + ((sg * G + u * 16 + (lane >> 1)) * G + r) * MLS + (lane & 1) * 4, tag ^ 1u);
        }
        asm volatile("bar.sync 2, %0;" ::"n"(NTHR) : "memory");
        if (lane == 0) asm volatile("red.release.gpu.global.add.u32 [%0], 1;" ::"l"(&g_sync.inits) : "memory");
        if (!is_att) return;
        volatile int* pace = reinterpret_cast<volatile int*>(smem + SM_PACE);
        if (cta == 0 && lane == 0) asm volatile("st.relaxed.gpu.global.u32 [%0], %1;" ::"l"(&g_sync.prog[epoch & 1u]), "r"(0u) : "memory");
        int reported = 0, j = 0;
        bool due = false;
#pragma unroll 1
        for (unsigned it = 0;; it++) {
            const int landed = pace[0];
            int sum = 0;
            uint2 ml[WPS];
            uint32_t bad = 1u;
            unsigned n = (epoch + 1u) * NCTA;
            if (lane == 0 && reported < ITEMS_ATT - DEPTH)
                asm volatile("atom.relaxed.gpu.global.add.u32 %0, [%1], %2;"
                             : "=r"(sum) : "l"(&g_sync.prog[~epoch & 1u]), "r"(landed - reported) : "memory");
            if (due) {
#pragma unroll
                for (int u = 0; u < WPS; u++) {
                    const float* src = g_ml + (pair_of(sg, j * WPS + u) * G + lane % G) * MLS;
                    if (P_MLATOM) { if (lane < G) ml[u] = atom_word(src); else ml[u] = make_uint2(0xff000000u | tag, 0u); }
                    else ml[u] = ld_word(src);
                }
                if (j == 0) asm volatile("ld.acquire.gpu.global.u32 %0, [%1];" : "=r"(n) : "l"(&g_sync.inits) : "memory");
            }
            reported = landed;
            if (lane == 0 && P_GAIN) {
                const int avg16 = sum / (NATT / 16), lag16 = avg16 - landed * 16 + P_BIAS;
                pace[1] = avg16 >= ITEMS_ATT * 16 - P_FLUSH ? 8 : min(max(DEPTH + ((lag16 * P_GAIN + 128) >> 8), P_DMIN), P_DMAX);
            }
            if (due) {
                bad = 0;
#pragma unroll
                for (int u = 0; u < WPS; u++) bad |= ml[u].x ^ tag;
            }
            if (__all_sync(0xffffffffu, !(bad & 1u) && n == (epoch + 1u) * NCTA)) {
#pragma unroll
                for (int u = 0; u < WPS; u++) {
                    const float mk = __uint_as_float(ml[u].x & ~1u);
                    float M = mk;
#pragma unroll
                    for (int o = G / 2; o; o >>= 1) M = fmaxf(M, shx(M, o));
                    const float w = __expf(mk - M);
                    float L = w * __uint_as_float(ml[u].y);
#pragma unroll
                    for (int o = G / 2; o; o >>= 1) L += shx(L, o);
                    if (lane == r) reinterpret_cast<float*>(smem + SM_LS)[16 + (j & 3) * WPS + u] = __fdividef(w, L);
                }
                if (lane == r) {
                    mbar_arrive(bar_full + B_WRDY + (j & 3) * 8);
                    if (j == NSTEP - 1) TS(11);
                }
                j++;
                due = false;
            }
            if (j == NSTEP && landed >= ITEMS_ATT - DEPTH) return;
            if (P_MLWAIT == 1 && !due && j < NSTEP) due = mbar_test(bar_full + B_WTRIG + (j & 3) * 8, (j >> 2) & 1);
            if (landed < ITEMS_ATT - P_FAST) __nanosleep(P_SLEEP);
            if (P_MLWAIT == 0 && !due && j < NSTEP) due = mbar_test(bar_full + B_WTRIG + (j & 3) * 8, (j >> 2) & 1);
            if (it > SPIN_LIMIT) __trap();
        }
    }
    if (warp > W_PROD) {
        const uint32_t tag = (epoch + 1u) & 1u;
        const int e = tid - (W_PROD + 1) * 32;
        if (is_att) {
#pragma unroll 1
            for (int i = e; i < 192; i += NXW * 32)
                st_fill4(g_qpart + (cta * NB + i / 48) * VS + (i % 48) / 6 * 32 + (i % 6) * 4, tag ^ 1u);
            st_fill4(reinterpret_cast<float*>(ocell(cta, e)), 0u);
            if (e < 32) *reinterpret_cast<uint32_t*>(smem + SM_HF + e * 16 + 12) = 0u;
        } else {
#pragma unroll 1
            for (int c = e; c < 256; c += NXW * 32) {
                const bf16* xp = x + qd * DM + (c >> 6) * 160 + ((c >> 3) & 7) * 8 + (c & 3) * 2 + ((c >> 2) & 1);
                asm volatile("st.relaxed.gpu.global.v4.f32 [%0], {%1,%2,%3,%4};"
                             ::"l"(g_acc + (qd * 32 + (c >> 3)) * ACS + (c & 7)), "f"(__bfloat162float(xp[0])),
                               "f"(__bfloat162float(xp[64])), "f"((c & 32) ? 0.f : __bfloat162float(xp[128])), "f"(0.f) : "memory");
            }
        }
        asm volatile("bar.sync 2, %0;" ::"n"(NTHR) : "memory");
        if (!is_att) return;
        {
            const uint32_t eq = (e >> 5) * 24 + min(lane, 23), xw = eq / 6, xr = eq % 6;
            mbar_wait(bar_full + B_QTRIG, 0);
            if (e == 0) TS(10);
            settle(P_QDELAY);
#pragma unroll 1
            for (int j = 0; j < NSTEP; j++) {
                uint4 v[WPS][4];
                uint32_t bad;
                unsigned spin = 0;
                do {
#pragma unroll
                    for (int u = 0; u < WPS; u++) {
                        const int pair = pair_of(sg, j * WPS + u);
                        const float* src = g_qpart + ((pair >> 2) * 4 * NB + (pair & 3)) * VS + xw * 32 + xr * 4;
#pragma unroll
                        for (int k = 0; k < 4; k++) v[u][k] = ld_word2(src + k * NB * VS);
                    }
                    bad = 0;
#pragma unroll
                    for (int u = 0; u < WPS; u++)
#pragma unroll
                        for (int k = 0; k < 4; k++) bad |= (v[u][k].x ^ tag) | (v[u][k].z ^ tag);
                    if (++spin > SPIN_LIMIT) __trap();
                } while (bad & 1u);
#define SUM4(c) ((__uint_as_float(v[u][0].c) + __uint_as_float(v[u][1].c)) + (__uint_as_float(v[u][2].c) + __uint_as_float(v[u][3].c)))
#pragma unroll
                for (int u = 0; u < WPS; u++) {
                    unsigned char* dst = smem + SM_QS + (j * WPS + u) * (DH * 2) + (xr & 1) * 192 + ((xr >> 1) * 8 + xw) * 4;
                    *reinterpret_cast<uint32_t*>(dst) = pack_bf2(SUM4(x), SUM4(y));
                    *reinterpret_cast<uint32_t*>(dst + 96) = pack_bf2(SUM4(z), SUM4(w));
                }
#undef SUM4
                __syncwarp();
                if (lane == 0) mbar_arrive(bar_full + B_QRDY + j * 8);
                if (e == 0 && j == 0) TS(12);
            }
        }
        bool have_h = false;
#pragma unroll 1
        for (int b = 0; b <= NB; b++) {
            if (!have_h && (b == NB || order_of(r, b) >= HSTEP * WPS)) {
                have_h = true;
                mbar_wait(bar_full + B_HTRIG, 0);
#pragma unroll 1
                for (int i = e; i < 96; i += NXW * 32) {
                    const int k = (i % 24) * 2;
                    uint2 v;
                    unsigned spin = 0;
                    do {
                        v = ld_word(g_h + i / 24 * FF + h * 48 + k);
                        if (++spin > SPIN_LIMIT) __trap();
                    } while ((v.x ^ tag) & 1u);
                    *reinterpret_cast<uint32_t*>(smem + SM_HF + k / 24 * 256 + i / 24 * 64 + frag_off(k % 24)) = __byte_perm(v.x, v.y, 0x7632);
                }
                __syncwarp();
                if (lane == 0) mbar_arrive(bar_full + B_HRDY);
            }
            if (b == NB) break;
            const float4* src = ocell(h * NB + b, e);
            uint32_t dst = sb + SM_OF + (e >> 5) * 256 + b * 64 + frag_off(lane), ordy = bar_full + B_ORDY;
            asm volatile("" : "+r"(dst), "+l"(src), "+r"(ordy));
            mbar_wait(bar_full + B_OTRIG + b * 8, 0);
            const int pause = order_of(r, b) < G - P_URG * WPS ? P_SETTLE : P_SETTLE0;
            unsigned spin = 0;
            float o0, o1, o2, n;
            do {
                settle(pause);
                asm volatile("atom.relaxed.gpu.global.add.v4.f32 {%0,%1,%2,%3}, [%4], {%5,%5,%5,%5};"
                             : "=f"(o0), "=f"(o1), "=f"(o2), "=f"(n) : "l"(src), "f"(0.f) : "memory");
                asm volatile("st.shared.u16 [%0], %1;\nst.shared.u16 [%0+512], %2;\nst.shared.u16 [%0+1024], %3;"
                             ::"r"(dst), "h"(__bfloat16_as_ushort(__float2bfloat16_rn(o0))),
                               "h"(__bfloat16_as_ushort(__float2bfloat16_rn(o1))), "h"(__bfloat16_as_ushort(__float2bfloat16_rn(o2))) : "memory");
                if (++spin > SPIN_LIMIT) __trap();
            } while (n != (float)G);
            __syncwarp();
            if (lane == 0) mbar_arrive(ordy);
        }
        return;
    }

    if (warp < NB) {
        uint2 raw[5];
#pragma unroll
        for (int i = 0; i < 5; i++) raw[i] = __ldg(reinterpret_cast<const uint2*>(x + warp * DM) + i * 32 + lane);
        float s = 0.f;
#pragma unroll
        for (int i = 0; i < 5; i++) s += (bf_lo(raw[i].x) + bf_hi(raw[i].x)) + (bf_lo(raw[i].y) + bf_hi(raw[i].y));
#pragma unroll
        for (int o = 16; o; o >>= 1) s += shx(s, o);
        const float mean = s * (1.0f / DM);
        float q2 = 0.f;
#pragma unroll
        for (int i = 0; i < 5; i++) {
            const float d0 = bf_lo(raw[i].x) - mean, d1 = bf_hi(raw[i].x) - mean;
            const float d2 = bf_lo(raw[i].y) - mean, d3 = bf_hi(raw[i].y) - mean;
            q2 += (d0 * d0 + d1 * d1) + (d2 * d2 + d3 * d3);
        }
#pragma unroll
        for (int o = 16; o; o >>= 1) q2 += shx(q2, o);
        const float mb = bf_round(mean);
        const float rs = __frcp_rn(bf_round(__fsqrt_rn(bf_round(bf_round(q2 * (1.0f / DM)) + 1e-5f))));
        const uint32_t k = (lane * 4) & 31;
        unsigned char* dst = smem + SM_XF + warp * 64 +
            (is_att ? (lane >> 3) * 256 + frag_off(k) : (lane >> 2) * 256 + frag_off(k & 15));
        const uint32_t step = is_att ? 1024 : 2048;
#pragma unroll
        for (int i = 0; i < 5; i++) {
            const uint32_t d0 = pack_bf2(bf_lo(raw[i].x) - mb, bf_hi(raw[i].x) - mb);
            const uint32_t d1 = pack_bf2(bf_lo(raw[i].y) - mb, bf_hi(raw[i].y) - mb);
            *reinterpret_cast<uint32_t*>(dst + i * step) = pack_bf2(bf_lo(d0) * rs, bf_hi(d0) * rs);
            *reinterpret_cast<uint32_t*>(dst + i * step + 16) = pack_bf2(bf_lo(d1) * rs, bf_hi(d1) * rs);
        }
    }
    asm volatile("bar.sync 2, %0;" ::"n"(NTHR) : "memory");
    uint32_t tag = (epoch + 1u) & 1u;
    asm volatile("" : "+r"(tag));
    if (tid == 0) TS(3);

    Ring ring{bar_full, sb + SM_RING, 0u, bar_full};
    float lo[3][4] = {}, hi[3][4] = {};
    uint32_t off[3];
    const uint32_t a_lane = (g & 3) * 64 + t * 16;

    if (is_att) {
        float* lsum = reinterpret_cast<float*>(smem + SM_LS);
#pragma unroll 1
        for (int j = -1; j < NSTEP + LA; j++) {
            if (j >= 0 && j < NSTEP) {
                constexpr int WW = NCW / WPS;
                const int win = j * WPS + warp / WW;
                uint32_t qf[6][4];
                mbar_wait(bar_full + B_QRDY + j * 8, 0);
                if (j == 0 && tid == 0) TS(6);
#pragma unroll
                for (int i = 0; i < 6; i++) lds128(sb + SM_QS + win * (DH * 2) + t * 96 + i * 16, qf[i]);
                const uint32_t key = (warp & 1) * 16 + (lane & 15);
                const uint32_t item = 5 + (j + max(j - LA, 0)) * 4 + (warp >> 1), slot = item % NS;
#pragma unroll
                for (int s = 0; s < 3; s++)
                    off[s] = sb + SM_RING + slot * SLOT + key * 384 + s * 128 + (((lane >> 4) ^ ((3 * key + s) & 7)) << 4);
                pin3(off);
                mbar_wait(bar_full + slot * 8, (item / NS) & 1);
                float c[3][4] = {};
#pragma unroll
                for (int dq = 0; dq < 4; dq++)
#pragma unroll
                    for (int s = 0; s < 3; s++) {
                        uint32_t a[4];
                        ldsm_x4(off[s] ^ (dq << 5), a);
                        mma16816(c[s], a, qf[s * 2 + (dq >> 1)][(dq & 1) * 2], qf[s * 2 + (dq >> 1)][(dq & 1) * 2 + 1]);
                    }
                __syncwarp();
                if (lane == 0)
                    asm volatile("mbarrier.arrive.shared::cta.b64 _, [%0], %1;" ::"r"(bar_full + (NS + slot) * 8), "n"(NCW / 2) : "memory");
                ring.skip(4);
                const float raw = (t & 1) ? (c[0][2] + c[1][2]) + c[2][2] : (c[0][0] + c[1][0]) + c[2][0];
                const float sv = bf_round(bf_round(raw) * 0.07216878364870323f);
                if (tid == 0 && j == NSTEP - 1) TS(14);
                float m = fmaxf(sv, shx(sv, 1));
#pragma unroll
                for (int o = 4; o < 32; o <<= 1) m = fmaxf(m, shx(m, o));
                if (lane == 0) lsum[8 + warp] = m;
                cons_bar();
#pragma unroll
                for (int i = 0; i < WW / 4; i++) {
                    const float4 m4 = reinterpret_cast<const float4*>(lsum)[2 + warp / WW * (WW / 4) + i];
                    m = fmaxf(m, fmaxf(fmaxf(m4.x, m4.y), fmaxf(m4.z, m4.w)));
                }
                float l = __expf(sv - m);
                *reinterpret_cast<bf16*>(smem + SM_PF + ((j & 3) * 4 + (warp >> 1)) * 64 + frag_off((warp & 1) * 16 + (t & 1) * 8 + g)) =
                    __float2bfloat16_rn(l);
                l += shx(l, 1);
#pragma unroll
                for (int o = 4; o < 32; o <<= 1) l += shx(l, o);
                if (lane == 0) lsum[warp] = l;
                cons_bar();
                if (tid % (WW * 32) < 4) {
                    l = 0.f;
#pragma unroll
                    for (int i = 0; i < WW / 4; i++) {
                        const float4 l4 = reinterpret_cast<const float4*>(lsum)[warp / 4 + i];
                        l += (l4.x + l4.y) + (l4.z + l4.w);
                    }
                    st_tag2(g_ml + (pair_of(sg, win) * G + r) * MLS + lane * 2, m, l, tag);
                    if (tid == 0) {
                        mbar_arrive(bar_full + B_WTRIG + (j & 3) * 8);
                        if (j == HSTEP) mbar_arrive(bar_full + B_HTRIG);
                    }
                }
                if (tid == 0 && j == NSTEP - 1) TS(13);
                if (j < LA) continue;
            }
            const bool kv = j >= 0;
            const uint32_t jv = j - LA;
#pragma unroll
            for (int s = 0; s < 3; s++) off[s] = lane * 384 + s * 128 + ((warp ^ ((3 * lane + s) & 7)) << 4);
#pragma unroll 1
            for (int u = 0; u < (kv ? WPS : 1); u++) {
                const int pair = pair_of(sg, jv * WPS + u);
                uint32_t trig = !kv ? bar_full + B_QTRIG : (pair >> 2) == h ? bar_full + B_OTRIG + (pair & 3) * 8 : 0;
                if (tid != 0) trig = 0;
                float4* oacc = ocell(pair, warp * 8 + 2 * t + (g & 1));
                uint32_t wrdy = bar_full + B_WRDY + (jv & 3) * 8;
                asm volatile("" : "+l"(oacc), "+r"(trig), "+r"(wrdy));
                gemv_loop(ring, kv ? NT : 5,
                          kv ? sb + SM_PF + ((jv & 3) * 4 + u * NT) * 64 + t * 16 : sb + SM_XF + qd * 5 * 256 + a_lane,
                          kv ? 64 : 256, off, lo, hi, lane);
                if (kv) {
                    mbar_wait(wrdy, (jv >> 2) & 1);
                    const float w = lsum[16 + (jv & 3) * WPS + u];
                    if (g < 2)
                        asm volatile("red.relaxed.gpu.global.add.v4.f32 [%0], {%1,%2,%3,%4};"
                                     ::"l"(oacc), "f"(w * (g ? lo[0][1] + hi[0][3] : lo[0][0] + hi[0][2])),
                                       "f"(w * (g ? lo[1][1] + hi[1][3] : lo[1][0] + hi[1][2])),
                                       "f"(w * (g ? lo[2][1] + hi[2][3] : lo[2][0] + hi[2][2])), "f"(1.0f) : "memory");
                } else if (g < NB) {
#pragma unroll
                    for (int s = 0; s < 3; s++)
                        st_tag2(g_qpart + (cta * NB + g) * VS + warp * 32 + 2 * t + s * 8, lo[s][0] + hi[s][2], lo[s][1] + hi[s][3], tag);
                }
                if (trig) mbar_arrive(trig);
            }
            const bool pass = j == NSTEP + LA - 1;
            if (pass && tid == 0) TS(5);
            if (kv && !pass && j != P_DRY) continue;
            if (tid == 0 && j < 0) TS(4);

            {
                constexpr int I0 = 5 + NKV;
                static_assert(((I0 / NS) & 1) == 0 && I0 / NS == (I0 + 7) / NS, "tail items complete an even phase");
                const uint32_t done = bar_full + B_QTRIG;
                uint32_t fb = pass ? bar_full + (I0 % NS) * 8 : done, fs = pass ? 8 : 0, ordy = pass ? bar_full + B_ORDY : done;
                uint32_t off2[3], a[8][4], b[8][3][4], a_addr = sb + SM_HF + a_lane;
#pragma unroll
                for (int s = 0; s < 3; s++) {
                    const uint32_t w64 = lane * 320 + (warp + 8 * s) * 16;
                    off[s] = sb + SM_RING + (I0 % NS) * SLOT + (w64 ^ (((w64 >> 7) & 3) << 4));
                    off2[s] = lane < 24 ? off[s] : off[s] - 8 * 320;
#pragma unroll
                    for (int e = 0; e < 4; e++) { lo[s][e] = 0.f; hi[s][e] = 0.f; }
                }
                const float4* accp = g_acc + (((g & 3) * 4 + qd) * NCW + warp) * ACS + (g >> 2) * 4 + t;
                bf16* outp = out + (g & 3) * DM + qd * 160 + warp * 8 + 2 * t + (g >> 2);
                pin3(off);
                asm volatile("" : "+l"(accp), "+l"(outp), "+r"(a_addr), "+r"(ordy), "+r"(fb), "+r"(fs));
                auto load_b = [&](int i, bool& next) {
                    if (!next) mbar_wait(fb + i * fs, 0);
                    if (i < 7) next = mbar_test(fb + (i + 1) * fs, 0);
#pragma unroll
                    for (int s = 0; s < 3; s++)
                        if (s < 2 || warp < 4) ldsm_x4_t((i < 2 ? off2[s] : off[s]) + i * SLOT, b[i][s]);
                };
                auto mul = [&](int i) {
#pragma unroll
                    for (int s = 0; s < 3; s++)
                        if (s < 2 || warp < 4) { mma16816(lo[s], a[i], b[i][s][0], b[i][s][1]); mma16816(hi[s], a[i], b[i][s][2], b[i][s][3]); }
                };
                bool next = mbar_test(fb, 0);
                mbar_wait(pass ? bar_full + B_HRDY : done, 0);
                lds128(a_addr, a[0]);
                lds128(a_addr + 256, a[1]);
                load_b(0, next);
                load_b(1, next);
                bool early = mbar_test(ordy, 0);
                mul(0);
                mul(1);
                if (pass && tid == 0) TS(31);
                unsigned spin = 0;
                while (!early && !mbar_test(fb + P_DEC * fs, 0)) {
                    early = mbar_test(ordy, 0);
                    if (++spin > SPIN_LIMIT) __trap();
                }
                if (pass ? __all_sync(0xffffffffu, early) : j < 0) {
                    if (pass && tid == 0) TS(7);
#pragma unroll
                    for (int i = 2; i < 8; i++) lds128(a_addr + i * 256, a[i]);
                    load_b(2, next);
#pragma unroll
                    for (int i = 2; i < 7; i++) { load_b(i + 1, next); mul(i); }
                    mul(7);
                } else {
#pragma unroll
                    for (int i = 2; i < 8; i++) load_b(i, next);
                    mbar_wait(ordy, 0);
                    if (pass && tid == 0) TS(7);
#pragma unroll
                    for (int i = 2; i < 8; i++) lds128(a_addr + i * 256, a[i]);
#pragma unroll
                    for (int i = 2; i < 8; i++) mul(i);
                }
                if (pass && tid == 0) TS(8);
                add_out(accp, outp, lo, hi, g >= NB, warp < 4, pass, epoch);
            }
        }
        if (tid == 0) { TS(9); TS_DUMP(3, 32); }
    } else {
        float gate[6][2];
#pragma unroll
        for (int s = 0; s < 3; s++) {
            const uint32_t r128 = (lane & 15) * 6 + 2 * s + (lane >> 4);
            off[s] = r128 * 128 + ((warp ^ (r128 & 7)) << 4);
        }
#pragma unroll 1
        for (int ps = 0; ps < 2; ps++) {
#pragma unroll
            for (int s = 0; s < 3; s++) {
                gate[2 * s][0] = lo[s][0]; gate[2 * s][1] = lo[s][1];
                gate[2 * s + 1][0] = hi[s][0]; gate[2 * s + 1][1] = hi[s][1];
            }
            gemv_loop(ring, 40, sb + SM_XF + a_lane, 256, off, lo, hi, lane);
        }
#pragma unroll
        for (int p = 0; p < 6; p++) {
            float hv[2];
#pragma unroll
            for (int e = 0; e < 2; e++) {
                const float gt = bf_round(gate[p][e]);
                hv[e] = bf_round(bf_round(__fdividef(gt, 1.0f + __expf(-gt))) * bf_round((p & 1) ? hi[p >> 1][e] : lo[p >> 1][e]));
            }
            if (g < NB) st_tag2(g_h + g * FF + qd * 384 + p * 64 + warp * 8 + 2 * t, hv[0], hv[1], tag);
        }
        if (tid == 0) { TS(9); TS_DUMP(3, 10); }
    }
}

typedef CUresult (*EncodeFn)(CUtensorMap*, CUtensorMapDataType, cuuint32_t, void*, const cuuint64_t*, const cuuint64_t*,
                             const cuuint32_t*, const cuuint32_t*, CUtensorMapInterleave, CUtensorMapSwizzle,
                             CUtensorMapL2promotion, CUtensorMapFloatOOBfill);

void make_map(EncodeFn enc, CUtensorMap* m, const void* p, uint64_t rows, uint64_t cols, uint32_t inner, uint32_t parts,
              uint32_t box_rows) {
    const cuuint64_t dims[3] = {inner, cols / inner, rows};
    const cuuint64_t strides[2] = {inner * 2ull, cols * 2ull};
    const cuuint32_t box[3] = {inner, parts, box_rows};
    const cuuint32_t es[3] = {1, 1, 1};
    enc(m, CU_TENSOR_MAP_DATA_TYPE_BFLOAT16, 3, const_cast<void*>(p), dims, strides, box, es, CU_TENSOR_MAP_INTERLEAVE_NONE,
        inner == 64 ? CU_TENSOR_MAP_SWIZZLE_128B : CU_TENSOR_MAP_SWIZZLE_64B, CU_TENSOR_MAP_L2_PROMOTION_NONE,
        CU_TENSOR_MAP_FLOAT_OOB_FILL_NONE);
}

}

extern "C" void kernel_launch(void* const* d_in, const int* in_sizes, int n_in, void* d_out, int out_size) {
    (void)in_sizes; (void)n_in; (void)out_size;
    static EncodeFn enc = nullptr;
    if (!enc) {
        void* fn = nullptr;
        cudaDriverEntryPointQueryResult qr;
        cudaGetDriverEntryPoint("cuTensorMapEncodeTiled", &fn, cudaEnableDefault, &qr);
        enc = (EncodeFn)fn;
        cudaFuncSetAttribute(fused_decode_kernel, cudaFuncAttributeMaxDynamicSharedMemorySize, SM_TOTAL);
    }
    Maps maps;
    make_map(enc, &maps.k, d_in[1], (uint64_t)NB * NH * SK, DH, 64, 3, TK);
    make_map(enc, &maps.v, d_in[2], (uint64_t)NB * NH * SK, DH, 64, 3, TK);
    make_map(enc, &maps.wq, d_in[3], DM, NH * DH, 64, 3, 32);
    make_map(enc, &maps.wo, d_in[4], NH * DH, DM, 32, 5, 32);
    make_map(enc, &maps.w1, d_in[6], DM, FF, 64, 6, 16);
    make_map(enc, &maps.w3, d_in[7], DM, FF, 64, 6, 16);
    make_map(enc, &maps.w2, d_in[8], FF, DM, 32, 5, 24);
    fused_decode_kernel<<<NCTA, NTHR, SM_TOTAL>>>(maps, (const bf16*)d_in[0], (bf16*)d_out);
}
```

```cpp
#include <cuda_runtime.h>
#include <cuda.h>
#include <cuda_bf16.h>
#include <stdint.h>

namespace {

typedef __nv_bfloat16 bf16;

constexpr int NB = 4, DM = 640, NH = 32, DH = 192, SK = 8192, WIN = 2048, FF = 1536;

#define P_G 32
#define P_DEPTH 4
#define P_DEPTH_FFN 5
#define P_GAIN 6
#define P_BIAS 16
#define P_SLEEP 500
#define P_DMIN 3
#define P_DMAX 6
#define P_SETTLE 3000
#define P_QDELAY 1600
#define P_NSL 20
#define P_DRY 4
#define P_FLUSH 112
#define P_DEC 6
#define P_FAST 24
#define P_LA 2
#define P_HEADMAJOR 0
#define P_MLATOM 0
#define P_MLWAIT 1
#define P_MLS 8
#define P_OAL 72
#define P_OAS 2
#define P_URG 1
#define P_SETTLE0 0
#define P_PAD 0
#define P_NS 16

constexpr int G = P_G;
constexpr int TK = 32;
constexpr int NT = WIN / TK / G;
constexpr int NSTEP = 16;
constexpr int WPS = G / NSTEP;
constexpr int LA = P_LA;
constexpr int MLS = P_MLS;
constexpr int OAL = P_OAL, OAS = P_OAS;
constexpr int HSTEP = 11;
constexpr int NS = P_NS;
constexpr int SLOT = 12288;
constexpr int DEPTH = P_DEPTH;
#define P_D0 5
constexpr int DEPTH0 = P_D0;
static_assert(DEPTH0 <= 5, "DEPTH0");
constexpr int NATT = 128, NFFN = 4, NCTA = NATT + NFFN;
constexpr int NCW = 8;
constexpr int NXW = 2;
constexpr int W_PROD = NCW, W_PACE = NCW + 1 + NXW;
constexpr int NTHR = (W_PACE + 1) * 32;
constexpr int NSRC = NH;
constexpr int VS = 256;
#define P_ACS 16
constexpr int ACS = P_ACS;
static_assert(G == 16 || G == 32, "G");

constexpr int SM_RING = 0;
constexpr int SM_XF = SM_RING + NS * SLOT;
constexpr int SM_QS = SM_XF + 20 * 256;
constexpr int SM_PF = SM_QS + G * DH * 2;
constexpr int SM_HF = SM_PF + 4 * 4 * 64;
constexpr int SM_OF = SM_HF + 2 * 256;
constexpr int SM_LS = SM_OF + 6 * 256;
constexpr int SM_ATT_END = SM_LS + 96;
constexpr int SM_FFN_END = SM_XF + 40 * 256;
constexpr int SM_BAR = SM_ATT_END > SM_FFN_END ? SM_ATT_END : SM_FFN_END;
constexpr int B_QRDY = 2 * NS * 8, B_ORDY = B_QRDY + NSTEP * 8, B_OTRIG = B_ORDY + 8, B_QTRIG = B_OTRIG + 32,
              B_WTRIG = B_QTRIG + 8, B_WRDY = B_WTRIG + 32, B_HTRIG = B_WRDY + 32, B_HRDY = B_HTRIG + 8,
              NBAR = 2 * NS + NSTEP + 16;
constexpr int SM_PACE = SM_BAR + NBAR * 8;
constexpr int SM_TS = SM_PACE + 8;
constexpr int SM_TOTAL = SM_TS + 256;
static_assert(SM_TOTAL <= 232448, "smem");

constexpr int NKV = 2 * NT * G;
constexpr int ITEMS_ATT = 5 + NKV + 2 + 6;
constexpr int ITEMS_FFN = 80;

struct Maps { CUtensorMap k, v, wq, wo, w1, w3, w2; };

struct alignas(32) Sync { unsigned epoch, inits, prog[2]; };
__device__ Sync g_sync;
__device__ __align__(128) float g_qpart[NATT * NB * VS];
__device__ __align__(128) float g_ml[NATT * G * MLS];
__device__ __align__(128) float g_h[NB * FF + P_PAD * 262144];
__device__ __align__(128) float4 g_oacc[NATT * 8 * OAL];
__device__ __align__(128) float4 g_acc[NB * 4 * NCW * ACS];
#define TS(i)
#define TS_DUMP(lo, hi)

constexpr unsigned SPIN_LIMIT = 1u << 24;

__device__ __forceinline__ void mbar_init(uint32_t bar, int cnt) {
    asm volatile("mbarrier.init.shared::cta.b64 [%0], %1;" ::"r"(bar), "r"(cnt) : "memory");
}
__device__ __forceinline__ void mbar_expect_tx(uint32_t bar, uint32_t bytes) {
    asm volatile("mbarrier.arrive.expect_tx.shared::cta.b64 _, [%0], %1;" ::"r"(bar), "r"(bytes) : "memory");
}
__device__ __forceinline__ void mbar_arrive(uint32_t bar) {
    asm volatile("mbarrier.arrive.shared::cta.b64 _, [%0];" ::"r"(bar) : "memory");
}
__device__ __forceinline__ void mbar_wait(uint32_t bar, uint32_t parity) {
    asm volatile("{\n.reg .pred p, q;\n.reg .u32 n;\nmov.u32 n, 0;\n"
                 "W: mbarrier.try_wait.parity.shared::cta.b64 p, [%0], %1;\n"
                 "@p bra D;\nadd.u32 n, n, 1;\nsetp.lt.u32 q, n, %2;\n@q bra W;\ntrap;\nD:\n}"
                 ::"r"(bar), "r"(parity), "n"(SPIN_LIMIT) : "memory");
}
__device__ __forceinline__ bool mbar_test(uint32_t bar, uint32_t parity) {
    uint32_t ok;
    asm volatile("{\n.reg .pred p;\nmbarrier.test_wait.parity.shared::cta.b64 p, [%1], %2;\nselp.u32 %0, 1, 0, p;\n}"
                 : "=r"(ok) : "r"(bar), "r"(parity) : "memory");
    return ok;
}
__device__ __forceinline__ void tma3d(uint32_t dst, const CUtensorMap* map, int c1, int c2, uint32_t bar) {
    const uint64_t pol = 0x12F0000000000000ull;
    asm volatile("cp.async.bulk.tensor.3d.shared::cluster.global.mbarrier::complete_tx::bytes.L2::cache_hint "
                 "[%0], [%1, {%2, %3, %4}], [%5], %6;"
                 ::"r"(dst), "l"(map), "r"(0), "r"(c1), "r"(c2), "r"(bar), "l"(pol) : "memory");
}
__device__ __forceinline__ void ldsm_x4(uint32_t addr, uint32_t (&r)[4]) {
    asm volatile("ldmatrix.sync.aligned.m8n8.x4.shared.b16 {%0,%1,%2,%3}, [%4];"
                 : "=r"(r[0]), "=r"(r[1]), "=r"(r[2]), "=r"(r[3]) : "r"(addr) : "memory");
}
__device__ __forceinline__ void ldsm_x4_t(uint32_t addr, uint32_t (&r)[4]) {
    asm volatile("ldmatrix.sync.aligned.m8n8.x4.trans.shared.b16 {%0,%1,%2,%3}, [%4];"
                 : "=r"(r[0]), "=r"(r[1]), "=r"(r[2]), "=r"(r[3]) : "r"(addr) : "memory");
}
__device__ __forceinline__ void lds128(uint32_t addr, uint32_t (&r)[4]) {
    asm volatile("ld.shared.v4.u32 {%0,%1,%2,%3}, [%4];"
                 : "=r"(r[0]), "=r"(r[1]), "=r"(r[2]), "=r"(r[3]) : "r"(addr) : "memory");
}
__device__ __forceinline__ void mma16816(float (&c)[4], const uint32_t (&a)[4], uint32_t b0, uint32_t b1) {
    asm volatile("mma.sync.aligned.m16n8k16.row.col.f32.bf16.bf16.f32 {%0,%1,%2,%3}, {%4,%5,%6,%7}, {%8,%9}, {%0,%1,%2,%3};"
                 : "+f"(c[0]), "+f"(c[1]), "+f"(c[2]), "+f"(c[3])
                 : "r"(a[0]), "r"(a[1]), "r"(a[2]), "r"(a[3]), "r"(b0), "r"(b1));
}
__device__ __forceinline__ void cons_bar() { asm volatile("bar.sync 1, 256;" ::: "memory"); }

__device__ __forceinline__ float bf_round(float v) { return __bfloat162float(__float2bfloat16_rn(v)); }
__device__ __forceinline__ uint32_t pack_bf2(float lo, float hi) {
    __nv_bfloat162 t = __floats2bfloat162_rn(lo, hi);
    return *reinterpret_cast<uint32_t*>(&t);
}
__device__ __forceinline__ float bf_lo(uint32_t u) { return __uint_as_float(u << 16); }
__device__ __forceinline__ float bf_hi(uint32_t u) { return __uint_as_float(u & 0xffff0000u); }
__device__ __forceinline__ float shx(float v, int o) { return __shfl_xor_sync(0xffffffffu, v, o); }

__device__ __forceinline__ uint32_t frag_off(uint32_t k) {
    return ((k >> 1) & 3) * 16 + ((k >> 3) & 1) * 8 + ((k >> 4) & 1) * 4 + (k & 1) * 2;
}

__device__ __forceinline__ void st_tag2(float* p, float a, float b, uint32_t tag) {
    asm volatile("{\n.reg .b64 w;\n.reg .b32 x;\nlop3.b32 x, %1, 0xfffffffe, %3, 0xea;\nmov.b64 w, {x, %2};\n"
                 "st.relaxed.gpu.global.b64 [%0], w;\n}"
                 ::"l"(p), "r"(__float_as_uint(a)), "r"(__float_as_uint(b)), "r"(tag) : "memory");
}
__device__ __forceinline__ void st_fill4(float* p, uint32_t v) {
    asm volatile("{\n.reg .b64 w;\nmov.b64 w, {%1, %1};\nst.relaxed.gpu.global.v2.b64 [%0], {w, w};\n}" ::"l"(p), "r"(v) : "memory");
}
__device__ __forceinline__ uint2 ld_word(const float* p) {
    uint2 v;
    asm volatile("{\n.reg .b64 w;\nld.relaxed.gpu.global.b64 w, [%2];\nmov.b64 {%0,%1}, w;\n}" : "=r"(v.x), "=r"(v.y) : "l"(p) : "memory");
    return v;
}
__device__ __forceinline__ uint2 atom_word(const float* p) {
    uint2 v;
    asm volatile("{\n.reg .b64 w;\natom.relaxed.gpu.global.or.b64 w, [%2], 0;\nmov.b64 {%0,%1}, w;\n}" : "=r"(v.x), "=r"(v.y) : "l"(p) : "memory");
    return v;
}
__device__ __forceinline__ uint4 ld_word2(const float* p) {
    uint4 v;
    asm volatile("{\n.reg .b64 w0, w1;\nld.relaxed.gpu.global.v2.b64 {w0, w1}, [%4];\nmov.b64 {%0,%1}, w0;\nmov.b64 {%2,%3}, w1;\n}"
                 : "=r"(v.x), "=r"(v.y), "=r"(v.z), "=r"(v.w) : "l"(p) : "memory");
    return v;
}

__device__ __forceinline__ void add_out(const float4* acc, bf16* out, const float (&lo)[3][4], const float (&hi)[3][4],
                                        bool odd, bool third, bool live, uint32_t epoch) {
    const float v0 = odd ? lo[0][1] + hi[0][3] : lo[0][0] + hi[0][2];
    const float v1 = odd ? lo[1][1] + hi[1][3] : lo[1][0] + hi[1][2];
    const float v2 = odd ? lo[2][1] + hi[2][3] : lo[2][0] + hi[2][2];
    float o0, o1, o2, n = 0.f;
    asm volatile("{\n.reg .pred p;\nsetp.ne.u32 p, %5, 0;\n"
                 "@p atom.relaxed.gpu.global.add.v4.f32 {%0,%1,%2,%3}, [%4], {%6,%7,%8,%9};\n}"
                 : "=f"(o0), "=f"(o1), "=f"(o2), "+f"(n)
                 : "l"(acc), "r"((uint32_t)live), "f"(v0), "f"(v1), "f"(v2), "f"(1.0f) : "memory");
    asm volatile("{\n.reg .pred p, q;\nsetp.eq.f32 p, %4, %5;\nsetp.ne.and.u32 q, %6, 0, p;\n"
                 "@p st.global.u16 [%0], %1;\n@p st.global.u16 [%0+128], %2;\n@q st.global.u16 [%0+256], %3;\n}"
                 ::"l"(out), "h"(__bfloat16_as_ushort(__float2bfloat16_rn(o0 + v0))),
                   "h"(__bfloat16_as_ushort(__float2bfloat16_rn(o1 + v1))), "h"(__bfloat16_as_ushort(__float2bfloat16_rn(o2 + v2))),
                   "f"(n), "f"((float)(NSRC - 1)), "r"((uint32_t)third) : "memory");
    if (acc == g_acc && n == (float)(NSRC - 1))
        asm volatile("st.relaxed.gpu.global.u32 [%0], %1;" ::"l"(&g_sync.epoch), "r"(epoch + 1u) : "memory");
}

__device__ __forceinline__ int pair_of(int sg, uint32_t j) { return sg * G + (j % (G / 4)) * 4 + j / (G / 4); }
__device__ __forceinline__ int order_of(int r, int b) { return b * (G / 4) + (r >> 2); }

__device__ __forceinline__ float4* ocell(int pair, uint32_t i) {
    return g_oacc + (pair * 8 + (i >> 3)) * OAL + ((i >> 1) & 3) * OAS + (i & 1);
}

__device__ __forceinline__ void settle(int cycles) {
    const uint32_t t0 = (uint32_t)clock();
    while ((uint32_t)clock() - t0 < (uint32_t)cycles) __nanosleep(P_NSL);
}

struct Ring {
    uint32_t full, addr, phase, first_full;
    __device__ __forceinline__ void wait() const { mbar_wait(full, phase); }
    __device__ __forceinline__ void skip(int n) {
        full += n * 8; addr += n * SLOT;
        if (full >= first_full + NS * 8) { full -= NS * 8; addr -= NS * SLOT; phase ^= 1; }
    }
    __device__ __forceinline__ void release(int lane) {
        __syncwarp();
        if (lane == 0) mbar_arrive(full + NS * 8);
        full += 8; addr += SLOT;
        if (full == first_full + NS * 8) { full = first_full; addr -= NS * SLOT; phase ^= 1; }
    }
};

__device__ __forceinline__ void pin3(uint32_t (&v)[3]) {
    asm volatile("" : "+r"(v[0]), "+r"(v[1]), "+r"(v[2]));
}
__device__ __forceinline__ void gemv_loop(Ring& ring, int n, uint32_t a_addr, uint32_t a_step, uint32_t (&off)[3],
                                          float (&lo)[3][4], float (&hi)[3][4], int lane) {
    pin3(off);
#pragma unroll
    for (int s = 0; s < 3; s++)
#pragma unroll
        for (int e = 0; e < 4; e++) { lo[s][e] = 0.f; hi[s][e] = 0.f; }
#pragma unroll 1
    for (int it = 0; it < n; it++) {
        uint32_t a[4], b[3][4];
        lds128(a_addr, a);
        a_addr += a_step;
        ring.wait();
#pragma unroll
        for (int s = 0; s < 3; s++) ldsm_x4_t(ring.addr + off[s], b[s]);
#pragma unroll
        for (int s = 0; s < 3; s++) { mma16816(lo[s], a, b[s][0], b[s][1]); mma16816(hi[s], a, b[s][2], b[s][3]); }
        ring.release(lane);
    }
}

__global__ void __launch_bounds__(NTHR, 1)
fused_decode_kernel(const __grid_constant__ Maps maps, const bf16* __restrict__ x, bf16* __restrict__ out) {
    extern __shared__ __align__(1024) unsigned char smem[];
    const uint32_t sb = (uint32_t)__cvta_generic_to_shared(smem);
    const uint32_t bar_full = sb + SM_BAR;
    if (threadIdx.x == 0 && blockIdx.x < NATT) {
        TS(0);
#pragma unroll 1
        for (int i = 0; i < DEPTH0; i++) {
            mbar_init(bar_full + i * 8, 1);
            mbar_expect_tx(bar_full + i * 8, 12288);
            tma3d(sb + SM_RING + i * SLOT, &maps.wq, (blockIdx.x >> 2) * 3, (blockIdx.x & 3) * 160 + i * 32, bar_full + i * 8);
        }
        TS(1);
    }
    unsigned ptid, cta;
    asm volatile("mov.u32 %0, %%tid.x;\nmov.u32 %1, %%ctaid.x;" : "=r"(ptid), "=r"(cta));
    const int tid = ptid < 32 ? ptid + NCW * 32 : ptid < (NCW + 1) * 32 ? ptid - 32 : ptid;
    const int warp = tid >> 5, lane = tid & 31;
    const bool is_att = cta < NATT;
    const int h = cta >> 2, qd = cta & 3;
    const int sg = cta / G, r = cta % G;

    if (warp == NCW) {
        volatile int* pace = reinterpret_cast<volatile int*>(smem + SM_PACE);
        if (lane == 0) {
            if (!is_att) { TS(0); TS(1); }
            pace[0] = 0;
            pace[1] = is_att ? DEPTH : P_DEPTH_FFN;
#pragma unroll
            for (int i = 0; i < NBAR; i++)
                if (i >= DEPTH0 || !is_att)
                mbar_init(bar_full + i * 8, i < NS ? 1 : i < 2 * NS ? NCW : i < 2 * NS + NSTEP ? NXW : i == 2 * NS + NSTEP ? NXW * NB : i == NBAR - 1 ? NXW : 1);
            asm volatile("fence.mbarrier_init.release.cluster;" ::: "memory");
        }
        __syncwarp();
        asm volatile("bar.arrive 2, %0;" ::"n"(NTHR) : "memory");
        if (lane == 0) {
            const int n_items = is_att ? ITEMS_ATT : ITEMS_FFN;

            asm volatile("prefetch.tensormap [%0];" ::"l"(is_att ? &maps.k : &maps.w3) : "memory");
            asm volatile("prefetch.tensormap [%0];" ::"l"(&maps.v) : "memory");
            asm volatile("prefetch.tensormap [%0];" ::"l"(&maps.w2) : "memory");
            asm volatile("prefetch.tensormap [%0];" ::"l"(&maps.wo) : "memory");
#pragma unroll 1
            for (int i = is_att ? DEPTH0 : 0; i < n_items; i++) {
                const CUtensorMap* map;
                int c1, c2;
                uint32_t bytes = 12288;
                if (is_att) {
                    const uint32_t u = i - 5;
                    if (u < NKV) {
                        const uint32_t blk = u / 4;
                        const bool isv = blk >= 2 * NSTEP - LA || (blk >= LA && ((blk - LA) & 1));
                        const uint32_t step = blk < LA ? blk : blk >= 2 * NSTEP - LA ? blk - NSTEP : (blk - LA) / 2 + (isv ? 0 : LA);
                        const int pair = pair_of(sg, step * WPS + (u % 4) / NT);
                        map = isv ? &maps.v : &maps.k;
                        c1 = 0;
                        c2 = ((pair & 3) * NH + (pair >> 2)) * SK + (SK - WIN) + ((u % NT) * G + r) * TK;
                    } else if (i < 5) {
                        map = &maps.wq; c1 = h * 3; c2 = qd * 160 + i * 32;
                    } else if (u < NKV + 2) {
                        map = &maps.w2; c1 = qd * 5; c2 = h * 48 + (u - NKV) * 24; bytes = 7680;
                    } else {
                        map = &maps.wo; c1 = qd * 5; c2 = h * DH + (u - NKV - 2) * 32; bytes = 10240;
                    }
                } else {
                    map = i < 40 ? &maps.w1 : &maps.w3; c1 = qd * 6; c2 = (i < 40 ? i : i - 40) * 16;
                }
                const int depth = pace[1];
                const uint32_t slot = (uint32_t)i % NS, landed = i - depth;
                if (i >= NS) mbar_wait(bar_full + (NS + slot) * 8, ((uint32_t)i / NS - 1) & 1);
                mbar_expect_tx(bar_full + slot * 8, bytes);
                uint32_t dst = sb + SM_RING + slot * SLOT, fb = bar_full + slot * 8;
                asm volatile("" : "+r"(dst), "+r"(fb), "+l"(map), "+r"(c1), "+r"(c2));
                if (i >= depth) mbar_wait(bar_full + (landed % NS) * 8, (landed / NS) & 1);
                tma3d(dst, map, c1, c2, fb);
                pace[0] = landed + 1;
            }
            pace[0] = n_items - DEPTH;
        }
        return;
    }

    const int g = lane >> 2, t = lane & 3;
    uint32_t epoch;
    asm volatile("ld.relaxed.gpu.global.u32 %0, [%1];" : "=r"(epoch) : "l"(&g_sync.epoch) : "memory");

    if (warp == W_PACE) {
        const uint32_t tag = (epoch + 1u) & 1u;
        if (is_att) {
#pragma unroll
            for (int u = 0; u < WPS; u++) st_fill4(g_ml + ((sg * G + u * 16 + (lane >> 1)) * G + r) * MLS + (lane & 1) * 4, tag ^ 1u);
        }
        asm volatile("bar.sync 2, %0;" ::"n"(NTHR) : "memory");
        if (lane == 0) asm volatile("red.release.gpu.global.add.u32 [%0], 1;" ::"l"(&g_sync.inits) : "memory");
        if (!is_att) return;
        volatile int* pace = reinterpret_cast<volatile int*>(smem + SM_PACE);
        if (cta == 0 && lane == 0) asm volatile("st.relaxed.gpu.global.u32 [%0], %1;" ::"l"(&g_sync.prog[epoch & 1u]), "r"(0u) : "memory");
        int reported = 0, j = 0;
        bool due = false;
#pragma unroll 1
        for (unsigned it = 0;; it++) {
            const int landed = pace[0];
            int sum = 0;
            uint2 ml[WPS];
            uint32_t bad = 1u;
            unsigned n = (epoch + 1u) * NCTA;
            if (lane == 0 && reported < ITEMS_ATT - DEPTH)
                asm volatile("atom.relaxed.gpu.global.add.u32 %0, [%1], %2;"
                             : "=r"(sum) : "l"(&g_sync.prog[~epoch & 1u]), "r"(landed - reported) : "memory");
            if (due) {
#pragma unroll
                for (int u = 0; u < WPS; u++) {
                    const float* src = g_ml + (pair_of(sg, j * WPS + u) * G + lane % G) * MLS;
                    if (P_MLATOM) { if (lane < G) ml[u] = atom_word(src); else ml[u] = make_uint2(0xff000000u | tag, 0u); }
                    else ml[u] = ld_word(src);
                }
                if (j == 0) asm volatile("ld.acquire.gpu.global.u32 %0, [%1];" : "=r"(n) : "l"(&g_sync.inits) : "memory");
            }
            reported = landed;
            if (lane == 0 && P_GAIN) {
                const int avg16 = sum / (NATT / 16), lag16 = avg16 - landed * 16 + P_BIAS;
                pace[1] = avg16 >= ITEMS_ATT * 16 - P_FLUSH ? 8 : min(max(DEPTH + ((lag16 * P_GAIN + 128) >> 8), P_DMIN), P_DMAX);
            }
            if (due) {
                bad = 0;
#pragma unroll
                for (int u = 0; u < WPS; u++) bad |= ml[u].x ^ tag;
            }
            if (__all_sync(0xffffffffu, !(bad & 1u) && n == (epoch + 1u) * NCTA)) {
#pragma unroll
                for (int u = 0; u < WPS; u++) {
                    const float mk = __uint_as_float(ml[u].x & ~1u);
                    float M = mk;
#pragma unroll
                    for (int o = G / 2; o; o >>= 1) M = fmaxf(M, shx(M, o));
                    const float w = __expf(mk - M);
                    float L = w * __uint_as_float(ml[u].y);
#pragma unroll
                    for (int o = G / 2; o; o >>= 1) L += shx(L, o);
                    if (lane == r) reinterpret_cast<float*>(smem + SM_LS)[16 + (j & 3) * WPS + u] = __fdividef(w, L);
                }
                if (lane == r) {
                    mbar_arrive(bar_full + B_WRDY + (j & 3) * 8);
                    if (j == NSTEP - 1) TS(11);
                }
                j++;
                due = false;
            }
            if (j == NSTEP && landed >= ITEMS_ATT - DEPTH) return;
            if (P_MLWAIT == 1 && !due && j < NSTEP) due = mbar_test(bar_full + B_WTRIG + (j & 3) * 8, (j >> 2) & 1);
            if (landed < ITEMS_ATT - P_FAST) __nanosleep(P_SLEEP);
            if (P_MLWAIT == 0 && !due && j < NSTEP) due = mbar_test(bar_full + B_WTRIG + (j & 3) * 8, (j >> 2) & 1);
            if (it > SPIN_LIMIT) __trap();
        }
    }
    if (warp > W_PROD) {
        const uint32_t tag = (epoch + 1u) & 1u;
        const int e = tid - (W_PROD + 1) * 32;
        if (is_att) {
#pragma unroll 1
            for (int i = e; i < 192; i += NXW * 32)
                st_fill4(g_qpart + (cta * NB + i / 48) * VS + (i % 48) / 6 * 32 + (i % 6) * 4, tag ^ 1u);
            st_fill4(reinterpret_cast<float*>(ocell(cta, e)), 0u);
            if (e < 32) *reinterpret_cast<uint32_t*>(smem + SM_HF + e * 16 + 12) = 0u;
        } else {
#pragma unroll 1
            for (int c = e; c < 256; c += NXW * 32) {
                const bf16* xp = x + qd * DM + (c >> 6) * 160 + ((c >> 3) & 7) * 8 + (c & 3) * 2 + ((c >> 2) & 1);
                asm volatile("st.relaxed.gpu.global.v4.f32 [%0], {%1,%2,%3,%4};"
                             ::"l"(g_acc + (qd * 32 + (c >> 3)) * ACS + (c & 7)), "f"(__bfloat162float(xp[0])),
                               "f"(__bfloat162float(xp[64])), "f"((c & 32) ? 0.f : __bfloat162float(xp[128])), "f"(0.f) : "memory");
            }
        }
        asm volatile("bar.sync 2, %0;" ::"n"(NTHR) : "memory");
        if (!is_att) return;
        {
            const uint32_t eq = (e >> 5) * 24 + min(lane, 23), xw = eq / 6, xr = eq % 6;
            mbar_wait(bar_full + B_QTRIG, 0);
            if (e == 0) TS(10);
            settle(P_QDELAY);
#pragma unroll 1
            for (int j = 0; j < NSTEP; j++) {
                uint4 v[WPS][4];
                uint32_t bad;
                unsigned spin = 0;
                do {
#pragma unroll
                    for (int u = 0; u < WPS; u++) {
                        const int pair = pair_of(sg, j * WPS + u);
                        const float* src = g_qpart + ((pair >> 2) * 4 * NB + (pair & 3)) * VS + xw * 32 + xr * 4;
#pragma unroll
                        for (int k = 0; k < 4; k++) v[u][k] = ld_word2(src + k * NB * VS);
                    }
                    bad = 0;
#pragma unroll
                    for (int u = 0; u < WPS; u++)
#pragma unroll
                        for (int k = 0; k < 4; k++) bad |= (v[u][k].x ^ tag) | (v[u][k].z ^ tag);
                    if (++spin > SPIN_LIMIT) __trap();
                } while (bad & 1u);
#define SUM4(c) ((__uint_as_float(v[u][0].c) + __uint_as_float(v[u][1].c)) + (__uint_as_float(v[u][2].c) + __uint_as_float(v[u][3].c)))
#pragma unroll
                for (int u = 0; u < WPS; u++) {
                    unsigned char* dst = smem + SM_QS + (j * WPS + u) * (DH * 2) + (xr & 1) * 192 + ((xr >> 1) * 8 + xw) * 4;
                    *reinterpret_cast<uint32_t*>(dst) = pack_bf2(SUM4(x), SUM4(y));
                    *reinterpret_cast<uint32_t*>(dst + 96) = pack_bf2(SUM4(z), SUM4(w));
                }
#undef SUM4
                __syncwarp();
                if (lane == 0) mbar_arrive(bar_full + B_QRDY + j * 8);
                if (e == 0 && j == 0) TS(12);
            }
        }
        bool have_h = false;
#pragma unroll 1
        for (int b = 0; b <= NB; b++) {
            if (!have_h && (b == NB || order_of(r, b) >= HSTEP * WPS)) {
                have_h = true;
                mbar_wait(bar_full + B_HTRIG, 0);
#pragma unroll 1
                for (int i = e; i < 96; i += NXW * 32) {
                    const int k = (i % 24) * 2;
                    uint2 v;
                    unsigned spin = 0;
                    do {
                        v = ld_word(g_h + i / 24 * FF + h * 48 + k);
                        if (++spin > SPIN_LIMIT) __trap();
                    } while ((v.x ^ tag) & 1u);
                    *reinterpret_cast<uint32_t*>(smem + SM_HF + k / 24 * 256 + i / 24 * 64 + frag_off(k % 24)) = __byte_perm(v.x, v.y, 0x7632);
                }
                __syncwarp();
                if (lane == 0) mbar_arrive(bar_full + B_HRDY);
            }
            if (b == NB) break;
            const float4* src = ocell(h * NB + b, e);
            uint32_t dst = sb + SM_OF + (e >> 5) * 256 + b * 64 + frag_off(lane), ordy = bar_full + B_ORDY;
            asm volatile("" : "+r"(dst), "+l"(src), "+r"(ordy));
            mbar_wait(bar_full + B_OTRIG + b * 8, 0);
            const int pause = order_of(r, b) < G - P_URG * WPS ? P_SETTLE : P_SETTLE0;
            unsigned spin = 0;
            float o0, o1, o2, n;
            do {
                settle(pause);
                asm volatile("atom.relaxed.gpu.global.add.v4.f32 {%0,%1,%2,%3}, [%4], {%5,%5,%5,%5};"
                             : "=f"(o0), "=f"(o1), "=f"(o2), "=f"(n) : "l"(src), "f"(0.f) : "memory");
                asm volatile("st.shared.u16 [%0], %1;\nst.shared.u16 [%0+512], %2;\nst.shared.u16 [%0+1024], %3;"
                             ::"r"(dst), "h"(__bfloat16_as_ushort(__float2bfloat16_rn(o0))),
                               "h"(__bfloat16_as_ushort(__float2bfloat16_rn(o1))), "h"(__bfloat16_as_ushort(__float2bfloat16_rn(o2))) : "memory");
                if (++spin > SPIN_LIMIT) __trap();
            } while (n != (float)G);
            __syncwarp();
            if (lane == 0) mbar_arrive(ordy);
        }
        return;
    }

    if (warp < NB) {
        uint2 raw[5];
#pragma unroll
        for (int i = 0; i < 5; i++) raw[i] = __ldg(reinterpret_cast<const uint2*>(x + warp * DM) + i * 32 + lane);
        float s = 0.f;
#pragma unroll
        for (int i = 0; i < 5; i++) s += (bf_lo(raw[i].x) + bf_hi(raw[i].x)) + (bf_lo(raw[i].y) + bf_hi(raw[i].y));
#pragma unroll
        for (int o = 16; o; o >>= 1) s += shx(s, o);
        const float mean = s * (1.0f / DM);
        float q2 = 0.f;
#pragma unroll
        for (int i = 0; i < 5; i++) {
            const float d0 = bf_lo(raw[i].x) - mean, d1 = bf_hi(raw[i].x) - mean;
            const float d2 = bf_lo(raw[i].y) - mean, d3 = bf_hi(raw[i].y) - mean;
            q2 += (d0 * d0 + d1 * d1) + (d2 * d2 + d3 * d3);
        }
#pragma unroll
        for (int o = 16; o; o >>= 1) q2 += shx(q2, o);
        const float mb = bf_round(mean);
        const float rs = __frcp_rn(bf_round(__fsqrt_rn(bf_round(bf_round(q2 * (1.0f / DM)) + 1e-5f))));
        const uint32_t k = (lane * 4) & 31;
        unsigned char* dst = smem + SM_XF + warp * 64 +
            (is_att ? (lane >> 3) * 256 + frag_off(k) : (lane >> 2) * 256 + frag_off(k & 15));
        const uint32_t step = is_att ? 1024 : 2048;
#pragma unroll
        for (int i = 0; i < 5; i++) {
            const uint32_t d0 = pack_bf2(bf_lo(raw[i].x) - mb, bf_hi(raw[i].x) - mb);
            const uint32_t d1 = pack_bf2(bf_lo(raw[i].y) - mb, bf_hi(raw[i].y) - mb);
            *reinterpret_cast<uint32_t*>(dst + i * step) = pack_bf2(bf_lo(d0) * rs, bf_hi(d0) * rs);
            *reinterpret_cast<uint32_t*>(dst + i * step + 16) = pack_bf2(bf_lo(d1) * rs, bf_hi(d1) * rs);
        }
    }
    asm volatile("bar.sync 2, %0;" ::"n"(NTHR) : "memory");
    uint32_t tag = (epoch + 1u) & 1u;
    asm volatile("" : "+r"(tag));
    if (tid == 0) TS(3);

    Ring ring{bar_full, sb + SM_RING, 0u, bar_full};
    float lo[3][4] = {}, hi[3][4] = {};
    uint32_t off[3];
    const uint32_t a_lane = (g & 3) * 64 + t * 16;

    if (is_att) {
        float* lsum = reinterpret_cast<float*>(smem + SM_LS);
#pragma unroll 1
        for (int j = -1; j < NSTEP + LA; j++) {
            if (j >= 0 && j < NSTEP) {
                constexpr int WW = NCW / WPS;
                const int win = j * WPS + warp / WW;
                uint32_t qf[6][4];
                mbar_wait(bar_full + B_QRDY + j * 8, 0);
                if (j == 0 && tid == 0) TS(6);
#pragma unroll
                for (int i = 0; i < 6; i++) lds128(sb + SM_QS + win * (DH * 2) + t * 96 + i * 16, qf[i]);
                const uint32_t key = (warp & 1) * 16 + (lane & 15);
                const uint32_t item = 5 + (j + max(j - LA, 0)) * 4 + (warp >> 1), slot = item % NS;
#pragma unroll
                for (int s = 0; s < 3; s++)
                    off[s] = sb + SM_RING + slot * SLOT + key * 384 + s * 128 + (((lane >> 4) ^ ((3 * key + s) & 7)) << 4);
                pin3(off);
                mbar_wait(bar_full + slot * 8, (item / NS) & 1);
                float c[3][4] = {};
#pragma unroll
                for (int dq = 0; dq < 4; dq++)
#pragma unroll
                    for (int s = 0; s < 3; s++) {
                        uint32_t a[4];
                        ldsm_x4(off[s] ^ (dq << 5), a);
                        mma16816(c[s], a, qf[s * 2 + (dq >> 1)][(dq & 1) * 2], qf[s * 2 + (dq >> 1)][(dq & 1) * 2 + 1]);
                    }
                __syncwarp();
                if (lane == 0)
                    asm volatile("mbarrier.arrive.shared::cta.b64 _, [%0], %1;" ::"r"(bar_full + (NS + slot) * 8), "n"(NCW / 2) : "memory");
                ring.skip(4);
                const float raw = (t & 1) ? (c[0][2] + c[1][2]) + c[2][2] : (c[0][0] + c[1][0]) + c[2][0];
                const float sv = bf_round(bf_round(raw) * 0.07216878364870323f);
                if (tid == 0 && j == NSTEP - 1) TS(14);
                float m = fmaxf(sv, shx(sv, 1));
#pragma unroll
                for (int o = 4; o < 32; o <<= 1) m = fmaxf(m, shx(m, o));
                if (lane == 0) lsum[8 + warp] = m;
                cons_bar();
#pragma unroll
                for (int i = 0; i < WW / 4; i++) {
                    const float4 m4 = reinterpret_cast<const float4*>(lsum)[2 + warp / WW * (WW / 4) + i];
                    m = fmaxf(m, fmaxf(fmaxf(m4.x, m4.y), fmaxf(m4.z, m4.w)));
                }
                float l = __expf(sv - m);
                *reinterpret_cast<bf16*>(smem + SM_PF + ((j & 3) * 4 + (warp >> 1)) * 64 + frag_off((warp & 1) * 16 + (t & 1) * 8 + g)) =
                    __float2bfloat16_rn(l);
                l += shx(l, 1);
#pragma unroll
                for (int o = 4; o < 32; o <<= 1) l += shx(l, o);
                if (lane == 0) lsum[warp] = l;
                cons_bar();
                if (tid % (WW * 32) < 4) {
                    l = 0.f;
#pragma unroll
                    for (int i = 0; i < WW / 4; i++) {
                        const float4 l4 = reinterpret_cast<const float4*>(lsum)[warp / 4 + i];
                        l += (l4.x + l4.y) + (l4.z + l4.w);
                    }
                    st_tag2(g_ml + (pair_of(sg, win) * G + r) * MLS + lane * 2, m, l, tag);
                    if (tid == 0) {
                        mbar_arrive(bar_full + B_WTRIG + (j & 3) * 8);
                        if (j == HSTEP) mbar_arrive(bar_full + B_HTRIG);
                    }
                }
                if (tid == 0 && j == NSTEP - 1) TS(13);
                if (j < LA) continue;
            }
            const bool kv = j >= 0;
            const uint32_t jv = j - LA;
#pragma unroll
            for (int s = 0; s < 3; s++) off[s] = lane * 384 + s * 128 + ((warp ^ ((3 * lane + s) & 7)) << 4);
#pragma unroll 1
            for (int u = 0; u < (kv ? WPS : 1); u++) {
                const int pair = pair_of(sg, jv * WPS + u);
                uint32_t trig = !kv ? bar_full + B_QTRIG : (pair >> 2) == h ? bar_full + B_OTRIG + (pair & 3) * 8 : 0;
                if (tid != 0) trig = 0;
                float4* oacc = ocell(pair, warp * 8 + 2 * t + (g & 1));
                uint32_t wrdy = bar_full + B_WRDY + (jv & 3) * 8;
                asm volatile("" : "+l"(oacc), "+r"(trig), "+r"(wrdy));
                gemv_loop(ring, kv ? NT : 5,
                          kv ? sb + SM_PF + ((jv & 3) * 4 + u * NT) * 64 + t * 16 : sb + SM_XF + qd * 5 * 256 + a_lane,
                          kv ? 64 : 256, off, lo, hi, lane);
                if (kv) {
                    mbar_wait(wrdy, (jv >> 2) & 1);
                    const float w = lsum[16 + (jv & 3) * WPS + u];
                    if (g < 2)
                        asm volatile("red.relaxed.gpu.global.add.v4.f32 [%0], {%1,%2,%3,%4};"
                                     ::"l"(oacc), "f"(w * (g ? lo[0][1] + hi[0][3] : lo[0][0] + hi[0][2])),
                                       "f"(w * (g ? lo[1][1] + hi[1][3] : lo[1][0] + hi[1][2])),
                                       "f"(w * (g ? lo[2][1] + hi[2][3] : lo[2][0] + hi[2][2])), "f"(1.0f) : "memory");
                } else if (g < NB) {
#pragma unroll
                    for (int s = 0; s < 3; s++)
                        st_tag2(g_qpart + (cta * NB + g) * VS + warp * 32 + 2 * t + s * 8, lo[s][0] + hi[s][2], lo[s][1] + hi[s][3], tag);
                }
                if (trig) mbar_arrive(trig);
            }
            const bool pass = j == NSTEP + LA - 1;
            if (pass && tid == 0) TS(5);
            if (kv && !pass && j != P_DRY) continue;
            if (tid == 0 && j < 0) TS(4);

            {
                constexpr int I0 = 5 + NKV;
                static_assert(((I0 / NS) & 1) == 0 && I0 / NS == (I0 + 7) / NS, "tail items complete an even phase");
                const uint32_t done = bar_full + B_QTRIG;
                uint32_t fb = pass ? bar_full + (I0 % NS) * 8 : done, fs = pass ? 8 : 0, ordy = pass ? bar_full + B_ORDY : done;
                uint32_t off2[3], a[8][4], b[8][3][4], a_addr = sb + SM_HF + a_lane;
#pragma unroll
                for (int s = 0; s < 3; s++) {
                    const uint32_t w64 = lane * 320 + (warp + 8 * s) * 16;
                    off[s] = sb + SM_RING + (I0 % NS) * SLOT + (w64 ^ (((w64 >> 7) & 3) << 4));
                    off2[s] = lane < 24 ? off[s] : off[s] - 8 * 320;
#pragma unroll
                    for (int e = 0; e < 4; e++) { lo[s][e] = 0.f; hi[s][e] = 0.f; }
                }
                const float4* accp = g_acc + (((g & 3) * 4 + qd) * NCW + warp) * ACS + (g >> 2) * 4 + t;
                bf16* outp = out + (g & 3) * DM + qd * 160 + warp * 8 + 2 * t + (g >> 2);
                pin3(off);
                asm volatile("" : "+l"(accp), "+l"(outp), "+r"(a_addr), "+r"(ordy), "+r"(fb), "+r"(fs));
                auto load_b = [&](int i, bool& next) {
                    if (!next) mbar_wait(fb + i * fs, 0);
                    if (i < 7) next = mbar_test(fb + (i + 1) * fs, 0);
#pragma unroll
                    for (int s = 0; s < 3; s++)
                        if (s < 2 || warp < 4) ldsm_x4_t((i < 2 ? off2[s] : off[s]) + i * SLOT, b[i][s]);
                };
                auto mul = [&](int i) {
#pragma unroll
                    for (int s = 0; s < 3; s++)
                        if (s < 2 || warp < 4) { mma16816(lo[s], a[i], b[i][s][0], b[i][s][1]); mma16816(hi[s], a[i], b[i][s][2], b[i][s][3]); }
                };
                bool next = mbar_test(fb, 0);
                mbar_wait(pass ? bar_full + B_HRDY : done, 0);
                lds128(a_addr, a[0]);
                lds128(a_addr + 256, a[1]);
                load_b(0, next);
                load_b(1, next);
                bool early = mbar_test(ordy, 0);
                mul(0);
                mul(1);
                if (pass && tid == 0) TS(31);
                unsigned spin = 0;
                while (!early && !mbar_test(fb + P_DEC * fs, 0)) {
                    early = mbar_test(ordy, 0);
                    if (++spin > SPIN_LIMIT) __trap();
                }
                if (pass ? __all_sync(0xffffffffu, early) : j < 0) {
                    if (pass && tid == 0) TS(7);
#pragma unroll
                    for (int i = 2; i < 8; i++) lds128(a_addr + i * 256, a[i]);
                    load_b(2, next);
#pragma unroll
                    for (int i = 2; i < 7; i++) { load_b(i + 1, next); mul(i); }
                    mul(7);
                } else {
#pragma unroll
                    for (int i = 2; i < 8; i++) load_b(i, next);
                    mbar_wait(ordy, 0);
                    if (pass && tid == 0) TS(7);
#pragma unroll
                    for (int i = 2; i < 8; i++) lds128(a_addr + i * 256, a[i]);
#pragma unroll
                    for (int i = 2; i < 8; i++) mul(i);
                }
                if (pass && tid == 0) TS(8);
                add_out(accp, outp, lo, hi, g >= NB, warp < 4, pass, epoch);
            }
        }
        if (tid == 0) { TS(9); TS_DUMP(3, 32); }
    } else {
        float gate[6][2];
#pragma unroll
        for (int s = 0; s < 3; s++) {
            const uint32_t r128 = (lane & 15) * 6 + 2 * s + (lane >> 4);
            off[s] = r128 * 128 + ((warp ^ (r128 & 7)) << 4);
        }
#pragma unroll 1
        for (int ps = 0; ps < 2; ps++) {
#pragma unroll
            for (int s = 0; s < 3; s++) {
                gate[2 * s][0] = lo[s][0]; gate[2 * s][1] = lo[s][1];
                gate[2 * s + 1][0] = hi[s][0]; gate[2 * s + 1][1] = hi[s][1];
            }
            gemv_loop(ring, 40, sb + SM_XF + a_lane, 256, off, lo, hi, lane);
        }
#pragma unroll
        for (int p = 0; p < 6; p++) {
            float hv[2];
#pragma unroll
            for (int e = 0; e < 2; e++) {
                const float gt = bf_round(gate[p][e]);
                hv[e] = bf_round(bf_round(__fdividef(gt, 1.0f + __expf(-gt))) * bf_round((p & 1) ? hi[p >> 1][e] : lo[p >> 1][e]));
            }
            if (g < NB) st_tag2(g_h + g * FF + qd * 384 + p * 64 + warp * 8 + 2 * t, hv[0], hv[1], tag);
        }
        if (tid == 0) { TS(9); TS_DUMP(3, 10); }
    }
}

typedef CUresult (*EncodeFn)(CUtensorMap*, CUtensorMapDataType, cuuint32_t, void*, const cuuint64_t*, const cuuint64_t*,
                             const cuuint32_t*, const cuuint32_t*, CUtensorMapInterleave, CUtensorMapSwizzle,
                             CUtensorMapL2promotion, CUtensorMapFloatOOBfill);

void make_map(EncodeFn enc, CUtensorMap* m, const void* p, uint64_t rows, uint64_t cols, uint32_t inner, uint32_t parts,
              uint32_t box_rows) {
    const cuuint64_t dims[3] = {inner, cols / inner, rows};
    const cuuint64_t strides[2] = {inner * 2ull, cols * 2ull};
    const cuuint32_t box[3] = {inner, parts, box_rows};
    const cuuint32_t es[3] = {1, 1, 1};
    enc(m, CU_TENSOR_MAP_DATA_TYPE_BFLOAT16, 3, const_cast<void*>(p), dims, strides, box, es, CU_TENSOR_MAP_INTERLEAVE_NONE,
        inner == 64 ? CU_TENSOR_MAP_SWIZZLE_128B : CU_TENSOR_MAP_SWIZZLE_64B, CU_TENSOR_MAP_L2_PROMOTION_NONE,
        CU_TENSOR_MAP_FLOAT_OOB_FILL_NONE);
}

}

extern "C" void kernel_launch(void* const* d_in, const int* in_sizes, int n_in, void* d_out, int out_size) {
    (void)in_sizes; (void)n_in; (void)out_size;
    static EncodeFn enc = nullptr;
    if (!enc) {
        void* fn = nullptr;
        cudaDriverEntryPointQueryResult qr;
        cudaGetDriverEntryPoint("cuTensorMapEncodeTiled", &fn, cudaEnableDefault, &qr);
        enc = (EncodeFn)fn;
        cudaFuncSetAttribute(fused_decode_kernel, cudaFuncAttributeMaxDynamicSharedMemorySize, SM_TOTAL);
    }
    Maps maps;
    make_map(enc, &maps.k, d_in[1], (uint64_t)NB * NH * SK, DH, 64, 3, TK);
    make_map(enc, &maps.v, d_in[2], (uint64_t)NB * NH * SK, DH, 64, 3, TK);
    make_map(enc, &maps.wq, d_in[3], DM, NH * DH, 64, 3, 32);
    make_map(enc, &maps.wo, d_in[4], NH * DH, DM, 32, 5, 32);
    make_map(enc, &maps.w1, d_in[6], DM, FF, 64, 6, 16);
    make_map(enc, &maps.w3, d_in[7], DM, FF, 64, 6, 16);
    make_map(enc, &maps.w2, d_in[8], FF, DM, 32, 5, 24);
    fused_decode_kernel<<<NCTA, NTHR, SM_TOTAL>>>(maps, (const bf16*)d_in[0], (bf16*)d_out);
}
```

```cpp
#include <cuda_runtime.h>
#include <cuda.h>
#include <cuda_bf16.h>
#include <stdint.h>

namespace {

typedef __nv_bfloat16 bf16;

constexpr int NB = 4, DM = 640, NH = 32, DH = 192, SK = 8192, WIN = 2048, FF = 1536;

#define P_G 32
#define P_DEPTH 4
#define P_DEPTH_FFN 5
#define P_GAIN 6
#define P_BIAS 16
#define P_SLEEP 500
#define P_DMIN 3
#define P_DMAX 6
#define P_SETTLE 3000
#define P_QDELAY 1600
#define P_DRY 4
#define P_DEC 6
#define P_LA 2
#define P_MLS 8
#define P_OAL 72
#define P_NS 16

constexpr int G = P_G;
constexpr int TK = 32;
constexpr int NT = WIN / TK / G;
constexpr int NSTEP = 16;
constexpr int WPS = G / NSTEP;
constexpr int LA = P_LA;
constexpr int MLS = P_MLS;
constexpr int OAL = P_OAL;
constexpr int HSTEP = 11;
constexpr int NS = P_NS;
constexpr int SLOT = 12288;
constexpr int DEPTH = P_DEPTH;
#define P_D0 5
constexpr int DEPTH0 = P_D0;
static_assert(DEPTH0 <= 5, "DEPTH0");
constexpr int NATT = 128, NFFN = 4, NCTA = NATT + NFFN;
constexpr int NCW = 8;
constexpr int NXW = 2;
constexpr int W_PROD = NCW, W_PACE = NCW + 1 + NXW;
constexpr int NTHR = (W_PACE + 1) * 32;
constexpr int NSRC = NH;
constexpr int VS = 256;
#define P_ACS 40
constexpr int ACS = P_ACS;
static_assert(G == 16 || G == 32 || G == 64, "G");

constexpr int SM_RING = 0;
constexpr int SM_XF = SM_RING + NS * SLOT;
constexpr int SM_QS = SM_XF + 20 * 256;
constexpr int SM_PF = SM_QS + G * DH * 2;
constexpr int SM_HF = SM_PF + 4 * 4 * 64;
constexpr int SM_OF = SM_HF + 2 * 256;
constexpr int SM_LS = SM_OF + 6 * 256;
constexpr int SM_ATT_END = SM_LS + 128;
constexpr int SM_FFN_END = SM_XF + 40 * 256;
constexpr int SM_BAR = SM_ATT_END > SM_FFN_END ? SM_ATT_END : SM_FFN_END;
constexpr int B_QRDY = 2 * NS * 8, B_ORDY = B_QRDY + NSTEP * 8, B_OTRIG = B_ORDY + 8, B_QTRIG = B_OTRIG + 32,
              B_WTRIG = B_QTRIG + 8, B_WRDY = B_WTRIG + 32, B_HTRIG = B_WRDY + 32, B_HRDY = B_HTRIG + 8,
              NBAR = 2 * NS + NSTEP + 16;
constexpr int SM_PACE = SM_BAR + NBAR * 8;
constexpr int SM_TS = SM_PACE + 8;
constexpr int SM_TOTAL = SM_TS + 256;
static_assert(SM_TOTAL <= 232448, "smem");

constexpr int NKV = 2 * NT * G;
constexpr int ITEMS_ATT = 5 + NKV + 2 + 6;
constexpr int ITEMS_FFN = 80;

struct Maps { CUtensorMap k, v, wq, wo, w1, w3, w2; };

struct alignas(32) Sync { unsigned epoch, inits, prog[2]; };
__device__ Sync g_sync;
__device__ __align__(128) float g_qpart[NATT * NB * VS];
__device__ __align__(128) float g_ml[NATT * G * MLS];
__device__ __align__(128) float g_h[NB * FF];
__device__ __align__(128) float4 g_oacc[NATT * 8 * OAL];
__device__ __align__(128) float4 g_acc[NB * 4 * NCW * ACS];
#define TS(i)
#define TS_DUMP(lo, hi)

constexpr unsigned SPIN_LIMIT = 1u << 22;

__device__ __forceinline__ void mbar_init(uint32_t bar, int cnt) {
    asm volatile("mbarrier.init.shared::cta.b64 [%0], %1;" ::"r"(bar), "r"(cnt) : "memory");
}
__device__ __forceinline__ void mbar_expect_tx(uint32_t bar, uint32_t bytes) {
    asm volatile("mbarrier.arrive.expect_tx.shared::cta.b64 _, [%0], %1;" ::"r"(bar), "r"(bytes) : "memory");
}
__device__ __forceinline__ void mbar_arrive(uint32_t bar) {
    asm volatile("mbarrier.arrive.shared::cta.b64 _, [%0];" ::"r"(bar) : "memory");
}
__device__ __forceinline__ void mbar_wait(uint32_t bar, uint32_t parity) {
    asm volatile("{\n.reg .pred p, q;\n.reg .u32 n;\nmov.u32 n, 0;\n"
                 "W: mbarrier.try_wait.parity.shared::cta.b64 p, [%0], %1;\n"
                 "@p bra D;\nadd.u32 n, n, 1;\nsetp.lt.u32 q, n, %2;\n@q bra W;\ntrap;\nD:\n}"
                 ::"r"(bar), "r"(parity), "n"(SPIN_LIMIT) : "memory");
}
__device__ __forceinline__ bool mbar_test(uint32_t bar, uint32_t parity) {
    uint32_t ok;
    asm volatile("{\n.reg .pred p;\nmbarrier.test_wait.parity.shared::cta.b64 p, [%1], %2;\nselp.u32 %0, 1, 0, p;\n}"
                 : "=r"(ok) : "r"(bar), "r"(parity) : "memory");
    return ok;
}
__device__ __forceinline__ void tma3d(uint32_t dst, const CUtensorMap* map, int c1, int c2, uint32_t bar) {
    const uint64_t pol = 0x12F0000000000000ull;
    asm volatile("cp.async.bulk.tensor.3d.shared::cluster.global.mbarrier::complete_tx::bytes.L2::cache_hint "
                 "[%0], [%1, {%2, %3, %4}], [%5], %6;"
                 ::"r"(dst), "l"(map), "r"(0), "r"(c1), "r"(c2), "r"(bar), "l"(pol) : "memory");
}
__device__ __forceinline__ void ldsm_x4(uint32_t addr, uint32_t (&r)[4]) {
    asm volatile("ldmatrix.sync.aligned.m8n8.x4.shared.b16 {%0,%1,%2,%3}, [%4];"
                 : "=r"(r[0]), "=r"(r[1]), "=r"(r[2]), "=r"(r[3]) : "r"(addr) : "memory");
}
__device__ __forceinline__ void ldsm_x4_t(uint32_t addr, uint32_t (&r)[4]) {
    asm volatile("ldmatrix.sync.aligned.m8n8.x4.trans.shared.b16 {%0,%1,%2,%3}, [%4];"
                 : "=r"(r[0]), "=r"(r[1]), "=r"(r[2]), "=r"(r[3]) : "r"(addr) : "memory");
}
__device__ __forceinline__ void lds128(uint32_t addr, uint32_t (&r)[4]) {
    asm volatile("ld.shared.v4.u32 {%0,%1,%2,%3}, [%4];"
                 : "=r"(r[0]), "=r"(r[1]), "=r"(r[2]), "=r"(r[3]) : "r"(addr) : "memory");
}
__device__ __forceinline__ void mma16816(float (&c)[4], const uint32_t (&a)[4], uint32_t b0, uint32_t b1) {
    asm volatile("mma.sync.aligned.m16n8k16.row.col.f32.bf16.bf16.f32 {%0,%1,%2,%3}, {%4,%5,%6,%7}, {%8,%9}, {%0,%1,%2,%3};"
                 : "+f"(c[0]), "+f"(c[1]), "+f"(c[2]), "+f"(c[3])
                 : "r"(a[0]), "r"(a[1]), "r"(a[2]), "r"(a[3]), "r"(b0), "r"(b1));
}
__device__ __forceinline__ void cons_bar() { asm volatile("bar.sync 1, 256;" ::: "memory"); }

__device__ __forceinline__ float bf_round(float v) { return __bfloat162float(__float2bfloat16_rn(v)); }
__device__ __forceinline__ uint32_t pack_bf2(float lo, float hi) {
    __nv_bfloat162 t = __floats2bfloat162_rn(lo, hi);
    return *reinterpret_cast<uint32_t*>(&t);
}
__device__ __forceinline__ float bf_lo(uint32_t u) { return __uint_as_float(u << 16); }
__device__ __forceinline__ float bf_hi(uint32_t u) { return __uint_as_float(u & 0xffff0000u); }
__device__ __forceinline__ float shx(float v, int o) { return __shfl_xor_sync(0xffffffffu, v, o); }

__device__ __forceinline__ uint32_t frag_off(uint32_t k) {
    return ((k >> 1) & 3) * 16 + ((k >> 3) & 1) * 8 + ((k >> 4) & 1) * 4 + (k & 1) * 2;
}

__device__ __forceinline__ void st_tag2(float* p, float a, float b, uint32_t tag) {
    asm volatile("{\n.reg .b64 w;\n.reg .b32 x;\nlop3.b32 x, %1, 0xfffffffe, %3, 0xea;\nmov.b64 w, {x, %2};\n"
                 "st.relaxed.gpu.global.b64 [%0], w;\n}"
                 ::"l"(p), "r"(__float_as_uint(a)), "r"(__float_as_uint(b)), "r"(tag) : "memory");
}
__device__ __forceinline__ void st_fill4(float* p, uint32_t v) {
    asm volatile("{\n.reg .b64 w;\nmov.b64 w, {%1, %1};\nst.relaxed.gpu.global.v2.b64 [%0], {w, w};\n}" ::"l"(p), "r"(v) : "memory");
}
__device__ __forceinline__ uint2 ld_word(const float* p) {
    uint2 v;
    asm volatile("{\n.reg .b64 w;\nld.relaxed.gpu.global.b64 w, [%2];\nmov.b64 {%0,%1}, w;\n}" : "=r"(v.x), "=r"(v.y) : "l"(p) : "memory");
    return v;
}
__device__ __forceinline__ uint4 ld_word2(const float* p) {
    uint4 v;
    asm volatile("{\n.reg .b64 w0, w1;\nld.relaxed.gpu.global.v2.b64 {w0, w1}, [%4];\nmov.b64 {%0,%1}, w0;\nmov.b64 {%2,%3}, w1;\n}"
                 : "=r"(v.x), "=r"(v.y), "=r"(v.z), "=r"(v.w) : "l"(p) : "memory");
    return v;
}

__device__ __forceinline__ void add_out(const float4* acc, bf16* out, const float (&lo)[3][4], const float (&hi)[3][4],
                                        bool odd, bool third, bool live, uint32_t epoch) {
    const float v0 = odd ? lo[0][1] + hi[0][3] : lo[0][0] + hi[0][2];
    const float v1 = odd ? lo[1][1] + hi[1][3] : lo[1][0] + hi[1][2];
    const float v2 = odd ? lo[2][1] + hi[2][3] : lo[2][0] + hi[2][2];
    float o0, o1, o2, n = 0.f;
    asm volatile("{\n.reg .pred p;\nsetp.ne.u32 p, %5, 0;\n"
                 "@p atom.relaxed.gpu.global.add.v4.f32 {%0,%1,%2,%3}, [%4], {%6,%7,%8,%9};\n}"
                 : "=f"(o0), "=f"(o1), "=f"(o2), "+f"(n)
                 : "l"(acc), "r"((uint32_t)live), "f"(v0), "f"(v1), "f"(v2), "f"(1.0f) : "memory");
    asm volatile("{\n.reg .pred p, q;\nsetp.eq.f32 p, %4, %5;\nsetp.ne.and.u32 q, %6, 0, p;\n"
                 "@p st.global.u16 [%0], %1;\n@p st.global.u16 [%0+128], %2;\n@q st.global.u16 [%0+256], %3;\n}"
                 ::"l"(out), "h"(__bfloat16_as_ushort(__float2bfloat16_rn(o0 + v0))),
                   "h"(__bfloat16_as_ushort(__float2bfloat16_rn(o1 + v1))), "h"(__bfloat16_as_ushort(__float2bfloat16_rn(o2 + v2))),
                   "f"(n), "f"((float)(NSRC - 1)), "r"((uint32_t)third) : "memory");
    if (acc == g_acc && n == (float)(NSRC - 1))
        asm volatile("st.relaxed.gpu.global.u32 [%0], %1;" ::"l"(&g_sync.epoch), "r"(epoch + 1u) : "memory");
}

__device__ __forceinline__ int pair_of(int sg, uint32_t j) { return sg * G + (j % (G / 4)) * 4 + j / (G / 4); }
__device__ __forceinline__ int order_of(int r, int b) { return b * (G / 4) + (r >> 2); }

__device__ __forceinline__ float4* ocell(uint32_t pair, uint32_t i) {
    return g_oacc + (pair * 8 + (i >> 3)) * OAL + (i & 7);
}

__device__ __forceinline__ void settle(int cycles) {
    const uint32_t t0 = (uint32_t)clock();
    while ((uint32_t)clock() - t0 < (uint32_t)cycles) __nanosleep(20);
}

struct Ring {
    uint32_t full, addr, phase, first_full;
    __device__ __forceinline__ void wait() const { mbar_wait(full, phase); }
    __device__ __forceinline__ void skip(int n) {
        full += n * 8; addr += n * SLOT;
        if (full >= first_full + NS * 8) { full -= NS * 8; addr -= NS * SLOT; phase ^= 1; }
    }
    __device__ __forceinline__ void release(int lane) {
        __syncwarp();
        if (lane == 0) mbar_arrive(full + NS * 8);
        full += 8; addr += SLOT;
        if (full == first_full + NS * 8) { full = first_full; addr -= NS * SLOT; phase ^= 1; }
    }
};

__device__ __forceinline__ void pin3(uint32_t (&v)[3]) {
    asm volatile("" : "+r"(v[0]), "+r"(v[1]), "+r"(v[2]));
}
__device__ __forceinline__ void gemv_loop(Ring& ring, int n, uint32_t a_addr, uint32_t a_step, uint32_t (&off)[3],
                                          float (&lo)[3][4], float (&hi)[3][4], int lane) {
    pin3(off);
#pragma unroll
    for (int s = 0; s < 3; s++)
#pragma unroll
        for (int e = 0; e < 4; e++) { lo[s][e] = 0.f; hi[s][e] = 0.f; }
#pragma unroll 1
    for (int it = 0; it < n; it++) {
        uint32_t a[4], b[3][4];
        lds128(a_addr, a);
        a_addr += a_step;
        ring.wait();
#pragma unroll
        for (int s = 0; s < 3; s++) ldsm_x4_t(ring.addr + off[s], b[s]);
#pragma unroll
        for (int s = 0; s < 3; s++) { mma16816(lo[s], a, b[s][0], b[s][1]); mma16816(hi[s], a, b[s][2], b[s][3]); }
        ring.release(lane);
    }
}

__global__ void __launch_bounds__(NTHR, 1)
fused_decode_kernel(const __grid_constant__ Maps maps, const bf16* __restrict__ x, bf16* __restrict__ out) {
    extern __shared__ __align__(1024) unsigned char smem[];
    const uint32_t sb = (uint32_t)__cvta_generic_to_shared(smem);
    const uint32_t bar_full = sb + SM_BAR;
    if (threadIdx.x == 0 && blockIdx.x < NATT) {
        TS(0);
#pragma unroll 1
        for (int i = 0; i < DEPTH0; i++) {
            mbar_init(bar_full + i * 8, 1);
            mbar_expect_tx(bar_full + i * 8, 12288);
            tma3d(sb + SM_RING + i * SLOT, &maps.wq, (blockIdx.x >> 2) * 3, (blockIdx.x & 3) * 160 + i * 32, bar_full + i * 8);
        }
        TS(1);
    }
    unsigned ptid, cta;
    asm volatile("mov.u32 %0, %%tid.x;\nmov.u32 %1, %%ctaid.x;" : "=r"(ptid), "=r"(cta));
    const int tid = ptid < 32 ? ptid + NCW * 32 : ptid < (NCW + 1) * 32 ? ptid - 32 : ptid;
    const int warp = tid >> 5, lane = tid & 31;
    const bool is_att = cta < NATT;
    const int h = cta >> 2, qd = cta & 3;
    const int sg = cta / G, r = cta % G;

    if (warp == NCW) {
        volatile int* pace = reinterpret_cast<volatile int*>(smem + SM_PACE);
        if (lane == 0) {
            if (!is_att) { TS(0); TS(1); }
            pace[0] = 0;
            pace[1] = is_att ? DEPTH : P_DEPTH_FFN;
#pragma unroll
            for (int i = 0; i < NBAR; i++)
                if (i >= DEPTH0 || !is_att)
                mbar_init(bar_full + i * 8, i < NS ? 1 : i < 2 * NS ? NCW : i < 2 * NS + NSTEP ? NXW : i == 2 * NS + NSTEP ? NXW * NB : i == NBAR - 1 ? NXW : 1);
            asm volatile("fence.mbarrier_init.release.cluster;" ::: "memory");
        }
        __syncwarp();
        asm volatile("bar.arrive 2, %0;" ::"n"(NTHR) : "memory");
        if (lane == 0) {
            const int n_items = is_att ? ITEMS_ATT : ITEMS_FFN;

            asm volatile("prefetch.tensormap [%0];" ::"l"(is_att ? &maps.k : &maps.w3) : "memory");
            asm volatile("prefetch.tensormap [%0];" ::"l"(&maps.v) : "memory");
            asm volatile("prefetch.tensormap [%0];" ::"l"(&maps.w2) : "memory");
            asm volatile("prefetch.tensormap [%0];" ::"l"(&maps.wo) : "memory");
#pragma unroll 1
            for (int i = is_att ? DEPTH0 : 0; i < n_items; i++) {
                const CUtensorMap* map;
                int c1, c2;
                uint32_t bytes = 12288;
                if (is_att) {
                    const uint32_t u = i - 5;
                    if (u < NKV) {
                        const uint32_t blk = u / 4;
                        const bool isv = blk >= 2 * NSTEP - LA || (blk >= LA && ((blk - LA) & 1));
                        const uint32_t step = blk < LA ? blk : blk >= 2 * NSTEP - LA ? blk - NSTEP : (blk - LA) / 2 + (isv ? 0 : LA);
                        const int pair = pair_of(sg, step * WPS + (u % 4) / NT);
                        map = isv ? &maps.v : &maps.k;
                        c1 = 0;
                        c2 = ((pair & 3) * NH + (pair >> 2)) * SK + (SK - WIN) + ((u % NT) * G + r) * TK;
                    } else if (i < 5) {
                        map = &maps.wq; c1 = h * 3; c2 = qd * 160 + i * 32;
                    } else if (u < NKV + 2) {
                        map = &maps.w2; c1 = qd * 5; c2 = h * 48 + (u - NKV) * 24; bytes = 7680;
                    } else {
                        map = &maps.wo; c1 = qd * 5; c2 = h * DH + (u - NKV - 2) * 32; bytes = 10240;
                    }
                } else {
                    map = i < 40 ? &maps.w1 : &maps.w3; c1 = qd * 6; c2 = (i < 40 ? i : i - 40) * 16;
                }
                const int depth = pace[1];
                const uint32_t slot = (uint32_t)i % NS, landed = i - depth;
                if (i >= NS) mbar_wait(bar_full + (NS + slot) * 8, ((uint32_t)i / NS - 1) & 1);
                mbar_expect_tx(bar_full + slot * 8, bytes);
                uint32_t dst = sb + SM_RING + slot * SLOT, fb = bar_full + slot * 8;
                asm volatile("" : "+r"(dst), "+r"(fb), "+l"(map), "+r"(c1), "+r"(c2));
                if (i >= depth) mbar_wait(bar_full + (landed % NS) * 8, (landed / NS) & 1);
                tma3d(dst, map, c1, c2, fb);
                pace[0] = landed + 1;
            }
            pace[0] = n_items - DEPTH;
        }
        return;
    }

    const int g = lane >> 2, t = lane & 3;
    uint32_t epoch;
    asm volatile("ld.relaxed.gpu.global.u32 %0, [%1];" : "=r"(epoch) : "l"(&g_sync.epoch) : "memory");

    if (warp == W_PACE) {
        const uint32_t tag = (epoch + 1u) & 1u;
        if (is_att) {
#pragma unroll
            for (int u = 0; u < WPS; u++) st_fill4(g_ml + ((sg * G + u * 16 + (lane >> 1)) * G + r) * MLS + (lane & 1) * 4, tag ^ 1u);
        }
        asm volatile("bar.sync 2, %0;" ::"n"(NTHR) : "memory");
        if (lane == 0) asm volatile("red.release.gpu.global.add.u32 [%0], 1;" ::"l"(&g_sync.inits) : "memory");
        if (!is_att) return;
        volatile int* pace = reinterpret_cast<volatile int*>(smem + SM_PACE);
        if (cta == 0 && lane == 0) asm volatile("st.relaxed.gpu.global.u32 [%0], %1;" ::"l"(&g_sync.prog[epoch & 1u]), "r"(0u) : "memory");
        int reported = 0, j = 0;
        bool due = false;
#pragma unroll 1
        for (unsigned it = 0;; it++) {
            const int landed = pace[0];
            int sum = 0;
            constexpr int RPL = (G + 31) / 32;
            uint2 ml[WPS][RPL];
            uint32_t bad = 1u;
            unsigned n = (epoch + 1u) * NCTA;
            if (lane == 0 && reported < ITEMS_ATT - DEPTH)
                asm volatile("atom.relaxed.gpu.global.add.u32 %0, [%1], %2;"
                             : "=r"(sum) : "l"(&g_sync.prog[~epoch & 1u]), "r"(landed - reported) : "memory");
            if (due) {
#pragma unroll
                for (int u = 0; u < WPS; u++)
#pragma unroll
                    for (int k = 0; k < RPL; k++) ml[u][k] = ld_word(g_ml + (pair_of(sg, j * WPS + u) * G + k * 32 + lane % G) * MLS);
                if (j == 0) asm volatile("ld.acquire.gpu.global.u32 %0, [%1];" : "=r"(n) : "l"(&g_sync.inits) : "memory");
            }
            reported = landed;
            if (lane == 0 && P_GAIN) {
                const int lag16 = sum / (NATT / 16) - landed * 16 + P_BIAS;
                pace[1] = min(max(DEPTH + ((lag16 * P_GAIN + 128) >> 8), P_DMIN), P_DMAX);
            }
            if (due) {
                bad = 0;
#pragma unroll
                for (int u = 0; u < WPS; u++)
#pragma unroll
                    for (int k = 0; k < RPL; k++) bad |= ml[u][k].x ^ tag;
            }
            if (__all_sync(0xffffffffu, !(bad & 1u) && n == (epoch + 1u) * NCTA)) {
#pragma unroll
                for (int u = 0; u < WPS; u++) {
                    float M = -INFINITY, L = 0.f, w = 0.f;
#pragma unroll
                    for (int k = 0; k < RPL; k++) M = fmaxf(M, __uint_as_float(ml[u][k].x & ~1u));
#pragma unroll
                    for (int o = G / RPL / 2; o; o >>= 1) M = fmaxf(M, shx(M, o));
#pragma unroll
                    for (int k = 0; k < RPL; k++) {
                        const float wk = __expf(__uint_as_float(ml[u][k].x & ~1u) - M);
                        L += wk * __uint_as_float(ml[u][k].y);
                        if (k == r / 32) w = wk;
                    }
#pragma unroll
                    for (int o = G / RPL / 2; o; o >>= 1) L += shx(L, o);
                    if (lane == r % 32) reinterpret_cast<float*>(smem + SM_LS)[16 + (j & 3) * WPS + u] = __fdividef(w, L);
                }
                if (lane == r % 32) {
                    mbar_arrive(bar_full + B_WRDY + (j & 3) * 8);
                    if (j == NSTEP - 1) TS(11);
                }
                j++;
                due = false;
            }
            if (j == NSTEP && landed >= ITEMS_ATT - DEPTH) return;
            if (!due && j < NSTEP) due = mbar_test(bar_full + B_WTRIG + (j & 3) * 8, (j >> 2) & 1);
            __nanosleep(P_SLEEP);
            if (it > SPIN_LIMIT) __trap();
        }
    }
    if (warp > W_PROD) {
        const uint32_t tag = (epoch + 1u) & 1u;
        const int e = tid - (W_PROD + 1) * 32;
        if (is_att) {
#pragma unroll 1
            for (int i = e; i < 192; i += NXW * 32)
                st_fill4(g_qpart + (cta * NB + i / 48) * VS + (i % 48) / 6 * 32 + (i % 6) * 4, tag ^ 1u);
            st_fill4(reinterpret_cast<float*>(ocell(cta, e)), 0u);
            if (e < 32) *reinterpret_cast<uint32_t*>(smem + SM_HF + e * 16 + 12) = 0u;
        } else {
#pragma unroll 1
            for (int c = e; c < 256; c += NXW * 32) {
                const bf16* xp = x + qd * DM + (c >> 6) * 160 + ((c >> 3) & 7) * 8 + (c & 3) * 2 + ((c >> 2) & 1);
                asm volatile("st.relaxed.gpu.global.v4.f32 [%0], {%1,%2,%3,%4};"
                             ::"l"(g_acc + (qd * 32 + (c >> 3)) * ACS + (c & 7)), "f"(__bfloat162float(xp[0])),
                               "f"(__bfloat162float(xp[64])), "f"((c & 32) ? 0.f : __bfloat162float(xp[128])), "f"(0.f) : "memory");
            }
        }
        asm volatile("bar.sync 2, %0;" ::"n"(NTHR) : "memory");
        if (!is_att) return;
        {
            const uint32_t eq = (e >> 5) * 24 + min(lane, 23), xw = eq / 6, xr = eq % 6;
            mbar_wait(bar_full + B_QTRIG, 0);
            if (e == 0) TS(10);
            settle(P_QDELAY);
#pragma unroll 1
            for (int j = 0; j < NSTEP; j++) {
                uint4 v[WPS][4];
                uint32_t bad;
                unsigned spin = 0;
                do {
#pragma unroll
                    for (int u = 0; u < WPS; u++) {
                        const int pair = pair_of(sg, j * WPS + u);
                        const float* src = g_qpart + ((pair >> 2) * 4 * NB + (pair & 3)) * VS + xw * 32 + xr * 4;
#pragma unroll
                        for (int k = 0; k < 4; k++) v[u][k] = ld_word2(src + k * NB * VS);
                    }
                    bad = 0;
#pragma unroll
                    for (int u = 0; u < WPS; u++)
#pragma unroll
                        for (int k = 0; k < 4; k++) bad |= (v[u][k].x ^ tag) | (v[u][k].z ^ tag);
                    if (++spin > SPIN_LIMIT) __trap();
                } while (bad & 1u);
#define SUM4(c) ((__uint_as_float(v[u][0].c) + __uint_as_float(v[u][1].c)) + (__uint_as_float(v[u][2].c) + __uint_as_float(v[u][3].c)))
#pragma unroll
                for (int u = 0; u < WPS; u++) {
                    unsigned char* dst = smem + SM_QS + (j * WPS + u) * (DH * 2) + (xr & 1) * 192 + ((xr >> 1) * 8 + xw) * 4;
                    *reinterpret_cast<uint32_t*>(dst) = pack_bf2(SUM4(x), SUM4(y));
                    *reinterpret_cast<uint32_t*>(dst + 96) = pack_bf2(SUM4(z), SUM4(w));
                }
#undef SUM4
                __syncwarp();
                if (lane == 0) mbar_arrive(bar_full + B_QRDY + j * 8);
                if (e == 0 && j == 0) TS(12);
            }
        }
        bool have_h = false;
#pragma unroll 1
        for (int b = 0; b <= NB; b++) {
            if (!have_h && (b == NB || order_of(r, b) >= HSTEP * WPS)) {
                have_h = true;
                mbar_wait(bar_full + B_HTRIG, 0);
#pragma unroll 1
                for (int i = e; i < 96; i += NXW * 32) {
                    const int k = (i % 24) * 2;
                    uint2 v;
                    unsigned spin = 0;
                    do {
                        v = ld_word(g_h + i / 24 * FF + h * 48 + k);
                        if (++spin > SPIN_LIMIT) __trap();
                    } while ((v.x ^ tag) & 1u);
                    *reinterpret_cast<uint32_t*>(smem + SM_HF + k / 24 * 256 + i / 24 * 64 + frag_off(k % 24)) = __byte_perm(v.x, v.y, 0x7632);
                }
                __syncwarp();
                if (lane == 0) mbar_arrive(bar_full + B_HRDY);
            }
            if (b == NB) break;
            const float4* src = ocell(h * NB + b, e);
            uint32_t dst = sb + SM_OF + (e >> 5) * 256 + b * 64 + frag_off(lane), ordy = bar_full + B_ORDY;
            asm volatile("" : "+r"(dst), "+l"(src), "+r"(ordy));
            mbar_wait(bar_full + B_OTRIG + b * 8, 0);
            const int pause = order_of(r, b) < G - WPS ? P_SETTLE : 0;
            unsigned spin = 0;
            float o0, o1, o2, n;
            do {
                settle(pause);
                asm volatile("atom.relaxed.gpu.global.add.v4.f32 {%0,%1,%2,%3}, [%4], {%5,%5,%5,%5};"
                             : "=f"(o0), "=f"(o1), "=f"(o2), "=f"(n) : "l"(src), "f"(0.f) : "memory");
                asm volatile("st.shared.u16 [%0], %1;\nst.shared.u16 [%0+512], %2;\nst.shared.u16 [%0+1024], %3;"
                             ::"r"(dst), "h"(__bfloat16_as_ushort(__float2bfloat16_rn(o0))),
                               "h"(__bfloat16_as_ushort(__float2bfloat16_rn(o1))), "h"(__bfloat16_as_ushort(__float2bfloat16_rn(o2))) : "memory");
                if (++spin > SPIN_LIMIT) __trap();
            } while (n != (float)G);
            __syncwarp();
            if (lane == 0) mbar_arrive(ordy);
        }
        return;
    }

    if (warp < NB) {
        uint2 raw[5];
#pragma unroll
        for (int i = 0; i < 5; i++) raw[i] = __ldg(reinterpret_cast<const uint2*>(x + warp * DM) + i * 32 + lane);
        float s = 0.f;
#pragma unroll
        for (int i = 0; i < 5; i++) s += (bf_lo(raw[i].x) + bf_hi(raw[i].x)) + (bf_lo(raw[i].y) + bf_hi(raw[i].y));
#pragma unroll
        for (int o = 16; o; o >>= 1) s += shx(s, o);
        const float mean = s * (1.0f / DM);
        float q2 = 0.f;
#pragma unroll
        for (int i = 0; i < 5; i++) {
            const float d0 = bf_lo(raw[i].x) - mean, d1 = bf_hi(raw[i].x) - mean;
            const float d2 = bf_lo(raw[i].y) - mean, d3 = bf_hi(raw[i].y) - mean;
            q2 += (d0 * d0 + d1 * d1) + (d2 * d2 + d3 * d3);
        }
#pragma unroll
        for (int o = 16; o; o >>= 1) q2 += shx(q2, o);
        const float mb = bf_round(mean);
        const float rs = __frcp_rn(bf_round(__fsqrt_rn(bf_round(bf_round(q2 * (1.0f / DM)) + 1e-5f))));
        const uint32_t k = (lane * 4) & 31;
        unsigned char* dst = smem + SM_XF + warp * 64 +
            (is_att ? (lane >> 3) * 256 + frag_off(k) : (lane >> 2) * 256 + frag_off(k & 15));
        const uint32_t step = is_att ? 1024 : 2048;
#pragma unroll
        for (int i = 0; i < 5; i++) {
            const uint32_t d0 = pack_bf2(bf_lo(raw[i].x) - mb, bf_hi(raw[i].x) - mb);
            const uint32_t d1 = pack_bf2(bf_lo(raw[i].y) - mb, bf_hi(raw[i].y) - mb);
            *reinterpret_cast<uint32_t*>(dst + i * step) = pack_bf2(bf_lo(d0) * rs, bf_hi(d0) * rs);
            *reinterpret_cast<uint32_t*>(dst + i * step + 16) = pack_bf2(bf_lo(d1) * rs, bf_hi(d1) * rs);
        }
    }
    asm volatile("bar.sync 2, %0;" ::"n"(NTHR) : "memory");
    uint32_t tag = (epoch + 1u) & 1u;
    asm volatile("" : "+r"(tag));
    if (tid == 0) TS(3);

    Ring ring{bar_full, sb + SM_RING, 0u, bar_full};
    float lo[3][4] = {}, hi[3][4] = {};
    uint32_t off[3];
    const uint32_t a_lane = (g & 3) * 64 + t * 16;

    if (is_att) {
        float* lsum = reinterpret_cast<float*>(smem + SM_LS);
#pragma unroll 1
        for (int j = -1; j < NSTEP + LA; j++) {
            if (j >= 0 && j < NSTEP) {
                constexpr int WW = NCW / WPS;
                const int win = j * WPS + warp / WW;
                uint32_t qf[6][4];
                mbar_wait(bar_full + B_QRDY + j * 8, 0);
                if (j == 0 && tid == 0) TS(6);
#pragma unroll
                for (int i = 0; i < 6; i++) lds128(sb + SM_QS + win * (DH * 2) + t * 96 + i * 16, qf[i]);
                const uint32_t key = (warp & 1) * 16 + (lane & 15);
                const uint32_t item = 5 + (j + max(j - LA, 0)) * 4 + (warp >> 1), slot = item % NS;
#pragma unroll
                for (int s = 0; s < 3; s++)
                    off[s] = sb + SM_RING + slot * SLOT + key * 384 + s * 128 + (((lane >> 4) ^ ((3 * key + s) & 7)) << 4);
                pin3(off);
                mbar_wait(bar_full + slot * 8, (item / NS) & 1);
                float c[3][4] = {};
#pragma unroll
                for (int dq = 0; dq < 4; dq++)
#pragma unroll
                    for (int s = 0; s < 3; s++) {
                        uint32_t a[4];
                        ldsm_x4(off[s] ^ (dq << 5), a);
                        mma16816(c[s], a, qf[s * 2 + (dq >> 1)][(dq & 1) * 2], qf[s * 2 + (dq >> 1)][(dq & 1) * 2 + 1]);
                    }
                __syncwarp();
                if (lane == 0)
                    asm volatile("mbarrier.arrive.shared::cta.b64 _, [%0], %1;" ::"r"(bar_full + (NS + slot) * 8), "n"(NCW / 2) : "memory");
                ring.skip(4);
                const float raw = (t & 1) ? (c[0][2] + c[1][2]) + c[2][2] : (c[0][0] + c[1][0]) + c[2][0];
                const float sv = bf_round(bf_round(raw) * 0.07216878364870323f);
                if (tid == 0 && j == NSTEP - 1) TS(14);
                float m = fmaxf(sv, shx(sv, 1));
#pragma unroll
                for (int o = 4; o < 32; o <<= 1) m = fmaxf(m, shx(m, o));
                if (lane == 0) lsum[8 + warp] = m;
                cons_bar();
#pragma unroll
                for (int i = 0; i < WW; i += 2) {
                    const float2 m2 = *reinterpret_cast<const float2*>(lsum + 8 + warp / WW * WW + i);
                    m = fmaxf(m, fmaxf(m2.x, m2.y));
                }
                float l = __expf(sv - m);
                *reinterpret_cast<bf16*>(smem + SM_PF + ((j & 3) * 4 + (warp >> 1)) * 64 + frag_off((warp & 1) * 16 + (t & 1) * 8 + g)) =
                    __float2bfloat16_rn(l);
                l += shx(l, 1);
#pragma unroll
                for (int o = 4; o < 32; o <<= 1) l += shx(l, o);
                if (lane == 0) lsum[warp] = l;
                cons_bar();
                if (tid % (WW * 32) < 4) {
                    l = 0.f;
#pragma unroll
                    for (int i = 0; i < WW; i += 2) {
                        const float2 l2 = *reinterpret_cast<const float2*>(lsum + warp + i);
                        l += l2.x + l2.y;
                    }
                    st_tag2(g_ml + (pair_of(sg, win) * G + r) * MLS + lane * 2, m, l, tag);
                    if (tid == 0) {
                        mbar_arrive(bar_full + B_WTRIG + (j & 3) * 8);
                        if (j == HSTEP) mbar_arrive(bar_full + B_HTRIG);
                    }
                }
                if (tid == 0 && j == NSTEP - 1) TS(13);
                if (j < LA) continue;
            }
            const bool kv = j >= 0;
            const uint32_t jv = j - LA;
#pragma unroll
            for (int s = 0; s < 3; s++) off[s] = lane * 384 + s * 128 + ((warp ^ ((3 * lane + s) & 7)) << 4);
#pragma unroll 1
            for (int u = 0; u < (kv ? WPS : 1); u++) {
                const int pair = pair_of(sg, jv * WPS + u);
                uint32_t trig = !kv ? bar_full + B_QTRIG : (pair >> 2) == h ? bar_full + B_OTRIG + (pair & 3) * 8 : 0;
                if (tid != 0) trig = 0;
                float4* oacc = ocell(pair, warp * 8 + 2 * t + (g & 1));
                uint32_t wrdy = bar_full + B_WRDY + (jv & 3) * 8;
                asm volatile("" : "+l"(oacc), "+r"(trig), "+r"(wrdy));
                gemv_loop(ring, kv ? NT : 5,
                          kv ? sb + SM_PF + ((jv & 3) * 4 + u * NT) * 64 + t * 16 : sb + SM_XF + qd * 5 * 256 + a_lane,
                          kv ? 64 : 256, off, lo, hi, lane);
                if (kv) {
                    mbar_wait(wrdy, (jv >> 2) & 1);
                    const float w = lsum[16 + (jv & 3) * WPS + u];
                    if (g < 2)
                        asm volatile("red.relaxed.gpu.global.add.v4.f32 [%0], {%1,%2,%3,%4};"
                                     ::"l"(oacc), "f"(w * (g ? lo[0][1] + hi[0][3] : lo[0][0] + hi[0][2])),
                                       "f"(w * (g ? lo[1][1] + hi[1][3] : lo[1][0] + hi[1][2])),
                                       "f"(w * (g ? lo[2][1] + hi[2][3] : lo[2][0] + hi[2][2])), "f"(1.0f) : "memory");
                } else if (g < NB) {
#pragma unroll
                    for (int s = 0; s < 3; s++)
                        st_tag2(g_qpart + (cta * NB + g) * VS + warp * 32 + 2 * t + s * 8, lo[s][0] + hi[s][2], lo[s][1] + hi[s][3], tag);
                }
                if (trig) mbar_arrive(trig);
            }
            const bool pass = j == NSTEP + LA - 1;
            if (pass && tid == 0) TS(5);
            if (kv && !pass && j != P_DRY) continue;
            if (tid == 0 && j < 0) TS(4);

            {
                constexpr int I0 = 5 + NKV;
                static_assert(((I0 / NS) & 1) == 0 && I0 / NS == (I0 + 7) / NS, "tail items complete an even phase");
                const uint32_t done = bar_full + B_QTRIG;
                uint32_t fb = pass ? bar_full + (I0 % NS) * 8 : done, fs = pass ? 8 : 0, ordy = pass ? bar_full + B_ORDY : done;
                uint32_t off2[3], a[8][4], b[8][3][4], a_addr = sb + SM_HF + a_lane;
#pragma unroll
                for (int s = 0; s < 3; s++) {
                    const uint32_t w64 = lane * 320 + (warp + 8 * s) * 16;
                    off[s] = sb + SM_RING + (I0 % NS) * SLOT + (w64 ^ (((w64 >> 7) & 3) << 4));
                    off2[s] = lane < 24 ? off[s] : off[s] - 8 * 320;
#pragma unroll
                    for (int e = 0; e < 4; e++) { lo[s][e] = 0.f; hi[s][e] = 0.f; }
                }
                const float4* accp = g_acc + (((g & 3) * 4 + qd) * NCW + warp) * ACS + (g >> 2) * 4 + t;
                bf16* outp = out + (g & 3) * DM + qd * 160 + warp * 8 + 2 * t + (g >> 2);
                pin3(off);
                asm volatile("" : "+l"(accp), "+l"(outp), "+r"(a_addr), "+r"(ordy), "+r"(fb), "+r"(fs));
                auto load_b = [&](int i, bool& next) {
                    if (!next) mbar_wait(fb + i * fs, 0);
                    if (i < 7) next = mbar_test(fb + (i + 1) * fs, 0);
#pragma unroll
                    for (int s = 0; s < 3; s++)
                        if (s < 2 || warp < 4) ldsm_x4_t((i < 2 ? off2[s] : off[s]) + i * SLOT, b[i][s]);
                };
                auto mul = [&](int i) {
#pragma unroll
                    for (int s = 0; s < 3; s++)
                        if (s < 2 || warp < 4) { mma16816(lo[s], a[i], b[i][s][0], b[i][s][1]); mma16816(hi[s], a[i], b[i][s][2], b[i][s][3]); }
                };
                bool next = mbar_test(fb, 0);
                mbar_wait(pass ? bar_full + B_HRDY : done, 0);
                lds128(a_addr, a[0]);
                lds128(a_addr + 256, a[1]);
                load_b(0, next);
                load_b(1, next);
                bool early = mbar_test(ordy, 0);
                mul(0);
                mul(1);
                if (pass && tid == 0) TS(31);
                unsigned spin = 0;
                while (!early && !mbar_test(fb + P_DEC * fs, 0)) {
                    early = mbar_test(ordy, 0);
                    if (++spin > SPIN_LIMIT) __trap();
                }
                if (pass ? __all_sync(0xffffffffu, early) : j < 0) {
                    if (pass && tid == 0) TS(7);
#pragma unroll
                    for (int i = 2; i < 8; i++) lds128(a_addr + i * 256, a[i]);
                    load_b(2, next);
#pragma unroll
                    for (int i = 2; i < 7; i++) { load_b(i + 1, next); mul(i); }
                    mul(7);
                } else {
#pragma unroll
                    for (int i = 2; i < 8; i++) load_b(i, next);
                    mbar_wait(ordy, 0);
                    if (pass && tid == 0) TS(7);
#pragma unroll
                    for (int i = 2; i < 8; i++) lds128(a_addr + i * 256, a[i]);
#pragma unroll
                    for (int i = 2; i < 8; i++) mul(i);
                }
                if (pass && tid == 0) TS(8);
                add_out(accp, outp, lo, hi, g >= NB, warp < 4, pass, epoch);
            }
        }
        if (tid == 0) { TS(9); TS_DUMP(3, 32); }
    } else {
        float gate[6][2];
#pragma unroll
        for (int s = 0; s < 3; s++) {
            const uint32_t r128 = (lane & 15) * 6 + 2 * s + (lane >> 4);
            off[s] = r128 * 128 + ((warp ^ (r128 & 7)) << 4);
        }
#pragma unroll 1
        for (int ps = 0; ps < 2; ps++) {
#pragma unroll
            for (int s = 0; s < 3; s++) {
                gate[2 * s][0] = lo[s][0]; gate[2 * s][1] = lo[s][1];
                gate[2 * s + 1][0] = hi[s][0]; gate[2 * s + 1][1] = hi[s][1];
            }
            gemv_loop(ring, 40, sb + SM_XF + a_lane, 256, off, lo, hi, lane);
        }
#pragma unroll
        for (int p = 0; p < 6; p++) {
            float hv[2];
#pragma unroll
            for (int e = 0; e < 2; e++) {
                const float gt = bf_round(gate[p][e]);
                hv[e] = bf_round(bf_round(__fdividef(gt, 1.0f + __expf(-gt))) * bf_round((p & 1) ? hi[p >> 1][e] : lo[p >> 1][e]));
            }
            if (g < NB) st_tag2(g_h + g * FF + qd * 384 + p * 64 + warp * 8 + 2 * t, hv[0], hv[1], tag);
        }
        if (tid == 0) { TS(9); TS_DUMP(3, 10); }
    }
}

typedef CUresult (*EncodeFn)(CUtensorMap*, CUtensorMapDataType, cuuint32_t, void*, const cuuint64_t*, const cuuint64_t*,
                             const cuuint32_t*, const cuuint32_t*, CUtensorMapInterleave, CUtensorMapSwizzle,
                             CUtensorMapL2promotion, CUtensorMapFloatOOBfill);

void make_map(EncodeFn enc, CUtensorMap* m, const void* p, uint64_t rows, uint64_t cols, uint32_t inner, uint32_t parts,
              uint32_t box_rows) {
    const cuuint64_t dims[3] = {inner, cols / inner, rows};
    const cuuint64_t strides[2] = {inner * 2ull, cols * 2ull};
    const cuuint32_t box[3] = {inner, parts, box_rows};
    const cuuint32_t es[3] = {1, 1, 1};
    enc(m, CU_TENSOR_MAP_DATA_TYPE_BFLOAT16, 3, const_cast<void*>(p), dims, strides, box, es, CU_TENSOR_MAP_INTERLEAVE_NONE,
        inner == 64 ? CU_TENSOR_MAP_SWIZZLE_128B : CU_TENSOR_MAP_SWIZZLE_64B, CU_TENSOR_MAP_L2_PROMOTION_NONE,
        CU_TENSOR_MAP_FLOAT_OOB_FILL_NONE);
}

}

extern "C" void kernel_launch(void* const* d_in, const int* in_sizes, int n_in, void* d_out, int out_size) {
    (void)in_sizes; (void)n_in; (void)out_size;
    static EncodeFn enc = nullptr;
    if (!enc) {
        void* fn = nullptr;
        cudaDriverEntryPointQueryResult qr;
        cudaGetDriverEntryPoint("cuTensorMapEncodeTiled", &fn, cudaEnableDefault, &qr);
        enc = (EncodeFn)fn;
        cudaFuncSetAttribute(fused_decode_kernel, cudaFuncAttributeMaxDynamicSharedMemorySize, SM_TOTAL);
    }
    Maps maps;
    make_map(enc, &maps.k, d_in[1], (uint64_t)NB * NH * SK, DH, 64, 3, TK);
    make_map(enc, &maps.v, d_in[2], (uint64_t)NB * NH * SK, DH, 64, 3, TK);
    make_map(enc, &maps.wq, d_in[3], DM, NH * DH, 64, 3, 32);
    make_map(enc, &maps.wo, d_in[4], NH * DH, DM, 32, 5, 32);
    make_map(enc, &maps.w1, d_in[6], DM, FF, 64, 6, 16);
    make_map(enc, &maps.w3, d_in[7], DM, FF, 64, 6, 16);
    make_map(enc, &maps.w2, d_in[8], FF, DM, 32, 5, 24);
    fused_decode_kernel<<<NCTA, NTHR, SM_TOTAL>>>(maps, (const bf16*)d_in[0], (bf16*)d_out);
}
```

```cpp
#include <cuda_runtime.h>
#include <cuda.h>
#include <cuda_bf16.h>
#include <stdint.h>

namespace {

typedef __nv_bfloat16 bf16;

constexpr int NB = 4, DM = 640, NH = 32, DH = 192, SK = 8192, WIN = 2048, FF = 1536;

#define P_G 32
#define P_DEPTH 4
#define P_DEPTH_FFN 5
#define P_GAIN 6
#define P_BIAS 16
#define P_SLEEP 500
#define P_DMIN 3
#define P_DMAX 6
#define P_SETTLE 3000
#define P_QDELAY 1600
#define P_DRY 4
#define P_DEC 6
#define P_LA 2
#define P_MLS 8
#define P_OAL 72
#define P_PF 64
#define P_PF3 3
#define P_ORD 1
#define P_NS 16

constexpr int G = P_G;
constexpr int TK = 32;
constexpr int NT = WIN / TK / G;
constexpr int NSTEP = 16;
constexpr int WPS = G / NSTEP;
constexpr int LA = P_LA;
constexpr int MLS = P_MLS;
constexpr int OAL = P_OAL;
constexpr int HSTEP = 11;
constexpr int NS = P_NS;
constexpr int SLOT = 12288;
constexpr int DEPTH = P_DEPTH;
#define P_D0 5
constexpr int DEPTH0 = P_D0;
static_assert(DEPTH0 <= 5, "DEPTH0");
constexpr int NATT = 128, NFFN = 4, NCTA = NATT + NFFN;
constexpr int NCW = 8;
constexpr int NXW = 2;
constexpr int W_PROD = NCW, W_PACE = NCW + 1 + NXW;
constexpr int NTHR = (W_PACE + 1) * 32;
constexpr int NSRC = NH;
constexpr int VS = 256;
#define P_ACS 40
constexpr int ACS = P_ACS;
static_assert(G == 16 || G == 32 || G == 64, "G");

constexpr int SM_RING = 0;
constexpr int SM_XF = SM_RING + NS * SLOT;
constexpr int SM_QS = SM_XF + 20 * 256;
constexpr int SM_PF = SM_QS + G * DH * 2;
constexpr int SM_HF = SM_PF + 4 * 4 * 64;
constexpr int SM_OF = SM_HF + 2 * 256;
constexpr int SM_LS = SM_OF + 6 * 256;
constexpr int SM_ATT_END = SM_LS + 128;
constexpr int SM_FFN_END = SM_XF + 40 * 256;
constexpr int SM_BAR = SM_ATT_END > SM_FFN_END ? SM_ATT_END : SM_FFN_END;
constexpr int B_QRDY = 2 * NS * 8, B_ORDY = B_QRDY + NSTEP * 8, B_OTRIG = B_ORDY + 8, B_QTRIG = B_OTRIG + 32,
              B_WTRIG = B_QTRIG + 8, B_WRDY = B_WTRIG + 32, B_HTRIG = B_WRDY + 32, B_HRDY = B_HTRIG + 8,
              NBAR = 2 * NS + NSTEP + 16;
constexpr int SM_PACE = SM_BAR + NBAR * 8;
constexpr int SM_TS = SM_PACE + 8;
constexpr int SM_TOTAL = SM_TS + 256;
static_assert(SM_TOTAL <= 232448, "smem");

constexpr int NKV = 2 * NT * G;
constexpr int ITEMS_ATT = 5 + NKV + 2 + 6;
constexpr int ITEMS_FFN = 80;

struct Maps { CUtensorMap k, v, wq, wo, w1, w3, w2; };

struct alignas(32) Sync { unsigned epoch, inits, prog[2]; };
__device__ Sync g_sync;
__device__ __align__(128) float g_qpart[NATT * NB * VS];
__device__ __align__(128) float g_ml[NATT * G * MLS];
__device__ __align__(128) float g_h[NB * FF];
__device__ __align__(128) float4 g_oacc[NATT * 8 * OAL];
__device__ __align__(128) float4 g_acc[NB * 4 * NCW * ACS];
#define TS(i)
#define TS_DUMP(lo, hi)

constexpr unsigned SPIN_LIMIT = 1u << 22;

__device__ __forceinline__ void mbar_init(uint32_t bar, int cnt) {
    asm volatile("mbarrier.init.shared::cta.b64 [%0], %1;" ::"r"(bar), "r"(cnt) : "memory");
}
__device__ __forceinline__ void mbar_expect_tx(uint32_t bar, uint32_t bytes) {
    asm volatile("mbarrier.arrive.expect_tx.shared::cta.b64 _, [%0], %1;" ::"r"(bar), "r"(bytes) : "memory");
}
__device__ __forceinline__ void mbar_arrive(uint32_t bar) {
    asm volatile("mbarrier.arrive.shared::cta.b64 _, [%0];" ::"r"(bar) : "memory");
}
__device__ __forceinline__ void mbar_wait(uint32_t bar, uint32_t parity) {
    asm volatile("{\n.reg .pred p, q;\n.reg .u32 n;\nmov.u32 n, 0;\n"
                 "W: mbarrier.try_wait.parity.shared::cta.b64 p, [%0], %1;\n"
                 "@p bra D;\nadd.u32 n, n, 1;\nsetp.lt.u32 q, n, %2;\n@q bra W;\ntrap;\nD:\n}"
                 ::"r"(bar), "r"(parity), "n"(SPIN_LIMIT) : "memory");
}
__device__ __forceinline__ bool mbar_test(uint32_t bar, uint32_t parity) {
    uint32_t ok;
    asm volatile("{\n.reg .pred p;\nmbarrier.test_wait.parity.shared::cta.b64 p, [%1], %2;\nselp.u32 %0, 1, 0, p;\n}"
                 : "=r"(ok) : "r"(bar), "r"(parity) : "memory");
    return ok;
}
__device__ __forceinline__ void tma3d(uint32_t dst, const CUtensorMap* map, int c1, int c2, uint32_t bar) {
    const uint64_t pol = 0x12F0000000000000ull;
    asm volatile("cp.async.bulk.tensor.3d.shared::cluster.global.mbarrier::complete_tx::bytes.L2::cache_hint "
                 "[%0], [%1, {%2, %3, %4}], [%5], %6;"
                 ::"r"(dst), "l"(map), "r"(0), "r"(c1), "r"(c2), "r"(bar), "l"(pol) : "memory");
}
__device__ __forceinline__ void ldsm_x4(uint32_t addr, uint32_t (&r)[4]) {
    asm volatile("ldmatrix.sync.aligned.m8n8.x4.shared.b16 {%0,%1,%2,%3}, [%4];"
                 : "=r"(r[0]), "=r"(r[1]), "=r"(r[2]), "=r"(r[3]) : "r"(addr) : "memory");
}
__device__ __forceinline__ void ldsm_x4_t(uint32_t addr, uint32_t (&r)[4]) {
    asm volatile("ldmatrix.sync.aligned.m8n8.x4.trans.shared.b16 {%0,%1,%2,%3}, [%4];"
                 : "=r"(r[0]), "=r"(r[1]), "=r"(r[2]), "=r"(r[3]) : "r"(addr) : "memory");
}
__device__ __forceinline__ void lds128(uint32_t addr, uint32_t (&r)[4]) {
    asm volatile("ld.shared.v4.u32 {%0,%1,%2,%3}, [%4];"
                 : "=r"(r[0]), "=r"(r[1]), "=r"(r[2]), "=r"(r[3]) : "r"(addr) : "memory");
}
__device__ __forceinline__ void mma16816(float (&c)[4], const uint32_t (&a)[4], uint32_t b0, uint32_t b1) {
    asm volatile("mma.sync.aligned.m16n8k16.row.col.f32.bf16.bf16.f32 {%0,%1,%2,%3}, {%4,%5,%6,%7}, {%8,%9}, {%0,%1,%2,%3};"
                 : "+f"(c[0]), "+f"(c[1]), "+f"(c[2]), "+f"(c[3])
                 : "r"(a[0]), "r"(a[1]), "r"(a[2]), "r"(a[3]), "r"(b0), "r"(b1));
}
__device__ __forceinline__ void cons_bar() { asm volatile("bar.sync 1, 256;" ::: "memory"); }

__device__ __forceinline__ float bf_round(float v) { return __bfloat162float(__float2bfloat16_rn(v)); }
__device__ __forceinline__ uint32_t pack_bf2(float lo, float hi) {
    __nv_bfloat162 t = __floats2bfloat162_rn(lo, hi);
    return *reinterpret_cast<uint32_t*>(&t);
}
__device__ __forceinline__ float bf_lo(uint32_t u) { return __uint_as_float(u << 16); }
__device__ __forceinline__ float bf_hi(uint32_t u) { return __uint_as_float(u & 0xffff0000u); }
__device__ __forceinline__ float shx(float v, int o) { return __shfl_xor_sync(0xffffffffu, v, o); }

__device__ __forceinline__ uint32_t frag_off(uint32_t k) {
    return ((k >> 1) & 3) * 16 + ((k >> 3) & 1) * 8 + ((k >> 4) & 1) * 4 + (k & 1) * 2;
}

__device__ __forceinline__ void st_tag2(float* p, float a, float b, uint32_t tag) {
    asm volatile("{\n.reg .b64 w;\n.reg .b32 x;\nlop3.b32 x, %1, 0xfffffffe, %3, 0xea;\nmov.b64 w, {x, %2};\n"
                 "st.relaxed.gpu.global.b64 [%0], w;\n}"
                 ::"l"(p), "r"(__float_as_uint(a)), "r"(__float_as_uint(b)), "r"(tag) : "memory");
}
__device__ __forceinline__ void st_fill4(float* p, uint32_t v) {
    asm volatile("{\n.reg .b64 w;\nmov.b64 w, {%1, %1};\nst.relaxed.gpu.global.v2.b64 [%0], {w, w};\n}" ::"l"(p), "r"(v) : "memory");
}
__device__ __forceinline__ uint2 ld_word(const float* p) {
    uint2 v;
    asm volatile("{\n.reg .b64 w;\nld.relaxed.gpu.global.b64 w, [%2];\nmov.b64 {%0,%1}, w;\n}" : "=r"(v.x), "=r"(v.y) : "l"(p) : "memory");
    return v;
}
__device__ __forceinline__ uint4 ld_word2(const float* p) {
    uint4 v;
    asm volatile("{\n.reg .b64 w0, w1;\nld.relaxed.gpu.global.v2.b64 {w0, w1}, [%4];\nmov.b64 {%0,%1}, w0;\nmov.b64 {%2,%3}, w1;\n}"
                 : "=r"(v.x), "=r"(v.y), "=r"(v.z), "=r"(v.w) : "l"(p) : "memory");
    return v;
}

__device__ __forceinline__ void add_out(const float4* acc, bf16* out, const float (&lo)[3][4], const float (&hi)[3][4],
                                        bool odd, bool third, bool live, uint32_t epoch) {
    const float v0 = odd ? lo[0][1] + hi[0][3] : lo[0][0] + hi[0][2];
    const float v1 = odd ? lo[1][1] + hi[1][3] : lo[1][0] + hi[1][2];
    const float v2 = odd ? lo[2][1] + hi[2][3] : lo[2][0] + hi[2][2];
    float o0, o1, o2, n = 0.f;
    asm volatile("{\n.reg .pred p;\nsetp.ne.u32 p, %5, 0;\n"
                 "@p atom.relaxed.gpu.global.add.v4.f32 {%0,%1,%2,%3}, [%4], {%6,%7,%8,%9};\n}"
                 : "=f"(o0), "=f"(o1), "=f"(o2), "+f"(n)
                 : "l"(acc), "r"((uint32_t)live), "f"(v0), "f"(v1), "f"(v2), "f"(1.0f) : "memory");
    asm volatile("{\n.reg .pred p, q;\nsetp.eq.f32 p, %4, %5;\nsetp.ne.and.u32 q, %6, 0, p;\n"
                 "@p st.global.u16 [%0], %1;\n@p st.global.u16 [%0+128], %2;\n@q st.global.u16 [%0+256], %3;\n}"
                 ::"l"(out), "h"(__bfloat16_as_ushort(__float2bfloat16_rn(o0 + v0))),
                   "h"(__bfloat16_as_ushort(__float2bfloat16_rn(o1 + v1))), "h"(__bfloat16_as_ushort(__float2bfloat16_rn(o2 + v2))),
                   "f"(n), "f"((float)(NSRC - 1)), "r"((uint32_t)third) : "memory");
    if (acc == g_acc && n == (float)(NSRC - 1))
        asm volatile("st.relaxed.gpu.global.u32 [%0], %1;" ::"l"(&g_sync.epoch), "r"(epoch + 1u) : "memory");
}

__device__ __forceinline__ int pair_of(int sg, uint32_t j) { return sg * G + (j % (G / 4)) * 4 + j / (G / 4); }
__device__ __forceinline__ int order_of(int r, int b) { return b * (G / 4) + (r >> 2); }

__device__ __forceinline__ float4* ocell(uint32_t pair, uint32_t i) {
    return g_oacc + (pair * 8 + (i >> 3)) * OAL + (i & 7);
}

__device__ __forceinline__ void settle(int cycles) {
    const uint32_t t0 = (uint32_t)clock();
    while ((uint32_t)clock() - t0 < (uint32_t)cycles) __nanosleep(20);
}

struct Ring {
    uint32_t full, addr, phase, first_full;
    __device__ __forceinline__ void wait() const { mbar_wait(full, phase); }
    __device__ __forceinline__ void skip(int n) {
        full += n * 8; addr += n * SLOT;
        if (full >= first_full + NS * 8) { full -= NS * 8; addr -= NS * SLOT; phase ^= 1; }
    }
    __device__ __forceinline__ void release(int lane) {
        __syncwarp();
        if (lane == 0) mbar_arrive(full + NS * 8);
        full += 8; addr += SLOT;
        if (full == first_full + NS * 8) { full = first_full; addr -= NS * SLOT; phase ^= 1; }
    }
};

__device__ __forceinline__ void pin3(uint32_t (&v)[3]) {
    asm volatile("" : "+r"(v[0]), "+r"(v[1]), "+r"(v[2]));
}
__device__ __forceinline__ void gemv_loop(Ring& ring, int n, uint32_t a_addr, uint32_t a_step, uint32_t (&off)[3],
                                          float (&lo)[3][4], float (&hi)[3][4], int lane) {
    pin3(off);
#pragma unroll
    for (int s = 0; s < 3; s++)
#pragma unroll
        for (int e = 0; e < 4; e++) { lo[s][e] = 0.f; hi[s][e] = 0.f; }
#pragma unroll 1
    for (int it = 0; it < n; it++) {
        uint32_t a[4], b[3][4];
        lds128(a_addr, a);
        a_addr += a_step;
        ring.wait();
#pragma unroll
        for (int s = 0; s < 3; s++) ldsm_x4_t(ring.addr + off[s], b[s]);
#pragma unroll
        for (int s = 0; s < 3; s++) { mma16816(lo[s], a, b[s][0], b[s][1]); mma16816(hi[s], a, b[s][2], b[s][3]); }
        ring.release(lane);
    }
}

__global__ void __launch_bounds__(NTHR, 1)
fused_decode_kernel(const char* __restrict__ wq, const bf16* __restrict__ x, bf16* __restrict__ out,
                    const __grid_constant__ Maps maps) {
    asm volatile("{\n.reg .pred p;\n.reg .b32 t, c, a, b;\n.reg .b64 o;\n"
                 "mov.u32 t, %%tid.x;\nmov.u32 c, %%ctaid.x;\n"
                 "and.b32 a, c, 3;\nshr.u32 c, c, 2;\nmul.lo.u32 a, a, 15360;\nmad.lo.u32 a, c, 3, a;\n"
                 "shr.u32 b, t, 2;\nmad.lo.u32 a, b, 92, a;\nadd.u32 a, a, t;\nmad.wide.u32 o, a, 128, %0;\n"
                 "and.b32 b, t, 3;\nsetp.ne.u32 p, b, %2;\nsetp.lt.and.u32 p, t, %1, p;\n@p prefetch.global.L2 [o];\n}"
                 ::"l"(wq), "n"(P_PF * 4), "n"(P_PF3) : "memory");
    extern __shared__ __align__(1024) unsigned char smem[];
    const uint32_t sb = (uint32_t)__cvta_generic_to_shared(smem);
    const uint32_t bar_full = sb + SM_BAR;
    if (threadIdx.x == 0 && blockIdx.x < NATT) {
        TS(0);
#pragma unroll 1
        for (int i = 0; i < DEPTH0; i++) {
            mbar_init(bar_full + i * 8, 1);
            mbar_expect_tx(bar_full + i * 8, 12288);
            tma3d(sb + SM_RING + i * SLOT, &maps.wq, (blockIdx.x >> 2) * 3, (blockIdx.x & 3) * 160 + i * 32, bar_full + i * 8);
        }
        TS(1);
    }
    unsigned ptid, cta;
    asm volatile("mov.u32 %0, %%tid.x;\nmov.u32 %1, %%ctaid.x;" : "=r"(ptid), "=r"(cta));
    const int tid = ptid < 32 ? ptid + NCW * 32 : ptid < (NCW + 1) * 32 ? ptid - 32 : ptid;
    const int warp = tid >> 5, lane = tid & 31;
    const bool is_att = cta < NATT;
    const int h = cta >> 2, qd = cta & 3;
    const int sg = cta / G, r = cta % G;

    if (warp == NCW) {
        volatile int* pace = reinterpret_cast<volatile int*>(smem + SM_PACE);
        if (lane == 0) {
            if (!is_att) { TS(0); TS(1); }
            pace[0] = 0;
            pace[1] = is_att ? DEPTH : P_DEPTH_FFN;
#pragma unroll
            for (int i = 0; i < NBAR; i++)
                if (i >= DEPTH0 || !is_att)
                mbar_init(bar_full + i * 8, i < NS ? 1 : i < 2 * NS ? NCW : i < 2 * NS + NSTEP ? NXW : i == 2 * NS + NSTEP ? NXW * NB : i == NBAR - 1 ? NXW : 1);
            asm volatile("fence.mbarrier_init.release.cluster;" ::: "memory");
        }
        __syncwarp();
        asm volatile("bar.arrive 2, %0;" ::"n"(NTHR) : "memory");
        if (lane == 0) {
            const int n_items = is_att ? ITEMS_ATT : ITEMS_FFN;

            asm volatile("prefetch.tensormap [%0];" ::"l"(is_att ? &maps.k : &maps.w3) : "memory");
            asm volatile("prefetch.tensormap [%0];" ::"l"(&maps.v) : "memory");
            asm volatile("prefetch.tensormap [%0];" ::"l"(&maps.w2) : "memory");
            asm volatile("prefetch.tensormap [%0];" ::"l"(&maps.wo) : "memory");
#pragma unroll 1
            for (int i = is_att ? DEPTH0 : 0; i < n_items; i++) {
                const CUtensorMap* map;
                int c1, c2;
                uint32_t bytes = 12288;
                if (is_att) {
                    const uint32_t u = i - 5;
                    if (u < NKV) {
                        const uint32_t blk = u / 4;
                        const bool isv = blk >= 2 * NSTEP - LA || (blk >= LA && ((blk - LA) & 1));
                        const uint32_t step = blk < LA ? blk : blk >= 2 * NSTEP - LA ? blk - NSTEP : (blk - LA) / 2 + (isv ? 0 : LA);
                        const int pair = pair_of(sg, step * WPS + (u % 4) / NT);
                        map = isv ? &maps.v : &maps.k;
                        c1 = 0;
                        c2 = ((pair & 3) * NH + (pair >> 2)) * SK + (SK - WIN) + ((u % NT) * G + r) * TK;
                    } else if (i < 5) {
                        map = &maps.wq; c1 = h * 3; c2 = qd * 160 + i * 32;
                    } else if (u < NKV + 2) {
                        map = &maps.w2; c1 = qd * 5; c2 = h * 48 + (u - NKV) * 24; bytes = 7680;
                    } else {
                        map = &maps.wo; c1 = qd * 5; c2 = h * DH + (u - NKV - 2) * 32; bytes = 10240;
                    }
                } else {
                    map = i < 40 ? &maps.w1 : &maps.w3; c1 = qd * 6; c2 = (i < 40 ? i : i - 40) * 16;
                }
                const int depth = pace[1];
                const uint32_t slot = (uint32_t)i % NS, landed = i - depth;
                if (i >= NS) mbar_wait(bar_full + (NS + slot) * 8, ((uint32_t)i / NS - 1) & 1);
                mbar_expect_tx(bar_full + slot * 8, bytes);
                uint32_t dst = sb + SM_RING + slot * SLOT, fb = bar_full + slot * 8;
                asm volatile("" : "+r"(dst), "+r"(fb), "+l"(map), "+r"(c1), "+r"(c2));
                if (i >= depth) mbar_wait(bar_full + (landed % NS) * 8, (landed / NS) & 1);
                tma3d(dst, map, c1, c2, fb);
                pace[0] = landed + 1;
            }
            pace[0] = n_items - DEPTH;
        }
        return;
    }

    const int g = lane >> 2, t = lane & 3;
    uint32_t epoch;
    asm volatile("ld.relaxed.gpu.global.u32 %0, [%1];" : "=r"(epoch) : "l"(&g_sync.epoch) : "memory");

    if (warp == W_PACE) {
        const uint32_t tag = (epoch + 1u) & 1u;
        if (is_att) {
#pragma unroll
            for (int u = 0; u < WPS; u++) st_fill4(g_ml + ((sg * G + u * 16 + (lane >> 1)) * G + r) * MLS + (lane & 1) * 4, tag ^ 1u);
        }
        asm volatile("bar.sync 2, %0;" ::"n"(NTHR) : "memory");
        if (lane == 0) asm volatile("red.release.gpu.global.add.u32 [%0], 1;" ::"l"(&g_sync.inits) : "memory");
        if (!is_att) return;
        volatile int* pace = reinterpret_cast<volatile int*>(smem + SM_PACE);
        if (cta == 0 && lane == 0) asm volatile("st.relaxed.gpu.global.u32 [%0], %1;" ::"l"(&g_sync.prog[epoch & 1u]), "r"(0u) : "memory");
        int reported = 0, j = 0;
        bool due = false;
#pragma unroll 1
        for (unsigned it = 0;; it++) {
            const int landed = pace[0];
            if (j == NSTEP && landed >= ITEMS_ATT - DEPTH) {
                if (lane == 0)
                    asm volatile("red.relaxed.gpu.global.add.u32 [%0], %1;" ::"l"(&g_sync.prog[~epoch & 1u]), "r"(landed - reported) : "memory");
                return;
            }
            int sum = 0;
            constexpr int RPL = (G + 31) / 32;
            uint2 ml[WPS][RPL];
            uint32_t bad = 1u;
            unsigned n = (epoch + 1u) * NCTA;
            if (lane == 0)
                asm volatile("atom.relaxed.gpu.global.add.u32 %0, [%1], %2;"
                             : "=r"(sum) : "l"(&g_sync.prog[~epoch & 1u]), "r"(landed - reported) : "memory");
            if (due) {
#pragma unroll
                for (int u = 0; u < WPS; u++)
#pragma unroll
                    for (int k = 0; k < RPL; k++) ml[u][k] = ld_word(g_ml + (pair_of(sg, j * WPS + u) * G + k * 32 + lane % G) * MLS);
                if (j == 0) asm volatile("ld.acquire.gpu.global.u32 %0, [%1];" : "=r"(n) : "l"(&g_sync.inits) : "memory");
            }
            reported = landed;
            if (lane == 0 && P_GAIN) {
                const int lag16 = sum / (NATT / 16) - landed * 16 + P_BIAS;
                pace[1] = min(max(DEPTH + ((lag16 * P_GAIN + 128) >> 8), P_DMIN), P_DMAX);
            }
            if (due) {
                bad = 0;
#pragma unroll
                for (int u = 0; u < WPS; u++)
#pragma unroll
                    for (int k = 0; k < RPL; k++) bad |= ml[u][k].x ^ tag;
            }
            if (__all_sync(0xffffffffu, !(bad & 1u) && n == (epoch + 1u) * NCTA)) {
#pragma unroll
                for (int u = 0; u < WPS; u++) {
                    float M = -INFINITY, L = 0.f, w = 0.f;
#pragma unroll
                    for (int k = 0; k < RPL; k++) M = fmaxf(M, __uint_as_float(ml[u][k].x & ~1u));
#pragma unroll
                    for (int o = G / RPL / 2; o; o >>= 1) M = fmaxf(M, shx(M, o));
#pragma unroll
                    for (int k = 0; k < RPL; k++) {
                        const float wk = __expf(__uint_as_float(ml[u][k].x & ~1u) - M);
                        L += wk * __uint_as_float(ml[u][k].y);
                        if (k == r / 32) w = wk;
                    }
#pragma unroll
                    for (int o = G / RPL / 2; o; o >>= 1) L += shx(L, o);
                    if (lane == r % 32) reinterpret_cast<float*>(smem + SM_LS)[16 + (j & 3) * WPS + u] = __fdividef(w, L);
                }
                if (lane == r % 32) {
                    mbar_arrive(bar_full + B_WRDY + (j & 3) * 8);
                    if (j == NSTEP - 1) TS(11);
                }
                j++;
                due = false;
            }
            if (!due && j < NSTEP) due = mbar_test(bar_full + B_WTRIG + (j & 3) * 8, (j >> 2) & 1);
            __nanosleep(P_SLEEP);
            if (it > SPIN_LIMIT) __trap();
        }
    }
    if (warp > W_PROD) {
        const uint32_t tag = (epoch + 1u) & 1u;
        const int e = tid - (W_PROD + 1) * 32;
        if (is_att) {
#pragma unroll 1
            for (int i = e; i < 192; i += NXW * 32)
                st_fill4(g_qpart + (cta * NB + i / 48) * VS + (i % 48) / 6 * 32 + (i % 6) * 4, tag ^ 1u);
            st_fill4(reinterpret_cast<float*>(ocell(cta, e)), 0u);
            if (e < 32) *reinterpret_cast<uint32_t*>(smem + SM_HF + e * 16 + 12) = 0u;
        } else {
#pragma unroll 1
            for (int c = e; c < 256; c += NXW * 32) {
                const bf16* xp = x + qd * DM + (c >> 6) * 160 + ((c >> 3) & 7) * 8 + (c & 3) * 2 + ((c >> 2) & 1);
                asm volatile("st.relaxed.gpu.global.v4.f32 [%0], {%1,%2,%3,%4};"
                             ::"l"(g_acc + (qd * 32 + (c >> 3)) * ACS + (c & 7)), "f"(__bfloat162float(xp[0])),
                               "f"(__bfloat162float(xp[64])), "f"((c & 32) ? 0.f : __bfloat162float(xp[128])), "f"(0.f) : "memory");
            }
        }
        asm volatile("bar.sync 2, %0;" ::"n"(NTHR) : "memory");
        if (!is_att) return;
        {
            const uint32_t eq = (e >> 5) * 24 + min(lane, 23), xw = eq / 6, xr = eq % 6;
            mbar_wait(bar_full + B_QTRIG, 0);
            if (e == 0) TS(10);
            settle(P_QDELAY);
#pragma unroll 1
            for (int j = 0; j < NSTEP; j++) {
                uint4 v[WPS][4];
                uint32_t bad;
                unsigned spin = 0;
                do {
#pragma unroll
                    for (int u = 0; u < WPS; u++) {
                        const int pair = pair_of(sg, j * WPS + u);
                        const float* src = g_qpart + ((pair >> 2) * 4 * NB + (pair & 3)) * VS + xw * 32 + xr * 4;
#pragma unroll
                        for (int k = 0; k < 4; k++) v[u][k] = ld_word2(src + k * NB * VS);
                    }
                    bad = 0;
#pragma unroll
                    for (int u = 0; u < WPS; u++)
#pragma unroll
                        for (int k = 0; k < 4; k++) bad |= (v[u][k].x ^ tag) | (v[u][k].z ^ tag);
                    if (++spin > SPIN_LIMIT) __trap();
                } while (bad & 1u);
#define SUM4(c) ((__uint_as_float(v[u][0].c) + __uint_as_float(v[u][1].c)) + (__uint_as_float(v[u][2].c) + __uint_as_float(v[u][3].c)))
#pragma unroll
                for (int u = 0; u < WPS; u++) {
                    unsigned char* dst = smem + SM_QS + (j * WPS + u) * (DH * 2) + (xr & 1) * 192 + ((xr >> 1) * 8 + xw) * 4;
                    *reinterpret_cast<uint32_t*>(dst) = pack_bf2(SUM4(x), SUM4(y));
                    *reinterpret_cast<uint32_t*>(dst + 96) = pack_bf2(SUM4(z), SUM4(w));
                }
#undef SUM4
                __syncwarp();
                if (lane == 0) mbar_arrive(bar_full + B_QRDY + j * 8);
                if (e == 0 && j == 0) TS(12);
            }
        }
        bool have_h = false;
#pragma unroll 1
        for (int b = 0; b <= NB; b++) {
            if (!have_h && (b == NB || order_of(r, b) >= HSTEP * WPS)) {
                have_h = true;
                mbar_wait(bar_full + B_HTRIG, 0);
#pragma unroll 1
                for (int i = e; i < 96; i += NXW * 32) {
                    const int k = (i % 24) * 2;
                    uint2 v;
                    unsigned spin = 0;
                    do {
                        v = ld_word(g_h + i / 24 * FF + h * 48 + k);
                        if (++spin > SPIN_LIMIT) __trap();
                    } while ((v.x ^ tag) & 1u);
                    *reinterpret_cast<uint32_t*>(smem + SM_HF + k / 24 * 256 + i / 24 * 64 + frag_off(k % 24)) = __byte_perm(v.x, v.y, 0x7632);
                }
                __syncwarp();
                if (lane == 0) mbar_arrive(bar_full + B_HRDY);
            }
            if (b == NB) break;
            const float4* src = ocell(h * NB + b, e);
            uint32_t dst = sb + SM_OF + (e >> 5) * 256 + b * 64 + frag_off(lane), ordy = bar_full + B_ORDY;
            asm volatile("" : "+r"(dst), "+l"(src), "+r"(ordy));
            mbar_wait(bar_full + B_OTRIG + b * 8, 0);
            const int pause = order_of(r, b) < G - WPS ? P_SETTLE : 0;
            unsigned spin = 0;
            float o0, o1, o2, n;
            do {
                settle(pause);
                asm volatile("atom.relaxed.gpu.global.add.v4.f32 {%0,%1,%2,%3}, [%4], {%5,%5,%5,%5};"
                             : "=f"(o0), "=f"(o1), "=f"(o2), "=f"(n) : "l"(src), "f"(0.f) : "memory");
                asm volatile("st.shared.u16 [%0], %1;\nst.shared.u16 [%0+512], %2;\nst.shared.u16 [%0+1024], %3;"
                             ::"r"(dst), "h"(__bfloat16_as_ushort(__float2bfloat16_rn(o0))),
                               "h"(__bfloat16_as_ushort(__float2bfloat16_rn(o1))), "h"(__bfloat16_as_ushort(__float2bfloat16_rn(o2))) : "memory");
                if (++spin > SPIN_LIMIT) __trap();
            } while (n != (float)G);
            __syncwarp();
            if (lane == 0) mbar_arrive(ordy);
        }
        return;
    }

    if (warp < NB) {
        uint2 raw[5];
#pragma unroll
        for (int i = 0; i < 5; i++) raw[i] = __ldg(reinterpret_cast<const uint2*>(x + warp * DM) + i * 32 + lane);
        float s = 0.f;
#pragma unroll
        for (int i = 0; i < 5; i++) s += (bf_lo(raw[i].x) + bf_hi(raw[i].x)) + (bf_lo(raw[i].y) + bf_hi(raw[i].y));
#pragma unroll
        for (int o = 16; o; o >>= 1) s += shx(s, o);
        const float mean = s * (1.0f / DM);
        float q2 = 0.f;
#pragma unroll
        for (int i = 0; i < 5; i++) {
            const float d0 = bf_lo(raw[i].x) - mean, d1 = bf_hi(raw[i].x) - mean;
            const float d2 = bf_lo(raw[i].y) - mean, d3 = bf_hi(raw[i].y) - mean;
            q2 += (d0 * d0 + d1 * d1) + (d2 * d2 + d3 * d3);
        }
#pragma unroll
        for (int o = 16; o; o >>= 1) q2 += shx(q2, o);
        const float mb = bf_round(mean);
        const float rs = __frcp_rn(bf_round(__fsqrt_rn(bf_round(bf_round(q2 * (1.0f / DM)) + 1e-5f))));
        const uint32_t k = (lane * 4) & 31;
        unsigned char* dst = smem + SM_XF + warp * 64 +
            (is_att ? (lane >> 3) * 256 + frag_off(k) : (lane >> 2) * 256 + frag_off(k & 15));
        const uint32_t step = is_att ? 1024 : 2048;
#pragma unroll
        for (int i = 0; i < 5; i++) {
            const uint32_t d0 = pack_bf2(bf_lo(raw[i].x) - mb, bf_hi(raw[i].x) - mb);
            const uint32_t d1 = pack_bf2(bf_lo(raw[i].y) - mb, bf_hi(raw[i].y) - mb);
            *reinterpret_cast<uint32_t*>(dst + i * step) = pack_bf2(bf_lo(d0) * rs, bf_hi(d0) * rs);
            *reinterpret_cast<uint32_t*>(dst + i * step + 16) = pack_bf2(bf_lo(d1) * rs, bf_hi(d1) * rs);
        }
    }
    asm volatile("bar.sync 2, %0;" ::"n"(NTHR) : "memory");
    uint32_t tag = (epoch + 1u) & 1u;
    asm volatile("" : "+r"(tag));
    if (tid == 0) TS(3);

    Ring ring{bar_full, sb + SM_RING, 0u, bar_full};
    float lo[3][4] = {}, hi[3][4] = {};
    uint32_t off[3];
    const uint32_t a_lane = (g & 3) * 64 + t * 16;

    if (is_att) {
        float* lsum = reinterpret_cast<float*>(smem + SM_LS);
#pragma unroll 1
        for (int j = -1; j < NSTEP + LA; j++) {
            if (j >= 0 && j < NSTEP) {
                constexpr int WW = NCW / WPS;
                const int win = j * WPS + warp / WW;
                uint32_t qf[6][4];
                mbar_wait(bar_full + B_QRDY + j * 8, 0);
                if (j == 0 && tid == 0) TS(6);
#pragma unroll
                for (int i = 0; i < 6; i++) lds128(sb + SM_QS + win * (DH * 2) + t * 96 + i * 16, qf[i]);
                const uint32_t key = (warp & 1) * 16 + (lane & 15);
                const uint32_t item = 5 + (j + max(j - LA, 0)) * 4 + (warp >> 1), slot = item % NS;
#pragma unroll
                for (int s = 0; s < 3; s++)
                    off[s] = sb + SM_RING + slot * SLOT + key * 384 + s * 128 + (((lane >> 4) ^ ((3 * key + s) & 7)) << 4);
                pin3(off);
                mbar_wait(bar_full + slot * 8, (item / NS) & 1);
                float c[3][4] = {};
#pragma unroll
                for (int dq = 0; dq < 4; dq++)
#pragma unroll
                    for (int s = 0; s < 3; s++) {
                        uint32_t a[4];
                        ldsm_x4(off[s] ^ (dq << 5), a);
                        mma16816(c[s], a, qf[s * 2 + (dq >> 1)][(dq & 1) * 2], qf[s * 2 + (dq >> 1)][(dq & 1) * 2 + 1]);
                    }
                __syncwarp();
                if (lane == 0)
                    asm volatile("mbarrier.arrive.shared::cta.b64 _, [%0], %1;" ::"r"(bar_full + (NS + slot) * 8), "n"(NCW / 2) : "memory");
                ring.skip(4);
                const float raw = (t & 1) ? (c[0][2] + c[1][2]) + c[2][2] : (c[0][0] + c[1][0]) + c[2][0];
                const float sv = bf_round(bf_round(raw) * 0.07216878364870323f);
                if (tid == 0 && j == NSTEP - 1) TS(14);
                float m = fmaxf(sv, shx(sv, 1));
#pragma unroll
                for (int o = 4; o < 32; o <<= 1) m = fmaxf(m, shx(m, o));
                if (lane == 0) lsum[8 + warp] = m;
                cons_bar();
#pragma unroll
                for (int i = 0; i < WW; i += 2) {
                    const float2 m2 = *reinterpret_cast<const float2*>(lsum + 8 + warp / WW * WW + i);
                    m = fmaxf(m, fmaxf(m2.x, m2.y));
                }
                float l = __expf(sv - m);
                *reinterpret_cast<bf16*>(smem + SM_PF + ((j & 3) * 4 + (warp >> 1)) * 64 + frag_off((warp & 1) * 16 + (t & 1) * 8 + g)) =
                    __float2bfloat16_rn(l);
                l += shx(l, 1);
#pragma unroll
                for (int o = 4; o < 32; o <<= 1) l += shx(l, o);
                if (lane == 0) lsum[warp] = l;
                cons_bar();
                if (tid % (WW * 32) < 4) {
                    l = 0.f;
#pragma unroll
                    for (int i = 0; i < WW; i += 2) {
                        const float2 l2 = *reinterpret_cast<const float2*>(lsum + warp + i);
                        l += l2.x + l2.y;
                    }
                    st_tag2(g_ml + (pair_of(sg, win) * G + r) * MLS + lane * 2, m, l, tag);
                    if (tid == 0) {
                        mbar_arrive(bar_full + B_WTRIG + (j & 3) * 8);
                        if (j == HSTEP) mbar_arrive(bar_full + B_HTRIG);
                    }
                }
                if (tid == 0 && j == NSTEP - 1) TS(13);
                if (j < LA) continue;
            }
            const bool kv = j >= 0;
            const uint32_t jv = j - LA;
#pragma unroll
            for (int s = 0; s < 3; s++) off[s] = lane * 384 + s * 128 + ((warp ^ ((3 * lane + s) & 7)) << 4);
#pragma unroll 1
            for (int u = 0; u < (kv ? WPS : 1); u++) {
                const int pair = pair_of(sg, jv * WPS + u);
                uint32_t trig = !kv ? bar_full + B_QTRIG : (pair >> 2) == h ? bar_full + B_OTRIG + (pair & 3) * 8 : 0;
                if (tid != 0) trig = 0;
                float4* oacc = ocell(pair, warp * 8 + 2 * t + (g & 1));
                uint32_t wrdy = bar_full + B_WRDY + (jv & 3) * 8;
                asm volatile("" : "+l"(oacc), "+r"(trig), "+r"(wrdy));
                gemv_loop(ring, kv ? NT : 5,
                          kv ? sb + SM_PF + ((jv & 3) * 4 + u * NT) * 64 + t * 16 : sb + SM_XF + qd * 5 * 256 + a_lane,
                          kv ? 64 : 256, off, lo, hi, lane);
                if (kv) {
                    mbar_wait(wrdy, (jv >> 2) & 1);
                    const float w = lsum[16 + (jv & 3) * WPS + u];
                    if (g < 2)
                        asm volatile("red.relaxed.gpu.global.add.v4.f32 [%0], {%1,%2,%3,%4};"
                                     ::"l"(oacc), "f"(w * (g ? lo[0][1] + hi[0][3] : lo[0][0] + hi[0][2])),
                                       "f"(w * (g ? lo[1][1] + hi[1][3] : lo[1][0] + hi[1][2])),
                                       "f"(w * (g ? lo[2][1] + hi[2][3] : lo[2][0] + hi[2][2])), "f"(1.0f) : "memory");
                } else if (g < NB) {
#pragma unroll
                    for (int s = 0; s < 3; s++)
                        st_tag2(g_qpart + (cta * NB + g) * VS + warp * 32 + 2 * t + s * 8, lo[s][0] + hi[s][2], lo[s][1] + hi[s][3], tag);
                }
                if (trig) mbar_arrive(trig);
            }
            const bool pass = j == NSTEP + LA - 1;
            if (pass && tid == 0) TS(5);
            if (kv && !pass && j != P_DRY) continue;
            if (tid == 0 && j < 0) TS(4);

            {
                constexpr int I0 = 5 + NKV;
                static_assert(((I0 / NS) & 1) == 0 && I0 / NS == (I0 + 7) / NS, "tail items complete an even phase");
                const uint32_t done = bar_full + B_QTRIG;
                uint32_t fb = pass ? bar_full + (I0 % NS) * 8 : done, fs = pass ? 8 : 0, ordy = pass ? bar_full + B_ORDY : done;
                uint32_t off2[3], a[8][4], b[8][3][4], a_addr = sb + SM_HF + a_lane;
#pragma unroll
                for (int s = 0; s < 3; s++) {
                    const uint32_t w64 = lane * 320 + (warp + 8 * s) * 16;
                    off[s] = sb + SM_RING + (I0 % NS) * SLOT + (w64 ^ (((w64 >> 7) & 3) << 4));
                    off2[s] = lane < 24 ? off[s] : off[s] - 8 * 320;
#pragma unroll
                    for (int e = 0; e < 4; e++) { lo[s][e] = 0.f; hi[s][e] = 0.f; }
                }
                const float4* accp = g_acc + (((g & 3) * 4 + qd) * NCW + warp) * ACS + (g >> 2) * 4 + t;
                bf16* outp = out + (g & 3) * DM + qd * 160 + warp * 8 + 2 * t + (g >> 2);
                pin3(off);
                asm volatile("" : "+l"(accp), "+l"(outp), "+r"(a_addr), "+r"(ordy), "+r"(fb), "+r"(fs));
                auto load_b = [&](int i, bool& next) {
                    if (!next) mbar_wait(fb + i * fs, 0);
                    if (i < 7) next = mbar_test(fb + (i + 1) * fs, 0);
#pragma unroll
                    for (int s = 0; s < 3; s++)
                        if (s < 2 || warp < 4) ldsm_x4_t((i < 2 ? off2[s] : off[s]) + i * SLOT, b[i][s]);
                };
                auto mul = [&](int i) {
#pragma unroll
                    for (int s = 0; s < 3; s++)
                        if (s < 2 || warp < 4) { mma16816(lo[s], a[i], b[i][s][0], b[i][s][1]); mma16816(hi[s], a[i], b[i][s][2], b[i][s][3]); }
                };
                bool next = mbar_test(fb, 0);
                mbar_wait(pass ? bar_full + B_HRDY : done, 0);
                lds128(a_addr, a[0]);
                lds128(a_addr + 256, a[1]);
                load_b(0, next);
                load_b(1, next);
                bool early = mbar_test(ordy, 0);
                mul(0);
                mul(1);
                if (pass && tid == 0) TS(31);
                unsigned spin = 0;
                while (!early && !mbar_test(fb + P_DEC * fs, 0)) {
                    early = mbar_test(ordy, 0);
                    if (++spin > SPIN_LIMIT) __trap();
                }
                if (pass ? __all_sync(0xffffffffu, early) : j < 0) {
                    if (pass && tid == 0) TS(7);
#pragma unroll
                    for (int i = 2; i < 8; i++) lds128(a_addr + i * 256, a[i]);
                    load_b(2, next);
#pragma unroll
                    for (int i = 2; i < 7; i++) { load_b(i + 1, next); mul(i); }
                    mul(7);
                } else {
#pragma unroll
                    for (int i = 2; i < 8; i++) load_b(i, next);
                    mbar_wait(ordy, 0);
                    if (pass && tid == 0) TS(7);
#pragma unroll
                    for (int i = 2; i < 8; i++) lds128(a_addr + i * 256, a[i]);
#pragma unroll
                    for (int i = 2; i < 8; i++) mul(i);
                }
                if (pass && tid == 0) TS(8);
                add_out(accp, outp, lo, hi, g >= NB, warp < 4, pass, epoch);
            }
        }
        if (tid == 0) { TS(9); TS_DUMP(3, 32); }
    } else {
        float gate[6][2];
#pragma unroll
        for (int s = 0; s < 3; s++) {
            const uint32_t r128 = (lane & 15) * 6 + 2 * s + (lane >> 4);
            off[s] = r128 * 128 + ((warp ^ (r128 & 7)) << 4);
        }
#pragma unroll 1
        for (int ps = 0; ps < 2; ps++) {
#pragma unroll
            for (int s = 0; s < 3; s++) {
                gate[2 * s][0] = lo[s][0]; gate[2 * s][1] = lo[s][1];
                gate[2 * s + 1][0] = hi[s][0]; gate[2 * s + 1][1] = hi[s][1];
            }
            gemv_loop(ring, 40, sb + SM_XF + a_lane, 256, off, lo, hi, lane);
        }
#pragma unroll
        for (int p = 0; p < 6; p++) {
            float hv[2];
#pragma unroll
            for (int e = 0; e < 2; e++) {
                const float gt = bf_round(gate[p][e]);
                hv[e] = bf_round(bf_round(__fdividef(gt, 1.0f + __expf(-gt))) * bf_round((p & 1) ? hi[p >> 1][e] : lo[p >> 1][e]));
            }
            if (g < NB) st_tag2(g_h + g * FF + qd * 384 + p * 64 + warp * 8 + 2 * t, hv[0], hv[1], tag);
        }
        if (tid == 0) { TS(9); TS_DUMP(3, 10); }
    }
}

typedef CUresult (*EncodeFn)(CUtensorMap*, CUtensorMapDataType, cuuint32_t, void*, const cuuint64_t*, const cuuint64_t*,
                             const cuuint32_t*, const cuuint32_t*, CUtensorMapInterleave, CUtensorMapSwizzle,
                             CUtensorMapL2promotion, CUtensorMapFloatOOBfill);

void make_map(EncodeFn enc, CUtensorMap* m, const void* p, uint64_t rows, uint64_t cols, uint32_t inner, uint32_t parts,
              uint32_t box_rows) {
    const cuuint64_t dims[3] = {inner, cols / inner, rows};
    const cuuint64_t strides[2] = {inner * 2ull, cols * 2ull};
    const cuuint32_t box[3] = {inner, parts, box_rows};
    const cuuint32_t es[3] = {1, 1, 1};
    enc(m, CU_TENSOR_MAP_DATA_TYPE_BFLOAT16, 3, const_cast<void*>(p), dims, strides, box, es, CU_TENSOR_MAP_INTERLEAVE_NONE,
        inner == 64 ? CU_TENSOR_MAP_SWIZZLE_128B : CU_TENSOR_MAP_SWIZZLE_64B, CU_TENSOR_MAP_L2_PROMOTION_NONE,
        CU_TENSOR_MAP_FLOAT_OOB_FILL_NONE);
}

}

extern "C" void kernel_launch(void* const* d_in, const int* in_sizes, int n_in, void* d_out, int out_size) {
    (void)in_sizes; (void)n_in; (void)out_size;
    static EncodeFn enc = nullptr;
    if (!enc) {
        void* fn = nullptr;
        cudaDriverEntryPointQueryResult qr;
        cudaGetDriverEntryPoint("cuTensorMapEncodeTiled", &fn, cudaEnableDefault, &qr);
        enc = (EncodeFn)fn;
        cudaFuncSetAttribute(fused_decode_kernel, cudaFuncAttributeMaxDynamicSharedMemorySize, SM_TOTAL);
    }
    Maps maps;
    make_map(enc, &maps.k, d_in[1], (uint64_t)NB * NH * SK, DH, 64, 3, TK);
    make_map(enc, &maps.v, d_in[2], (uint64_t)NB * NH * SK, DH, 64, 3, TK);
    make_map(enc, &maps.wq, d_in[3], DM, NH * DH, 64, 3, 32);
    make_map(enc, &maps.wo, d_in[4], NH * DH, DM, 32, 5, 32);
    make_map(enc, &maps.w1, d_in[6], DM, FF, 64, 6, 16);
    make_map(enc, &maps.w3, d_in[7], DM, FF, 64, 6, 16);
    make_map(enc, &maps.w2, d_in[8], FF, DM, 32, 5, 24);
    fused_decode_kernel<<<NCTA, NTHR, SM_TOTAL>>>((const char*)d_in[3], (const bf16*)d_in[0], (bf16*)d_out, maps);
}
```

```cpp
#include <cuda_runtime.h>
#include <cuda.h>
#include <cuda_bf16.h>
#include <stdint.h>

namespace {

typedef __nv_bfloat16 bf16;

constexpr int NB = 4, DM = 640, NH = 32, DH = 192, SK = 8192, WIN = 2048, FF = 1536;

#define P_G 32
#define P_DEPTH 4
#define P_DEPTH_FFN 5
#define P_GAIN 6
#define P_BIAS 16
#define P_SLEEP 500
#define P_DMIN 3
#define P_DMAX 6
#define P_SETTLE 3000
#define P_QDELAY 1600
#define P_DRY 4
#define P_DEC 6
#define P_LA 2
#define P_MLS 8
#define P_OAL 72
#define P_PF 64
#define P_NS 16

constexpr int G = P_G;
constexpr int TK = 32;
constexpr int NT = WIN / TK / G;
constexpr int NSTEP = 16;
constexpr int WPS = G / NSTEP;
constexpr int LA = P_LA;
constexpr int MLS = P_MLS;
constexpr int OAL = P_OAL;
constexpr int HSTEP = 11;
constexpr int NS = P_NS;
constexpr int SLOT = 12288;
constexpr int DEPTH = P_DEPTH;
#define P_D0 5
constexpr int DEPTH0 = P_D0;
static_assert(DEPTH0 <= 5, "DEPTH0");
constexpr int NATT = 128, NFFN = 4, NCTA = NATT + NFFN;
constexpr int NCW = 8;
constexpr int NXW = 2;
constexpr int W_PROD = NCW, W_PACE = NCW + 1 + NXW;
constexpr int NTHR = (W_PACE + 1) * 32;
constexpr int NSRC = NH;
constexpr int VS = 256;
#define P_ACS 40
constexpr int ACS = P_ACS;
static_assert(G == 16 || G == 32 || G == 64, "G");

constexpr int SM_RING = 0;
constexpr int SM_XF = SM_RING + NS * SLOT;
constexpr int SM_QS = SM_XF + 20 * 256;
constexpr int SM_PF = SM_QS + G * DH * 2;
constexpr int SM_HF = SM_PF + 4 * 4 * 64;
constexpr int SM_OF = SM_HF + 2 * 256;
constexpr int SM_LS = SM_OF + 6 * 256;
constexpr int SM_ATT_END = SM_LS + 128;
constexpr int SM_FFN_END = SM_XF + 40 * 256;
constexpr int SM_BAR = SM_ATT_END > SM_FFN_END ? SM_ATT_END : SM_FFN_END;
constexpr int B_QRDY = 2 * NS * 8, B_ORDY = B_QRDY + NSTEP * 8, B_OTRIG = B_ORDY + 8, B_QTRIG = B_OTRIG + 32,
              B_WTRIG = B_QTRIG + 8, B_WRDY = B_WTRIG + 32, B_HTRIG = B_WRDY + 32, B_HRDY = B_HTRIG + 8,
              NBAR = 2 * NS + NSTEP + 16;
constexpr int SM_PACE = SM_BAR + NBAR * 8;
constexpr int SM_TS = SM_PACE + 8;
constexpr int SM_TOTAL = SM_TS + 256;
static_assert(SM_TOTAL <= 232448, "smem");

constexpr int NKV = 2 * NT * G;
constexpr int ITEMS_ATT = 5 + NKV + 2 + 6;
constexpr int ITEMS_FFN = 80;

struct Maps { CUtensorMap k, v, wq, wo, w1, w3, w2; };

struct alignas(32) Sync { unsigned epoch, inits, prog[2]; };
__device__ Sync g_sync;
__device__ __align__(128) float g_qpart[NATT * NB * VS];
__device__ __align__(128) float g_ml[NATT * G * MLS];
__device__ __align__(128) float g_h[NB * FF];
__device__ __align__(128) float4 g_oacc[NATT * 8 * OAL];
__device__ __align__(128) float4 g_acc[NB * 4 * NCW * ACS];
#define TS(i)
#define TS_DUMP(lo, hi)

constexpr unsigned SPIN_LIMIT = 1u << 22;

__device__ __forceinline__ void mbar_init(uint32_t bar, int cnt) {
    asm volatile("mbarrier.init.shared::cta.b64 [%0], %1;" ::"r"(bar), "r"(cnt) : "memory");
}
__device__ __forceinline__ void mbar_expect_tx(uint32_t bar, uint32_t bytes) {
    asm volatile("mbarrier.arrive.expect_tx.shared::cta.b64 _, [%0], %1;" ::"r"(bar), "r"(bytes) : "memory");
}
__device__ __forceinline__ void mbar_arrive(uint32_t bar) {
    asm volatile("mbarrier.arrive.shared::cta.b64 _, [%0];" ::"r"(bar) : "memory");
}
__device__ __forceinline__ void mbar_wait(uint32_t bar, uint32_t parity) {
    asm volatile("{\n.reg .pred p, q;\n.reg .u32 n;\nmov.u32 n, 0;\n"
                 "W: mbarrier.try_wait.parity.shared::cta.b64 p, [%0], %1;\n"
                 "@p bra D;\nadd.u32 n, n, 1;\nsetp.lt.u32 q, n, %2;\n@q bra W;\ntrap;\nD:\n}"
                 ::"r"(bar), "r"(parity), "n"(SPIN_LIMIT) : "memory");
}
__device__ __forceinline__ bool mbar_test(uint32_t bar, uint32_t parity) {
    uint32_t ok;
    asm volatile("{\n.reg .pred p;\nmbarrier.test_wait.parity.shared::cta.b64 p, [%1], %2;\nselp.u32 %0, 1, 0, p;\n}"
                 : "=r"(ok) : "r"(bar), "r"(parity) : "memory");
    return ok;
}
__device__ __forceinline__ void tma3d(uint32_t dst, const CUtensorMap* map, int c1, int c2, uint32_t bar) {
    const uint64_t pol = 0x12F0000000000000ull;
    asm volatile("cp.async.bulk.tensor.3d.shared::cluster.global.mbarrier::complete_tx::bytes.L2::cache_hint "
                 "[%0], [%1, {%2, %3, %4}], [%5], %6;"
                 ::"r"(dst), "l"(map), "r"(0), "r"(c1), "r"(c2), "r"(bar), "l"(pol) : "memory");
}
__device__ __forceinline__ void ldsm_x4(uint32_t addr, uint32_t (&r)[4]) {
    asm volatile("ldmatrix.sync.aligned.m8n8.x4.shared.b16 {%0,%1,%2,%3}, [%4];"
                 : "=r"(r[0]), "=r"(r[1]), "=r"(r[2]), "=r"(r[3]) : "r"(addr) : "memory");
}
__device__ __forceinline__ void ldsm_x4_t(uint32_t addr, uint32_t (&r)[4]) {
    asm volatile("ldmatrix.sync.aligned.m8n8.x4.trans.shared.b16 {%0,%1,%2,%3}, [%4];"
                 : "=r"(r[0]), "=r"(r[1]), "=r"(r[2]), "=r"(r[3]) : "r"(addr) : "memory");
}
__device__ __forceinline__ void lds128(uint32_t addr, uint32_t (&r)[4]) {
    asm volatile("ld.shared.v4.u32 {%0,%1,%2,%3}, [%4];"
                 : "=r"(r[0]), "=r"(r[1]), "=r"(r[2]), "=r"(r[3]) : "r"(addr) : "memory");
}
__device__ __forceinline__ void mma16816(float (&c)[4], const uint32_t (&a)[4], uint32_t b0, uint32_t b1) {
    asm volatile("mma.sync.aligned.m16n8k16.row.col.f32.bf16.bf16.f32 {%0,%1,%2,%3}, {%4,%5,%6,%7}, {%8,%9}, {%0,%1,%2,%3};"
                 : "+f"(c[0]), "+f"(c[1]), "+f"(c[2]), "+f"(c[3])
                 : "r"(a[0]), "r"(a[1]), "r"(a[2]), "r"(a[3]), "r"(b0), "r"(b1));
}
__device__ __forceinline__ void cons_bar() { asm volatile("bar.sync 1, 256;" ::: "memory"); }

__device__ __forceinline__ float bf_round(float v) { return __bfloat162float(__float2bfloat16_rn(v)); }
__device__ __forceinline__ uint32_t pack_bf2(float lo, float hi) {
    __nv_bfloat162 t = __floats2bfloat162_rn(lo, hi);
    return *reinterpret_cast<uint32_t*>(&t);
}
__device__ __forceinline__ float bf_lo(uint32_t u) { return __uint_as_float(u << 16); }
__device__ __forceinline__ float bf_hi(uint32_t u) { return __uint_as_float(u & 0xffff0000u); }
__device__ __forceinline__ float shx(float v, int o) { return __shfl_xor_sync(0xffffffffu, v, o); }

__device__ __forceinline__ uint32_t frag_off(uint32_t k) {
    return ((k >> 1) & 3) * 16 + ((k >> 3) & 1) * 8 + ((k >> 4) & 1) * 4 + (k & 1) * 2;
}

__device__ __forceinline__ void st_tag2(float* p, float a, float b, uint32_t tag) {
    asm volatile("{\n.reg .b64 w;\n.reg .b32 x;\nlop3.b32 x, %1, 0xfffffffe, %3, 0xea;\nmov.b64 w, {x, %2};\n"
                 "st.relaxed.gpu.global.b64 [%0], w;\n}"
                 ::"l"(p), "r"(__float_as_uint(a)), "r"(__float_as_uint(b)), "r"(tag) : "memory");
}
__device__ __forceinline__ void st_fill4(float* p, uint32_t v) {
    asm volatile("{\n.reg .b64 w;\nmov.b64 w, {%1, %1};\nst.relaxed.gpu.global.v2.b64 [%0], {w, w};\n}" ::"l"(p), "r"(v) : "memory");
}
__device__ __forceinline__ uint2 ld_word(const float* p) {
    uint2 v;
    asm volatile("{\n.reg .b64 w;\nld.relaxed.gpu.global.b64 w, [%2];\nmov.b64 {%0,%1}, w;\n}" : "=r"(v.x), "=r"(v.y) : "l"(p) : "memory");
    return v;
}
__device__ __forceinline__ uint4 ld_word2(const float* p) {
    uint4 v;
    asm volatile("{\n.reg .b64 w0, w1;\nld.relaxed.gpu.global.v2.b64 {w0, w1}, [%4];\nmov.b64 {%0,%1}, w0;\nmov.b64 {%2,%3}, w1;\n}"
                 : "=r"(v.x), "=r"(v.y), "=r"(v.z), "=r"(v.w) : "l"(p) : "memory");
    return v;
}

__device__ __forceinline__ void add_out(const float4* acc, bf16* out, const float (&lo)[3][4], const float (&hi)[3][4],
                                        bool odd, bool third, bool live, uint32_t epoch) {
    const float v0 = odd ? lo[0][1] + hi[0][3] : lo[0][0] + hi[0][2];
    const float v1 = odd ? lo[1][1] + hi[1][3] : lo[1][0] + hi[1][2];
    const float v2 = odd ? lo[2][1] + hi[2][3] : lo[2][0] + hi[2][2];
    float o0, o1, o2, n = 0.f;
    asm volatile("{\n.reg .pred p;\nsetp.ne.u32 p, %5, 0;\n"
                 "@p atom.relaxed.gpu.global.add.v4.f32 {%0,%1,%2,%3}, [%4], {%6,%7,%8,%9};\n}"
                 : "=f"(o0), "=f"(o1), "=f"(o2), "+f"(n)
                 : "l"(acc), "r"((uint32_t)live), "f"(v0), "f"(v1), "f"(v2), "f"(1.0f) : "memory");
    asm volatile("{\n.reg .pred p, q;\nsetp.eq.f32 p, %4, %5;\nsetp.ne.and.u32 q, %6, 0, p;\n"
                 "@p st.global.u16 [%0], %1;\n@p st.global.u16 [%0+128], %2;\n@q st.global.u16 [%0+256], %3;\n}"
                 ::"l"(out), "h"(__bfloat16_as_ushort(__float2bfloat16_rn(o0 + v0))),
                   "h"(__bfloat16_as_ushort(__float2bfloat16_rn(o1 + v1))), "h"(__bfloat16_as_ushort(__float2bfloat16_rn(o2 + v2))),
                   "f"(n), "f"((float)(NSRC - 1)), "r"((uint32_t)third) : "memory");
    if (acc == g_acc && n == (float)(NSRC - 1))
        asm volatile("st.relaxed.gpu.global.u32 [%0], %1;" ::"l"(&g_sync.epoch), "r"(epoch + 1u) : "memory");
}

__device__ __forceinline__ int pair_of(int sg, uint32_t j) { return sg * G + (j % (G / 4)) * 4 + j / (G / 4); }
__device__ __forceinline__ int order_of(int r, int b) { return b * (G / 4) + (r >> 2); }

__device__ __forceinline__ float4* ocell(uint32_t pair, uint32_t i) {
    return g_oacc + (pair * 8 + (i >> 3)) * OAL + (i & 7);
}

__device__ __forceinline__ void settle(int cycles) {
    const uint32_t t0 = (uint32_t)clock();
    while ((uint32_t)clock() - t0 < (uint32_t)cycles) __nanosleep(20);
}

struct Ring {
    uint32_t full, addr, phase, first_full;
    __device__ __forceinline__ void wait() const { mbar_wait(full, phase); }
    __device__ __forceinline__ void skip(int n) {
        full += n * 8; addr += n * SLOT;
        if (full >= first_full + NS * 8) { full -= NS * 8; addr -= NS * SLOT; phase ^= 1; }
    }
    __device__ __forceinline__ void release(int lane) {
        __syncwarp();
        if (lane == 0) mbar_arrive(full + NS * 8);
        full += 8; addr += SLOT;
        if (full == first_full + NS * 8) { full = first_full; addr -= NS * SLOT; phase ^= 1; }
    }
};

__device__ __forceinline__ void pin3(uint32_t (&v)[3]) {
    asm volatile("" : "+r"(v[0]), "+r"(v[1]), "+r"(v[2]));
}
__device__ __forceinline__ void gemv_loop(Ring& ring, int n, uint32_t a_addr, uint32_t a_step, uint32_t (&off)[3],
                                          float (&lo)[3][4], float (&hi)[3][4], int lane) {
    pin3(off);
#pragma unroll
    for (int s = 0; s < 3; s++)
#pragma unroll
        for (int e = 0; e < 4; e++) { lo[s][e] = 0.f; hi[s][e] = 0.f; }
#pragma unroll 1
    for (int it = 0; it < n; it++) {
        uint32_t a[4], b[3][4];
        lds128(a_addr, a);
        a_addr += a_step;
        ring.wait();
#pragma unroll
        for (int s = 0; s < 3; s++) ldsm_x4_t(ring.addr + off[s], b[s]);
#pragma unroll
        for (int s = 0; s < 3; s++) { mma16816(lo[s], a, b[s][0], b[s][1]); mma16816(hi[s], a, b[s][2], b[s][3]); }
        ring.release(lane);
    }
}

__global__ void __launch_bounds__(NTHR, 1)
fused_decode_kernel(const char* __restrict__ wq, const bf16* __restrict__ x, bf16* __restrict__ out,
                    const __grid_constant__ Maps maps) {
    asm volatile("{\n.reg .pred p;\n.reg .b32 t, c, a, b;\n.reg .b64 o;\n"
                 "mov.u32 t, %%tid.x;\nmov.u32 c, %%ctaid.x;\n"
                 "and.b32 a, c, 3;\nshr.u32 c, c, 2;\nmul.lo.u32 a, a, 15360;\nmad.lo.u32 a, c, 3, a;\n"
                 "shr.u32 b, t, 2;\nmad.lo.u32 a, b, 92, a;\nadd.u32 a, a, t;\nmad.wide.u32 o, a, 128, %0;\n"
                 "and.b32 b, t, 3;\nsetp.ne.u32 p, b, 3;\nsetp.lt.and.u32 p, t, %1, p;\n@p prefetch.global.L2 [o];\n}"
                 ::"l"(wq), "n"(P_PF * 4) : "memory");
    extern __shared__ __align__(1024) unsigned char smem[];
    const uint32_t sb = (uint32_t)__cvta_generic_to_shared(smem);
    const uint32_t bar_full = sb + SM_BAR;
    if (threadIdx.x == 0 && blockIdx.x < NATT) {
        TS(0);
#pragma unroll 1
        for (int i = 0; i < DEPTH0; i++) {
            mbar_init(bar_full + i * 8, 1);
            mbar_expect_tx(bar_full + i * 8, 12288);
            tma3d(sb + SM_RING + i * SLOT, &maps.wq, (blockIdx.x >> 2) * 3, (blockIdx.x & 3) * 160 + i * 32, bar_full + i * 8);
        }
        TS(1);
    }
    unsigned ptid, cta;
    asm volatile("mov.u32 %0, %%tid.x;\nmov.u32 %1, %%ctaid.x;" : "=r"(ptid), "=r"(cta));
    const int tid = ptid < 32 ? ptid + NCW * 32 : ptid < (NCW + 1) * 32 ? ptid - 32 : ptid;
    const int warp = tid >> 5, lane = tid & 31;
    const bool is_att = cta < NATT;
    const int h = cta >> 2, qd = cta & 3;
    const int sg = cta / G, r = cta % G;

    if (warp == NCW) {
        volatile int* pace = reinterpret_cast<volatile int*>(smem + SM_PACE);
        if (lane == 0) {
            if (!is_att) { TS(0); TS(1); }
            pace[0] = 0;
            pace[1] = is_att ? DEPTH : P_DEPTH_FFN;
#pragma unroll
            for (int i = 0; i < NBAR; i++)
                if (i >= DEPTH0 || !is_att)
                mbar_init(bar_full + i * 8, i < NS ? 1 : i < 2 * NS ? NCW : i < 2 * NS + NSTEP ? NXW : i == 2 * NS + NSTEP ? NXW * NB : i == NBAR - 1 ? NXW : 1);
            asm volatile("fence.mbarrier_init.release.cluster;" ::: "memory");
        }
        __syncwarp();
        asm volatile("bar.arrive 2, %0;" ::"n"(NTHR) : "memory");
        if (lane == 0) {
            const int n_items = is_att ? ITEMS_ATT : ITEMS_FFN;

            asm volatile("prefetch.tensormap [%0];" ::"l"(is_att ? &maps.k : &maps.w3) : "memory");
            asm volatile("prefetch.tensormap [%0];" ::"l"(&maps.v) : "memory");
            asm volatile("prefetch.tensormap [%0];" ::"l"(&maps.w2) : "memory");
            asm volatile("prefetch.tensormap [%0];" ::"l"(&maps.wo) : "memory");
#pragma unroll 1
            for (int i = is_att ? DEPTH0 : 0; i < n_items; i++) {
                const CUtensorMap* map;
                int c1, c2;
                uint32_t bytes = 12288;
                if (is_att) {
                    const uint32_t u = i - 5;
                    if (u < NKV) {
                        const uint32_t blk = u / 4;
                        const bool isv = blk >= 2 * NSTEP - LA || (blk >= LA && ((blk - LA) & 1));
                        const uint32_t step = blk < LA ? blk : blk >= 2 * NSTEP - LA ? blk - NSTEP : (blk - LA) / 2 + (isv ? 0 : LA);
                        const int pair = pair_of(sg, step * WPS + (u % 4) / NT);
                        map = isv ? &maps.v : &maps.k;
                        c1 = 0;
                        c2 = ((pair & 3) * NH + (pair >> 2)) * SK + (SK - WIN) + ((u % NT) * G + r) * TK;
                    } else if (i < 5) {
                        map = &maps.wq; c1 = h * 3; c2 = qd * 160 + i * 32;
                    } else if (u < NKV + 2) {
                        map = &maps.w2; c1 = qd * 5; c2 = h * 48 + (u - NKV) * 24; bytes = 7680;
                    } else {
                        map = &maps.wo; c1 = qd * 5; c2 = h * DH + (u - NKV - 2) * 32; bytes = 10240;
                    }
                } else {
                    map = i < 40 ? &maps.w1 : &maps.w3; c1 = qd * 6; c2 = (i < 40 ? i : i - 40) * 16;
                }
                const int depth = pace[1];
                const uint32_t slot = (uint32_t)i % NS, landed = i - depth;
                if (i >= NS) mbar_wait(bar_full + (NS + slot) * 8, ((uint32_t)i / NS - 1) & 1);
                mbar_expect_tx(bar_full + slot * 8, bytes);
                uint32_t dst = sb + SM_RING + slot * SLOT, fb = bar_full + slot * 8;
                asm volatile("" : "+r"(dst), "+r"(fb), "+l"(map), "+r"(c1), "+r"(c2));
                if (i >= depth) mbar_wait(bar_full + (landed % NS) * 8, (landed / NS) & 1);
                tma3d(dst, map, c1, c2, fb);
                pace[0] = landed + 1;
            }
            pace[0] = n_items - DEPTH;
        }
        return;
    }

    const int g = lane >> 2, t = lane & 3;
    uint32_t epoch;
    asm volatile("ld.relaxed.gpu.global.u32 %0, [%1];" : "=r"(epoch) : "l"(&g_sync.epoch) : "memory");

    if (warp == W_PACE) {
        const uint32_t tag = (epoch + 1u) & 1u;
        if (is_att) {
#pragma unroll
            for (int u = 0; u < WPS; u++) st_fill4(g_ml + ((sg * G + u * 16 + (lane >> 1)) * G + r) * MLS + (lane & 1) * 4, tag ^ 1u);
        }
        asm volatile("bar.sync 2, %0;" ::"n"(NTHR) : "memory");
        if (lane == 0) asm volatile("red.release.gpu.global.add.u32 [%0], 1;" ::"l"(&g_sync.inits) : "memory");
        if (!is_att) return;
        volatile int* pace = reinterpret_cast<volatile int*>(smem + SM_PACE);
        if (cta == 0 && lane == 0) asm volatile("st.relaxed.gpu.global.u32 [%0], %1;" ::"l"(&g_sync.prog[epoch & 1u]), "r"(0u) : "memory");
        int reported = 0, j = 0;
        bool due = false;
#pragma unroll 1
        for (unsigned it = 0;; it++) {
            const int landed = pace[0];
            if (j == NSTEP && landed >= ITEMS_ATT - DEPTH) {
                if (lane == 0)
                    asm volatile("red.relaxed.gpu.global.add.u32 [%0], %1;" ::"l"(&g_sync.prog[~epoch & 1u]), "r"(landed - reported) : "memory");
                return;
            }
            int sum = 0;
            constexpr int RPL = (G + 31) / 32;
            uint2 ml[WPS][RPL];
            uint32_t bad = 1u;
            unsigned n = (epoch + 1u) * NCTA;
            if (lane == 0)
                asm volatile("atom.relaxed.gpu.global.add.u32 %0, [%1], %2;"
                             : "=r"(sum) : "l"(&g_sync.prog[~epoch & 1u]), "r"(landed - reported) : "memory");
            if (due) {
#pragma unroll
                for (int u = 0; u < WPS; u++)
#pragma unroll
                    for (int k = 0; k < RPL; k++) ml[u][k] = ld_word(g_ml + (pair_of(sg, j * WPS + u) * G + k * 32 + lane % G) * MLS);
                if (j == 0) asm volatile("ld.acquire.gpu.global.u32 %0, [%1];" : "=r"(n) : "l"(&g_sync.inits) : "memory");
            }
            reported = landed;
            if (lane == 0 && P_GAIN) {
                const int lag16 = sum / (NATT / 16) - landed * 16 + P_BIAS;
                pace[1] = min(max(DEPTH + ((lag16 * P_GAIN + 128) >> 8), P_DMIN), P_DMAX);
            }
            if (due) {
                bad = 0;
#pragma unroll
                for (int u = 0; u < WPS; u++)
#pragma unroll
                    for (int k = 0; k < RPL; k++) bad |= ml[u][k].x ^ tag;
            }
            if (__all_sync(0xffffffffu, !(bad & 1u) && n == (epoch + 1u) * NCTA)) {
#pragma unroll
                for (int u = 0; u < WPS; u++) {
                    float M = -INFINITY, L = 0.f, w = 0.f;
#pragma unroll
                    for (int k = 0; k < RPL; k++) M = fmaxf(M, __uint_as_float(ml[u][k].x & ~1u));
#pragma unroll
                    for (int o = G / RPL / 2; o; o >>= 1) M = fmaxf(M, shx(M, o));
#pragma unroll
                    for (int k = 0; k < RPL; k++) {
                        const float wk = __expf(__uint_as_float(ml[u][k].x & ~1u) - M);
                        L += wk * __uint_as_float(ml[u][k].y);
                        if (k == r / 32) w = wk;
                    }
#pragma unroll
                    for (int o = G / RPL / 2; o; o >>= 1) L += shx(L, o);
                    if (lane == r % 32) reinterpret_cast<float*>(smem + SM_LS)[16 + (j & 3) * WPS + u] = __fdividef(w, L);
                }
                if (lane == r % 32) {
                    mbar_arrive(bar_full + B_WRDY + (j & 3) * 8);
                    if (j == NSTEP - 1) TS(11);
                }
                j++;
                due = false;
            }
            if (!due && j < NSTEP) due = mbar_test(bar_full + B_WTRIG + (j & 3) * 8, (j >> 2) & 1);
            __nanosleep(P_SLEEP);
            if (it > SPIN_LIMIT) __trap();
        }
    }
    if (warp > W_PROD) {
        const uint32_t tag = (epoch + 1u) & 1u;
        const int e = tid - (W_PROD + 1) * 32;
        if (is_att) {
#pragma unroll 1
            for (int i = e; i < 192; i += NXW * 32)
                st_fill4(g_qpart + (cta * NB + i / 48) * VS + (i % 48) / 6 * 32 + (i % 6) * 4, tag ^ 1u);
            st_fill4(reinterpret_cast<float*>(ocell(cta, e)), 0u);
            if (e < 32) *reinterpret_cast<uint32_t*>(smem + SM_HF + e * 16 + 12) = 0u;
        } else {
#pragma unroll 1
            for (int c = e; c < 256; c += NXW * 32) {
                const bf16* xp = x + qd * DM + (c >> 6) * 160 + ((c >> 3) & 7) * 8 + (c & 3) * 2 + ((c >> 2) & 1);
                asm volatile("st.relaxed.gpu.global.v4.f32 [%0], {%1,%2,%3,%4};"
                             ::"l"(g_acc + (qd * 32 + (c >> 3)) * ACS + (c & 7)), "f"(__bfloat162float(xp[0])),
                               "f"(__bfloat162float(xp[64])), "f"((c & 32) ? 0.f : __bfloat162float(xp[128])), "f"(0.f) : "memory");
            }
        }
        asm volatile("bar.sync 2, %0;" ::"n"(NTHR) : "memory");
        if (!is_att) return;
        {
            const uint32_t eq = (e >> 5) * 24 + min(lane, 23), xw = eq / 6, xr = eq % 6;
            mbar_wait(bar_full + B_QTRIG, 0);
            if (e == 0) TS(10);
            settle(P_QDELAY);
#pragma unroll 1
            for (int j = 0; j < NSTEP; j++) {
                uint4 v[WPS][4];
                uint32_t bad;
                unsigned spin = 0;
                do {
#pragma unroll
                    for (int u = 0; u < WPS; u++) {
                        const int pair = pair_of(sg, j * WPS + u);
                        const float* src = g_qpart + ((pair >> 2) * 4 * NB + (pair & 3)) * VS + xw * 32 + xr * 4;
#pragma unroll
                        for (int k = 0; k < 4; k++) v[u][k] = ld_word2(src + k * NB * VS);
                    }
                    bad = 0;
#pragma unroll
                    for (int u = 0; u < WPS; u++)
#pragma unroll
                        for (int k = 0; k < 4; k++) bad |= (v[u][k].x ^ tag) | (v[u][k].z ^ tag);
                    if (++spin > SPIN_LIMIT) __trap();
                } while (bad & 1u);
#define SUM4(c) ((__uint_as_float(v[u][0].c) + __uint_as_float(v[u][1].c)) + (__uint_as_float(v[u][2].c) + __uint_as_float(v[u][3].c)))
#pragma unroll
                for (int u = 0; u < WPS; u++) {
                    unsigned char* dst = smem + SM_QS + (j * WPS + u) * (DH * 2) + (xr & 1) * 192 + ((xr >> 1) * 8 + xw) * 4;
                    *reinterpret_cast<uint32_t*>(dst) = pack_bf2(SUM4(x), SUM4(y));
                    *reinterpret_cast<uint32_t*>(dst + 96) = pack_bf2(SUM4(z), SUM4(w));
                }
#undef SUM4
                __syncwarp();
                if (lane == 0) mbar_arrive(bar_full + B_QRDY + j * 8);
                if (e == 0 && j == 0) TS(12);
            }
        }
        bool have_h = false;
#pragma unroll 1
        for (int b = 0; b <= NB; b++) {
            if (!have_h && (b == NB || order_of(r, b) >= HSTEP * WPS)) {
                have_h = true;
                mbar_wait(bar_full + B_HTRIG, 0);
#pragma unroll 1
                for (int i = e; i < 96; i += NXW * 32) {
                    const int k = (i % 24) * 2;
                    uint2 v;
                    unsigned spin = 0;
                    do {
                        v = ld_word(g_h + i / 24 * FF + h * 48 + k);
                        if (++spin > SPIN_LIMIT) __trap();
                    } while ((v.x ^ tag) & 1u);
                    *reinterpret_cast<uint32_t*>(smem + SM_HF + k / 24 * 256 + i / 24 * 64 + frag_off(k % 24)) = __byte_perm(v.x, v.y, 0x7632);
                }
                __syncwarp();
                if (lane == 0) mbar_arrive(bar_full + B_HRDY);
            }
            if (b == NB) break;
            const float4* src = ocell(h * NB + b, e);
            uint32_t dst = sb + SM_OF + (e >> 5) * 256 + b * 64 + frag_off(lane), ordy = bar_full + B_ORDY;
            asm volatile("" : "+r"(dst), "+l"(src), "+r"(ordy));
            mbar_wait(bar_full + B_OTRIG + b * 8, 0);
            const int pause = order_of(r, b) < G - WPS ? P_SETTLE : 0;
            unsigned spin = 0;
            float o0, o1, o2, n;
            do {
                settle(pause);
                asm volatile("atom.relaxed.gpu.global.add.v4.f32 {%0,%1,%2,%3}, [%4], {%5,%5,%5,%5};"
                             : "=f"(o0), "=f"(o1), "=f"(o2), "=f"(n) : "l"(src), "f"(0.f) : "memory");
                asm volatile("st.shared.u16 [%0], %1;\nst.shared.u16 [%0+512], %2;\nst.shared.u16 [%0+1024], %3;"
                             ::"r"(dst), "h"(__bfloat16_as_ushort(__float2bfloat16_rn(o0))),
                               "h"(__bfloat16_as_ushort(__float2bfloat16_rn(o1))), "h"(__bfloat16_as_ushort(__float2bfloat16_rn(o2))) : "memory");
                if (++spin > SPIN_LIMIT) __trap();
            } while (n != (float)G);
            __syncwarp();
            if (lane == 0) mbar_arrive(ordy);
        }
        return;
    }

    if (warp < NB) {
        uint2 raw[5];
#pragma unroll
        for (int i = 0; i < 5; i++) raw[i] = __ldg(reinterpret_cast<const uint2*>(x + warp * DM) + i * 32 + lane);
        float s = 0.f;
#pragma unroll
        for (int i = 0; i < 5; i++) s += (bf_lo(raw[i].x) + bf_hi(raw[i].x)) + (bf_lo(raw[i].y) + bf_hi(raw[i].y));
#pragma unroll
        for (int o = 16; o; o >>= 1) s += shx(s, o);
        const float mean = s * (1.0f / DM);
        float q2 = 0.f;
#pragma unroll
        for (int i = 0; i < 5; i++) {
            const float d0 = bf_lo(raw[i].x) - mean, d1 = bf_hi(raw[i].x) - mean;
            const float d2 = bf_lo(raw[i].y) - mean, d3 = bf_hi(raw[i].y) - mean;
            q2 += (d0 * d0 + d1 * d1) + (d2 * d2 + d3 * d3);
        }
#pragma unroll
        for (int o = 16; o; o >>= 1) q2 += shx(q2, o);
        const float mb = bf_round(mean);
        const float rs = __frcp_rn(bf_round(__fsqrt_rn(bf_round(bf_round(q2 * (1.0f / DM)) + 1e-5f))));
        const uint32_t k = (lane * 4) & 31;
        unsigned char* dst = smem + SM_XF + warp * 64 +
            (is_att ? (lane >> 3) * 256 + frag_off(k) : (lane >> 2) * 256 + frag_off(k & 15));
        const uint32_t step = is_att ? 1024 : 2048;
#pragma unroll
        for (int i = 0; i < 5; i++) {
            const uint32_t d0 = pack_bf2(bf_lo(raw[i].x) - mb, bf_hi(raw[i].x) - mb);
            const uint32_t d1 = pack_bf2(bf_lo(raw[i].y) - mb, bf_hi(raw[i].y) - mb);
            *reinterpret_cast<uint32_t*>(dst + i * step) = pack_bf2(bf_lo(d0) * rs, bf_hi(d0) * rs);
            *reinterpret_cast<uint32_t*>(dst + i * step + 16) = pack_bf2(bf_lo(d1) * rs, bf_hi(d1) * rs);
        }
    }
    asm volatile("bar.sync 2, %0;" ::"n"(NTHR) : "memory");
    uint32_t tag = (epoch + 1u) & 1u;
    asm volatile("" : "+r"(tag));
    if (tid == 0) TS(3);

    Ring ring{bar_full, sb + SM_RING, 0u, bar_full};
    float lo[3][4] = {}, hi[3][4] = {};
    uint32_t off[3];
    const uint32_t a_lane = (g & 3) * 64 + t * 16;

    if (is_att) {
        float* lsum = reinterpret_cast<float*>(smem + SM_LS);
#pragma unroll 1
        for (int j = -1; j < NSTEP + LA; j++) {
            if (j >= 0 && j < NSTEP) {
                constexpr int WW = NCW / WPS;
                const int win = j * WPS + warp / WW;
                uint32_t qf[6][4];
                mbar_wait(bar_full + B_QRDY + j * 8, 0);
                if (j == 0 && tid == 0) TS(6);
#pragma unroll
                for (int i = 0; i < 6; i++) lds128(sb + SM_QS + win * (DH * 2) + t * 96 + i * 16, qf[i]);
                const uint32_t key = (warp & 1) * 16 + (lane & 15);
                const uint32_t item = 5 + (j + max(j - LA, 0)) * 4 + (warp >> 1), slot = item % NS;
#pragma unroll
                for (int s = 0; s < 3; s++)
                    off[s] = sb + SM_RING + slot * SLOT + key * 384 + s * 128 + (((lane >> 4) ^ ((3 * key + s) & 7)) << 4);
                pin3(off);
                mbar_wait(bar_full + slot * 8, (item / NS) & 1);
                float c[3][4] = {};
#pragma unroll
                for (int dq = 0; dq < 4; dq++)
#pragma unroll
                    for (int s = 0; s < 3; s++) {
                        uint32_t a[4];
                        ldsm_x4(off[s] ^ (dq << 5), a);
                        mma16816(c[s], a, qf[s * 2 + (dq >> 1)][(dq & 1) * 2], qf[s * 2 + (dq >> 1)][(dq & 1) * 2 + 1]);
                    }
                __syncwarp();
                if (lane == 0)
                    asm volatile("mbarrier.arrive.shared::cta.b64 _, [%0], %1;" ::"r"(bar_full + (NS + slot) * 8), "n"(NCW / 2) : "memory");
                ring.skip(4);
                const float raw = (t & 1) ? (c[0][2] + c[1][2]) + c[2][2] : (c[0][0] + c[1][0]) + c[2][0];
                const float sv = bf_round(bf_round(raw) * 0.07216878364870323f);
                if (tid == 0 && j == NSTEP - 1) TS(14);
                float m = fmaxf(sv, shx(sv, 1));
#pragma unroll
                for (int o = 4; o < 32; o <<= 1) m = fmaxf(m, shx(m, o));
                if (lane == 0) lsum[8 + warp] = m;
                cons_bar();
#pragma unroll
                for (int i = 0; i < WW; i += 2) {
                    const float2 m2 = *reinterpret_cast<const float2*>(lsum + 8 + warp / WW * WW + i);
                    m = fmaxf(m, fmaxf(m2.x, m2.y));
                }
                float l = __expf(sv - m);
                *reinterpret_cast<bf16*>(smem + SM_PF + ((j & 3) * 4 + (warp >> 1)) * 64 + frag_off((warp & 1) * 16 + (t & 1) * 8 + g)) =
                    __float2bfloat16_rn(l);
                l += shx(l, 1);
#pragma unroll
                for (int o = 4; o < 32; o <<= 1) l += shx(l, o);
                if (lane == 0) lsum[warp] = l;
                cons_bar();
                if (tid % (WW * 32) < 4) {
                    l = 0.f;
#pragma unroll
                    for (int i = 0; i < WW; i += 2) {
                        const float2 l2 = *reinterpret_cast<const float2*>(lsum + warp + i);
                        l += l2.x + l2.y;
                    }
                    st_tag2(g_ml + (pair_of(sg, win) * G + r) * MLS + lane * 2, m, l, tag);
                    if (tid == 0) {
                        mbar_arrive(bar_full + B_WTRIG + (j & 3) * 8);
                        if (j == HSTEP) mbar_arrive(bar_full + B_HTRIG);
                    }
                }
                if (tid == 0 && j == NSTEP - 1) TS(13);
                if (j < LA) continue;
            }
            const bool kv = j >= 0;
            const uint32_t jv = j - LA;
#pragma unroll
            for (int s = 0; s < 3; s++) off[s] = lane * 384 + s * 128 + ((warp ^ ((3 * lane + s) & 7)) << 4);
#pragma unroll 1
            for (int u = 0; u < (kv ? WPS : 1); u++) {
                const int pair = pair_of(sg, jv * WPS + u);
                uint32_t trig = !kv ? bar_full + B_QTRIG : (pair >> 2) == h ? bar_full + B_OTRIG + (pair & 3) * 8 : 0;
                if (tid != 0) trig = 0;
                float4* oacc = ocell(pair, warp * 8 + 2 * t + (g & 1));
                uint32_t wrdy = bar_full + B_WRDY + (jv & 3) * 8;
                asm volatile("" : "+l"(oacc), "+r"(trig), "+r"(wrdy));
                gemv_loop(ring, kv ? NT : 5,
                          kv ? sb + SM_PF + ((jv & 3) * 4 + u * NT) * 64 + t * 16 : sb + SM_XF + qd * 5 * 256 + a_lane,
                          kv ? 64 : 256, off, lo, hi, lane);
                if (kv) {
                    mbar_wait(wrdy, (jv >> 2) & 1);
                    const float w = lsum[16 + (jv & 3) * WPS + u];
                    if (g < 2)
                        asm volatile("red.relaxed.gpu.global.add.v4.f32 [%0], {%1,%2,%3,%4};"
                                     ::"l"(oacc), "f"(w * (g ? lo[0][1] + hi[0][3] : lo[0][0] + hi[0][2])),
                                       "f"(w * (g ? lo[1][1] + hi[1][3] : lo[1][0] + hi[1][2])),
                                       "f"(w * (g ? lo[2][1] + hi[2][3] : lo[2][0] + hi[2][2])), "f"(1.0f) : "memory");
                } else if (g < NB) {
#pragma unroll
                    for (int s = 0; s < 3; s++)
                        st_tag2(g_qpart + (cta * NB + g) * VS + warp * 32 + 2 * t + s * 8, lo[s][0] + hi[s][2], lo[s][1] + hi[s][3], tag);
                }
                if (trig) mbar_arrive(trig);
            }
            const bool pass = j == NSTEP + LA - 1;
            if (pass && tid == 0) TS(5);
            if (kv && !pass && j != P_DRY) continue;
            if (tid == 0 && j < 0) TS(4);

            {
                constexpr int I0 = 5 + NKV;
                static_assert(((I0 / NS) & 1) == 0 && I0 / NS == (I0 + 7) / NS, "tail items complete an even phase");
                const uint32_t done = bar_full + B_QTRIG;
                uint32_t fb = pass ? bar_full + (I0 % NS) * 8 : done, fs = pass ? 8 : 0, ordy = pass ? bar_full + B_ORDY : done;
                uint32_t off2[3], a[8][4], b[8][3][4], a_addr = sb + SM_HF + a_lane;
#pragma unroll
                for (int s = 0; s < 3; s++) {
                    const uint32_t w64 = lane * 320 + (warp + 8 * s) * 16;
                    off[s] = sb + SM_RING + (I0 % NS) * SLOT + (w64 ^ (((w64 >> 7) & 3) << 4));
                    off2[s] = lane < 24 ? off[s] : off[s] - 8 * 320;
#pragma unroll
                    for (int e = 0; e < 4; e++) { lo[s][e] = 0.f; hi[s][e] = 0.f; }
                }
                const float4* accp = g_acc + (((g & 3) * 4 + qd) * NCW + warp) * ACS + (g >> 2) * 4 + t;
                bf16* outp = out + (g & 3) * DM + qd * 160 + warp * 8 + 2 * t + (g >> 2);
                pin3(off);
                asm volatile("" : "+l"(accp), "+l"(outp), "+r"(a_addr), "+r"(ordy), "+r"(fb), "+r"(fs));
                auto load_b = [&](int i, bool& next) {
                    if (!next) mbar_wait(fb + i * fs, 0);
                    if (i < 7) next = mbar_test(fb + (i + 1) * fs, 0);
#pragma unroll
                    for (int s = 0; s < 3; s++)
                        if (s < 2 || warp < 4) ldsm_x4_t((i < 2 ? off2[s] : off[s]) + i * SLOT, b[i][s]);
                };
                auto mul = [&](int i) {
#pragma unroll
                    for (int s = 0; s < 3; s++)
                        if (s < 2 || warp < 4) { mma16816(lo[s], a[i], b[i][s][0], b[i][s][1]); mma16816(hi[s], a[i], b[i][s][2], b[i][s][3]); }
                };
                bool next = mbar_test(fb, 0);
                mbar_wait(pass ? bar_full + B_HRDY : done, 0);
                lds128(a_addr, a[0]);
                lds128(a_addr + 256, a[1]);
                load_b(0, next);
                load_b(1, next);
                bool early = mbar_test(ordy, 0);
                mul(0);
                mul(1);
                if (pass && tid == 0) TS(31);
                unsigned spin = 0;
                while (!early && !mbar_test(fb + P_DEC * fs, 0)) {
                    early = mbar_test(ordy, 0);
                    if (++spin > SPIN_LIMIT) __trap();
                }
                if (pass ? __all_sync(0xffffffffu, early) : j < 0) {
                    if (pass && tid == 0) TS(7);
#pragma unroll
                    for (int i = 2; i < 8; i++) lds128(a_addr + i * 256, a[i]);
                    load_b(2, next);
#pragma unroll
                    for (int i = 2; i < 7; i++) { load_b(i + 1, next); mul(i); }
                    mul(7);
                } else {
#pragma unroll
                    for (int i = 2; i < 8; i++) load_b(i, next);
                    mbar_wait(ordy, 0);
                    if (pass && tid == 0) TS(7);
#pragma unroll
                    for (int i = 2; i < 8; i++) lds128(a_addr + i * 256, a[i]);
#pragma unroll
                    for (int i = 2; i < 8; i++) mul(i);
                }
                if (pass && tid == 0) TS(8);
                add_out(accp, outp, lo, hi, g >= NB, warp < 4, pass, epoch);
            }
        }
        if (tid == 0) { TS(9); TS_DUMP(3, 32); }
    } else {
        float gate[6][2];
#pragma unroll
        for (int s = 0; s < 3; s++) {
            const uint32_t r128 = (lane & 15) * 6 + 2 * s + (lane >> 4);
            off[s] = r128 * 128 + ((warp ^ (r128 & 7)) << 4);
        }
#pragma unroll 1
        for (int ps = 0; ps < 2; ps++) {
#pragma unroll
            for (int s = 0; s < 3; s++) {
                gate[2 * s][0] = lo[s][0]; gate[2 * s][1] = lo[s][1];
                gate[2 * s + 1][0] = hi[s][0]; gate[2 * s + 1][1] = hi[s][1];
            }
            gemv_loop(ring, 40, sb + SM_XF + a_lane, 256, off, lo, hi, lane);
        }
#pragma unroll
        for (int p = 0; p < 6; p++) {
            float hv[2];
#pragma unroll
            for (int e = 0; e < 2; e++) {
                const float gt = bf_round(gate[p][e]);
                hv[e] = bf_round(bf_round(__fdividef(gt, 1.0f + __expf(-gt))) * bf_round((p & 1) ? hi[p >> 1][e] : lo[p >> 1][e]));
            }
            if (g < NB) st_tag2(g_h + g * FF + qd * 384 + p * 64 + warp * 8 + 2 * t, hv[0], hv[1], tag);
        }
        if (tid == 0) { TS(9); TS_DUMP(3, 10); }
    }
}

typedef CUresult (*EncodeFn)(CUtensorMap*, CUtensorMapDataType, cuuint32_t, void*, const cuuint64_t*, const cuuint64_t*,
                             const cuuint32_t*, const cuuint32_t*, CUtensorMapInterleave, CUtensorMapSwizzle,
                             CUtensorMapL2promotion, CUtensorMapFloatOOBfill);

void make_map(EncodeFn enc, CUtensorMap* m, const void* p, uint64_t rows, uint64_t cols, uint32_t inner, uint32_t parts,
              uint32_t box_rows) {
    const cuuint64_t dims[3] = {inner, cols / inner, rows};
    const cuuint64_t strides[2] = {inner * 2ull, cols * 2ull};
    const cuuint32_t box[3] = {inner, parts, box_rows};
    const cuuint32_t es[3] = {1, 1, 1};
    enc(m, CU_TENSOR_MAP_DATA_TYPE_BFLOAT16, 3, const_cast<void*>(p), dims, strides, box, es, CU_TENSOR_MAP_INTERLEAVE_NONE,
        inner == 64 ? CU_TENSOR_MAP_SWIZZLE_128B : CU_TENSOR_MAP_SWIZZLE_64B, CU_TENSOR_MAP_L2_PROMOTION_NONE,
        CU_TENSOR_MAP_FLOAT_OOB_FILL_NONE);
}

}

extern "C" void kernel_launch(void* const* d_in, const int* in_sizes, int n_in, void* d_out, int out_size) {
    (void)in_sizes; (void)n_in; (void)out_size;
    static EncodeFn enc = nullptr;
    if (!enc) {
        void* fn = nullptr;
        cudaDriverEntryPointQueryResult qr;
        cudaGetDriverEntryPoint("cuTensorMapEncodeTiled", &fn, cudaEnableDefault, &qr);
        enc = (EncodeFn)fn;
        cudaFuncSetAttribute(fused_decode_kernel, cudaFuncAttributeMaxDynamicSharedMemorySize, SM_TOTAL);
    }
    Maps maps;
    make_map(enc, &maps.k, d_in[1], (uint64_t)NB * NH * SK, DH, 64, 3, TK);
    make_map(enc, &maps.v, d_in[2], (uint64_t)NB * NH * SK, DH, 64, 3, TK);
    make_map(enc, &maps.wq, d_in[3], DM, NH * DH, 64, 3, 32);
    make_map(enc, &maps.wo, d_in[4], NH * DH, DM, 32, 5, 32);
    make_map(enc, &maps.w1, d_in[6], DM, FF, 64, 6, 16);
    make_map(enc, &maps.w3, d_in[7], DM, FF, 64, 6, 16);
    make_map(enc, &maps.w2, d_in[8], FF, DM, 32, 5, 24);
    fused_decode_kernel<<<NCTA, NTHR, SM_TOTAL>>>((const char*)d_in[3], (const bf16*)d_in[0], (bf16*)d_out, maps);
}
```

```cpp
#include <cuda_runtime.h>
#include <cuda.h>
#include <cuda_bf16.h>
#include <stdint.h>

namespace {

typedef __nv_bfloat16 bf16;

constexpr int NB = 4, DM = 640, NH = 32, DH = 192, SK = 8192, WIN = 2048, FF = 1536;

#define P_G 32
#define P_DEPTH 4
#define P_DEPTH_FFN 5
#define P_GAIN 6
#define P_BIAS 16
#define P_SLEEP 500
#define P_DMIN 3
#define P_DMAX 6
#define P_SETTLE 3000
#define P_QDELAY 1600
#define P_LA 2
#define P_MLS 8
#define P_OAL 72
#define P_PF 64
#define P_TLB 3
#define P_DT 3
#define P_DT0 5
#define P_NS 16

constexpr int G = P_G;
constexpr int TK = 32;
constexpr int NT = WIN / TK / G;
constexpr int NSTEP = 16;
constexpr int WPS = G / NSTEP;
constexpr int LA = P_LA;
constexpr int MLS = P_MLS;
constexpr int OAL = P_OAL;
constexpr int HSTEP = 11;
constexpr int NS = P_NS;
constexpr int SLOT = 12288;
constexpr int DEPTH = P_DEPTH;
#define P_D0 5
constexpr int DEPTH0 = P_D0;
static_assert(DEPTH0 <= 5, "DEPTH0");
constexpr int NATT = 128, NFFN = 4, NCTA = NATT + NFFN;
constexpr int NCW = 8;
constexpr int NXW = 2;
constexpr int W_PROD = NCW, W_PACE = NCW + 1 + NXW;
constexpr int NTHR = (W_PACE + 1) * 32;
constexpr int NSRC = NH;
constexpr int VS = 256;
#define P_ACS 72
constexpr int ACS = P_ACS;
static_assert(G == 16 || G == 32 || G == 64, "G");

constexpr int SM_RING = 0;
constexpr int SM_XF = SM_RING + NS * SLOT;
constexpr int SM_QS = SM_XF + 20 * 256;
constexpr int SM_PF = SM_QS + G * DH * 2;
constexpr int SM_HF = SM_PF + 4 * 4 * 64;
constexpr int SM_OF = SM_HF + 2 * 256;
constexpr int SM_LS = SM_OF + 6 * 256;
constexpr int SM_ATT_END = SM_LS + 128;
constexpr int SM_FFN_END = SM_XF + 40 * 256;
constexpr int SM_BAR = SM_ATT_END > SM_FFN_END ? SM_ATT_END : SM_FFN_END;
constexpr int B_QRDY = 2 * NS * 8, B_ORDY = B_QRDY + NSTEP * 8, B_OTRIG = B_ORDY + 8, B_QTRIG = B_OTRIG + 32,
              B_WTRIG = B_QTRIG + 8, B_WRDY = B_WTRIG + 32, B_HTRIG = B_WRDY + 32, B_HRDY = B_HTRIG + 8,
              NBAR = 2 * NS + NSTEP + 16;
constexpr int SM_PACE = SM_BAR + NBAR * 8;
constexpr int SM_TS = SM_PACE + 8;
constexpr int SM_TOTAL = SM_TS + 256;
static_assert(SM_TOTAL <= 232448, "smem");

constexpr int NKV = 2 * NT * G;
constexpr int ITEMS_ATT = 5 + NKV + 2 + 6;
constexpr int ITEMS_FFN = 80;

struct Maps { CUtensorMap k, v, wq, wo, w1, w3, w2; };

struct alignas(32) Sync { unsigned epoch, inits, prog[2]; };
__device__ Sync g_sync;
__device__ __align__(128) float g_qpart[NATT * NB * VS];
__device__ __align__(128) float g_ml[NATT * G * MLS];
__device__ __align__(128) float g_h[NB * FF];
__device__ __align__(128) float4 g_oacc[NATT * 8 * OAL];
__device__ __align__(128) float4 g_acc[NB * 4 * NCW * ACS];
#define TS(i)
#define TS_DUMP(lo, hi)

constexpr unsigned SPIN_LIMIT = 1u << 22;

__device__ __forceinline__ void mbar_init(uint32_t bar, int cnt) {
    asm volatile("mbarrier.init.shared::cta.b64 [%0], %1;" ::"r"(bar), "r"(cnt) : "memory");
}
__device__ __forceinline__ void mbar_expect_tx(uint32_t bar, uint32_t bytes) {
    asm volatile("mbarrier.arrive.expect_tx.shared::cta.b64 _, [%0], %1;" ::"r"(bar), "r"(bytes) : "memory");
}
__device__ __forceinline__ void mbar_arrive(uint32_t bar) {
    asm volatile("mbarrier.arrive.shared::cta.b64 _, [%0];" ::"r"(bar) : "memory");
}
__device__ __forceinline__ void mbar_wait(uint32_t bar, uint32_t parity) {
    asm volatile("{\n.reg .pred p, q;\n.reg .u32 n;\nmov.u32 n, 0;\n"
                 "W: mbarrier.try_wait.parity.shared::cta.b64 p, [%0], %1;\n"
                 "@p bra D;\nadd.u32 n, n, 1;\nsetp.lt.u32 q, n, %2;\n@q bra W;\ntrap;\nD:\n}"
                 ::"r"(bar), "r"(parity), "n"(SPIN_LIMIT) : "memory");
}
__device__ __forceinline__ bool mbar_test(uint32_t bar, uint32_t parity) {
    uint32_t ok;
    asm volatile("{\n.reg .pred p;\nmbarrier.test_wait.parity.shared::cta.b64 p, [%1], %2;\nselp.u32 %0, 1, 0, p;\n}"
                 : "=r"(ok) : "r"(bar), "r"(parity) : "memory");
    return ok;
}
__device__ __forceinline__ void tma3d(uint32_t dst, const CUtensorMap* map, int c1, int c2, uint32_t bar) {
    const uint64_t pol = 0x12F0000000000000ull;
    asm volatile("cp.async.bulk.tensor.3d.shared::cluster.global.mbarrier::complete_tx::bytes.L2::cache_hint "
                 "[%0], [%1, {%2, %3, %4}], [%5], %6;"
                 ::"r"(dst), "l"(map), "r"(0), "r"(c1), "r"(c2), "r"(bar), "l"(pol) : "memory");
}
__device__ __forceinline__ void ldsm_x4(uint32_t addr, uint32_t (&r)[4]) {
    asm volatile("ldmatrix.sync.aligned.m8n8.x4.shared.b16 {%0,%1,%2,%3}, [%4];"
                 : "=r"(r[0]), "=r"(r[1]), "=r"(r[2]), "=r"(r[3]) : "r"(addr) : "memory");
}
__device__ __forceinline__ void ldsm_x4_t(uint32_t addr, uint32_t (&r)[4]) {
    asm volatile("ldmatrix.sync.aligned.m8n8.x4.trans.shared.b16 {%0,%1,%2,%3}, [%4];"
                 : "=r"(r[0]), "=r"(r[1]), "=r"(r[2]), "=r"(r[3]) : "r"(addr) : "memory");
}
__device__ __forceinline__ void lds128(uint32_t addr, uint32_t (&r)[4]) {
    asm volatile("ld.shared.v4.u32 {%0,%1,%2,%3}, [%4];"
                 : "=r"(r[0]), "=r"(r[1]), "=r"(r[2]), "=r"(r[3]) : "r"(addr) : "memory");
}
__device__ __forceinline__ void mma16816(float (&c)[4], const uint32_t (&a)[4], uint32_t b0, uint32_t b1) {
    asm volatile("mma.sync.aligned.m16n8k16.row.col.f32.bf16.bf16.f32 {%0,%1,%2,%3}, {%4,%5,%6,%7}, {%8,%9}, {%0,%1,%2,%3};"
                 : "+f"(c[0]), "+f"(c[1]), "+f"(c[2]), "+f"(c[3])
                 : "r"(a[0]), "r"(a[1]), "r"(a[2]), "r"(a[3]), "r"(b0), "r"(b1));
}
__device__ __forceinline__ void cons_bar() { asm volatile("bar.sync 1, 256;" ::: "memory"); }

__device__ __forceinline__ float bf_round(float v) { return __bfloat162float(__float2bfloat16_rn(v)); }
__device__ __forceinline__ uint32_t pack_bf2(float lo, float hi) {
    __nv_bfloat162 t = __floats2bfloat162_rn(lo, hi);
    return *reinterpret_cast<uint32_t*>(&t);
}
__device__ __forceinline__ float bf_lo(uint32_t u) { return __uint_as_float(u << 16); }
__device__ __forceinline__ float bf_hi(uint32_t u) { return __uint_as_float(u & 0xffff0000u); }
__device__ __forceinline__ float shx(float v, int o) { return __shfl_xor_sync(0xffffffffu, v, o); }

__device__ __forceinline__ uint32_t frag_off(uint32_t k) {
    return ((k >> 1) & 3) * 16 + ((k >> 3) & 1) * 8 + ((k >> 4) & 1) * 4 + (k & 1) * 2;
}

__device__ __forceinline__ void st_tag2(float* p, float a, float b, uint32_t tag) {
    asm volatile("{\n.reg .b64 w;\n.reg .b32 x;\nlop3.b32 x, %1, 0xfffffffe, %3, 0xea;\nmov.b64 w, {x, %2};\n"
                 "st.relaxed.gpu.global.b64 [%0], w;\n}"
                 ::"l"(p), "r"(__float_as_uint(a)), "r"(__float_as_uint(b)), "r"(tag) : "memory");
}
__device__ __forceinline__ void st_fill4(float* p, uint32_t v) {
    asm volatile("{\n.reg .b64 w;\nmov.b64 w, {%1, %1};\nst.relaxed.gpu.global.v2.b64 [%0], {w, w};\n}" ::"l"(p), "r"(v) : "memory");
}
__device__ __forceinline__ uint2 ld_word(const float* p) {
    uint2 v;
    asm volatile("{\n.reg .b64 w;\nld.relaxed.gpu.global.b64 w, [%2];\nmov.b64 {%0,%1}, w;\n}" : "=r"(v.x), "=r"(v.y) : "l"(p) : "memory");
    return v;
}
__device__ __forceinline__ uint4 ld_word2(const float* p) {
    uint4 v;
    asm volatile("{\n.reg .b64 w0, w1;\nld.relaxed.gpu.global.v2.b64 {w0, w1}, [%4];\nmov.b64 {%0,%1}, w0;\nmov.b64 {%2,%3}, w1;\n}"
                 : "=r"(v.x), "=r"(v.y), "=r"(v.z), "=r"(v.w) : "l"(p) : "memory");
    return v;
}

__device__ __forceinline__ void add_out(const float4* acc, bf16* out, const float (&lo)[3][4], const float (&hi)[3][4],
                                        bool odd, bool third, bool live, uint32_t epoch) {
    const float v0 = odd ? lo[0][1] + hi[0][3] : lo[0][0] + hi[0][2];
    const float v1 = odd ? lo[1][1] + hi[1][3] : lo[1][0] + hi[1][2];
    const float v2 = odd ? lo[2][1] + hi[2][3] : lo[2][0] + hi[2][2];
    float o0, o1, o2, n = 0.f;
    asm volatile("{\n.reg .pred p;\nsetp.ne.u32 p, %5, 0;\n"
                 "@p atom.relaxed.gpu.global.add.v4.f32 {%0,%1,%2,%3}, [%4], {%6,%7,%8,%9};\n}"
                 : "=f"(o0), "=f"(o1), "=f"(o2), "+f"(n)
                 : "l"(acc), "r"((uint32_t)live), "f"(v0), "f"(v1), "f"(v2), "f"(1.0f) : "memory");
    asm volatile("{\n.reg .pred p, q;\nsetp.eq.f32 p, %4, %5;\nsetp.ne.and.u32 q, %6, 0, p;\n"
                 "@p st.global.u16 [%0], %1;\n@p st.global.u16 [%0+128], %2;\n@q st.global.u16 [%0+256], %3;\n}"
                 ::"l"(out), "h"(__bfloat16_as_ushort(__float2bfloat16_rn(o0 + v0))),
                   "h"(__bfloat16_as_ushort(__float2bfloat16_rn(o1 + v1))), "h"(__bfloat16_as_ushort(__float2bfloat16_rn(o2 + v2))),
                   "f"(n), "f"((float)(NSRC - 1)), "r"((uint32_t)third) : "memory");
    if (acc == g_acc && n == (float)(NSRC - 1))
        asm volatile("st.relaxed.gpu.global.u32 [%0], %1;" ::"l"(&g_sync.epoch), "r"(epoch + 1u) : "memory");
}

__device__ __forceinline__ int pair_of(int sg, uint32_t j) { return sg * G + (j % (G / 4)) * 4 + j / (G / 4); }
__device__ __forceinline__ int order_of(int r, int b) { return b * (G / 4) + (r >> 2); }

__device__ __forceinline__ int window_row(int sg, uint32_t u, bool& isv) {
    const uint32_t blk = u / 4;
    isv = blk >= 2 * NSTEP - LA || (blk >= LA && ((blk - LA) & 1));
    const uint32_t step = blk < LA ? blk : blk >= 2 * NSTEP - LA ? blk - NSTEP : (blk - LA) / 2 + (isv ? 0 : LA);
    const int pair = pair_of(sg, step * WPS + (u % 4) / NT);
    return ((pair & 3) * NH + (pair >> 2)) * SK + (SK - WIN);
}

__device__ __forceinline__ float4* ocell(uint32_t pair, uint32_t i) {
    return g_oacc + (pair * 8 + (i >> 3)) * OAL + (i & 7);
}

__device__ __forceinline__ void settle(int cycles) {
    const uint32_t t0 = (uint32_t)clock();
    while ((uint32_t)clock() - t0 < (uint32_t)cycles) __nanosleep(20);
}

struct Ring {
    uint32_t full, addr, phase, first_full;
    __device__ __forceinline__ void wait() const { mbar_wait(full, phase); }
    __device__ __forceinline__ void skip(int n) {
        full += n * 8; addr += n * SLOT;
        if (full >= first_full + NS * 8) { full -= NS * 8; addr -= NS * SLOT; phase ^= 1; }
    }
    __device__ __forceinline__ void release(int lane) {
        __syncwarp();
        if (lane == 0) mbar_arrive(full + NS * 8);
        full += 8; addr += SLOT;
        if (full == first_full + NS * 8) { full = first_full; addr -= NS * SLOT; phase ^= 1; }
    }
};

__device__ __forceinline__ void pin3(uint32_t (&v)[3]) {
    asm volatile("" : "+r"(v[0]), "+r"(v[1]), "+r"(v[2]));
}
__device__ __forceinline__ void gemv_loop(Ring& ring, int n, uint32_t a_addr, uint32_t a_step, uint32_t (&off)[3],
                                          float (&lo)[3][4], float (&hi)[3][4], int lane) {
    pin3(off);
#pragma unroll
    for (int s = 0; s < 3; s++)
#pragma unroll
        for (int e = 0; e < 4; e++) { lo[s][e] = 0.f; hi[s][e] = 0.f; }
#pragma unroll 1
    for (int it = 0; it < n; it++) {
        uint32_t a[4], b[3][4];
        lds128(a_addr, a);
        a_addr += a_step;
        ring.wait();
#pragma unroll
        for (int s = 0; s < 3; s++) ldsm_x4_t(ring.addr + off[s], b[s]);
#pragma unroll
        for (int s = 0; s < 3; s++) { mma16816(lo[s], a, b[s][0], b[s][1]); mma16816(hi[s], a, b[s][2], b[s][3]); }
        ring.release(lane);
    }
}

__global__ void __launch_bounds__(NTHR, 1)
fused_decode_kernel(const char* __restrict__ wq, const bf16* __restrict__ x, bf16* __restrict__ out,
                    const char* __restrict__ kc, const char* __restrict__ vc, const __grid_constant__ Maps maps) {
    asm volatile("{\n.reg .pred p;\n.reg .b32 t, c, a, b;\n.reg .b64 o;\n"
                 "mov.u32 t, %%tid.x;\nmov.u32 c, %%ctaid.x;\n"
                 "and.b32 a, c, 3;\nshr.u32 c, c, 2;\nmul.lo.u32 a, a, 15360;\nmad.lo.u32 a, c, 3, a;\n"
                 "shr.u32 b, t, 2;\nmad.lo.u32 a, b, 92, a;\nadd.u32 a, a, t;\nmad.wide.u32 o, a, 128, %0;\n"
                 "and.b32 b, t, 3;\nsetp.ne.u32 p, b, 3;\nsetp.lt.and.u32 p, t, %1, p;\n@p prefetch.global.L2 [o];\n}"
                 ::"l"(wq), "n"(P_PF * 4) : "memory");
    extern __shared__ __align__(1024) unsigned char smem[];
    const uint32_t sb = (uint32_t)__cvta_generic_to_shared(smem);
    const uint32_t bar_full = sb + SM_BAR;
    if (threadIdx.x == 0 && blockIdx.x < NATT) {
        TS(0);
#pragma unroll 1
        for (int i = 0; i < DEPTH0; i++) {
            mbar_init(bar_full + i * 8, 1);
            mbar_expect_tx(bar_full + i * 8, 12288);
            tma3d(sb + SM_RING + i * SLOT, &maps.wq, (blockIdx.x >> 2) * 3, (blockIdx.x & 3) * 160 + i * 32, bar_full + i * 8);
        }
        TS(1);
    }
    unsigned ptid, cta;
    asm volatile("mov.u32 %0, %%tid.x;\nmov.u32 %1, %%ctaid.x;" : "=r"(ptid), "=r"(cta));
    const int tid = ptid < 32 ? ptid + NCW * 32 : ptid < (NCW + 1) * 32 ? ptid - 32 : ptid;
    const int warp = tid >> 5, lane = tid & 31;
    const bool is_att = cta < NATT;
    const int h = cta >> 2, qd = cta & 3;
    const int sg = cta / G, r = cta % G;

    if (warp == NCW) {
        volatile int* pace = reinterpret_cast<volatile int*>(smem + SM_PACE);
        if (lane == 0) {
            if (!is_att) { TS(0); TS(1); }
            pace[0] = 0;
            pace[1] = is_att ? DEPTH : P_DEPTH_FFN;
#pragma unroll
            for (int i = 0; i < NBAR; i++)
                if (i >= DEPTH0 || !is_att)
                mbar_init(bar_full + i * 8, i < NS ? 1 : i < 2 * NS ? NCW : i < 2 * NS + NSTEP ? NXW : i == 2 * NS + NSTEP ? NXW * NB : i == NBAR - 1 ? NXW : 1);
            asm volatile("fence.mbarrier_init.release.cluster;" ::: "memory");
        }
        __syncwarp();
        asm volatile("bar.arrive 2, %0;" ::"n"(NTHR) : "memory");
        if (lane == 0) {
            const int n_items = is_att ? ITEMS_ATT : ITEMS_FFN;

            asm volatile("prefetch.tensormap [%0];" ::"l"(is_att ? &maps.k : &maps.w3) : "memory");
            asm volatile("prefetch.tensormap [%0];" ::"l"(&maps.v) : "memory");
            asm volatile("prefetch.tensormap [%0];" ::"l"(&maps.w2) : "memory");
            asm volatile("prefetch.tensormap [%0];" ::"l"(&maps.wo) : "memory");
#pragma unroll 1
            for (int i = is_att ? DEPTH0 : 0; i < n_items; i++) {
                const CUtensorMap* map;
                int c1, c2;
                uint32_t bytes = 12288;
                if (is_att) {
                    const uint32_t u = i - 5;
                    if (u < NKV) {
                        bool isv;
                        c2 = window_row(sg, u, isv) + ((u % NT) * G + r) * TK;
                        map = isv ? &maps.v : &maps.k;
                        c1 = 0;
                    } else if (i < 5) {
                        map = &maps.wq; c1 = h * 3; c2 = qd * 160 + i * 32;
                    } else if (u < NKV + 2) {
                        map = &maps.w2; c1 = qd * 5; c2 = h * 48 + (u - NKV) * 24; bytes = 7680;
                    } else {
                        map = &maps.wo; c1 = qd * 5; c2 = h * DH + (u - NKV - 2) * 32; bytes = 10240;
                    }
                } else {
                    map = i < 40 ? &maps.w1 : &maps.w3; c1 = qd * 6; c2 = (i < 40 ? i : i - 40) * 16;
                }
                const int depth = pace[1] + (is_att && i >= 5 + NKV + P_DT0 ? P_DT : 0);
                const uint32_t slot = (uint32_t)i % NS, landed = i - depth;
                if (i >= NS) mbar_wait(bar_full + (NS + slot) * 8, ((uint32_t)i / NS - 1) & 1);
                mbar_expect_tx(bar_full + slot * 8, bytes);
                uint32_t dst = sb + SM_RING + slot * SLOT, fb = bar_full + slot * 8;
                asm volatile("" : "+r"(dst), "+r"(fb), "+l"(map), "+r"(c1), "+r"(c2));
                if (i >= depth) mbar_wait(bar_full + (landed % NS) * 8, (landed / NS) & 1);
                tma3d(dst, map, c1, c2, fb);
                pace[0] = landed + 1;
                const uint32_t un = i - 5 + P_TLB;
                if (is_att && un < NKV && un % NT == 0 && r == (un / NT) % G) {
                    bool isv;
                    const int row = window_row(sg, un, isv);
                    asm volatile("prefetch.global.L2 [%0];" ::"l"((isv ? vc : kc) + (size_t)row * (DH * 2)) : "memory");
                }
            }
            pace[0] = n_items - DEPTH;
        }
        return;
    }

    const int g = lane >> 2, t = lane & 3;
    uint32_t epoch;
    asm volatile("ld.relaxed.gpu.global.u32 %0, [%1];" : "=r"(epoch) : "l"(&g_sync.epoch) : "memory");

    if (warp == W_PACE) {
        const uint32_t tag = (epoch + 1u) & 1u;
        if (is_att) {
#pragma unroll
            for (int u = 0; u < WPS; u++) st_fill4(g_ml + ((sg * G + u * 16 + (lane >> 1)) * G + r) * MLS + (lane & 1) * 4, tag ^ 1u);
        }
        asm volatile("bar.sync 2, %0;" ::"n"(NTHR) : "memory");
        if (lane == 0) asm volatile("red.release.gpu.global.add.u32 [%0], 1;" ::"l"(&g_sync.inits) : "memory");
        if (!is_att) return;
        volatile int* pace = reinterpret_cast<volatile int*>(smem + SM_PACE);
        if (cta == 0 && lane == 0) asm volatile("st.relaxed.gpu.global.u32 [%0], %1;" ::"l"(&g_sync.prog[epoch & 1u]), "r"(0u) : "memory");
        int reported = 0, j = 0;
        bool due = false;
#pragma unroll 1
        for (unsigned it = 0;; it++) {
            const int landed = pace[0];
            if (j == NSTEP && landed >= ITEMS_ATT - DEPTH) {
                if (lane == 0)
                    asm volatile("red.relaxed.gpu.global.add.u32 [%0], %1;" ::"l"(&g_sync.prog[~epoch & 1u]), "r"(landed - reported) : "memory");
                return;
            }
            int sum = 0;
            constexpr int RPL = (G + 31) / 32;
            uint2 ml[WPS][RPL];
            uint32_t bad = 1u;
            unsigned n = (epoch + 1u) * NCTA;
            if (lane == 0)
                asm volatile("atom.relaxed.gpu.global.add.u32 %0, [%1], %2;"
                             : "=r"(sum) : "l"(&g_sync.prog[~epoch & 1u]), "r"(landed - reported) : "memory");
            if (due) {
#pragma unroll
                for (int u = 0; u < WPS; u++)
#pragma unroll
                    for (int k = 0; k < RPL; k++) ml[u][k] = ld_word(g_ml + (pair_of(sg, j * WPS + u) * G + k * 32 + lane % G) * MLS);
                if (j == 0) asm volatile("ld.acquire.gpu.global.u32 %0, [%1];" : "=r"(n) : "l"(&g_sync.inits) : "memory");
            }
            reported = landed;
            if (lane == 0 && P_GAIN) {
                const int lag16 = sum / (NATT / 16) - landed * 16 + P_BIAS;
                pace[1] = min(max(DEPTH + ((lag16 * P_GAIN + 128) >> 8), P_DMIN), P_DMAX);
            }
            if (due) {
                bad = 0;
#pragma unroll
                for (int u = 0; u < WPS; u++)
#pragma unroll
                    for (int k = 0; k < RPL; k++) bad |= ml[u][k].x ^ tag;
            }
            if (__all_sync(0xffffffffu, !(bad & 1u) && n == (epoch + 1u) * NCTA)) {
#pragma unroll
                for (int u = 0; u < WPS; u++) {
                    float M = -INFINITY, L = 0.f, w = 0.f;
#pragma unroll
                    for (int k = 0; k < RPL; k++) M = fmaxf(M, __uint_as_float(ml[u][k].x & ~1u));
#pragma unroll
                    for (int o = G / RPL / 2; o; o >>= 1) M = fmaxf(M, shx(M, o));
#pragma unroll
                    for (int k = 0; k < RPL; k++) {
                        const float wk = __expf(__uint_as_float(ml[u][k].x & ~1u) - M);
                        L += wk * __uint_as_float(ml[u][k].y);
                        if (k == r / 32) w = wk;
                    }
#pragma unroll
                    for (int o = G / RPL / 2; o; o >>= 1) L += shx(L, o);
                    if (lane == r % 32) reinterpret_cast<float*>(smem + SM_LS)[16 + (j & 3) * WPS + u] = __fdividef(w, L);
                }
                if (lane == r % 32) {
                    mbar_arrive(bar_full + B_WRDY + (j & 3) * 8);
                    if (j == NSTEP - 1) TS(11);
                }
                j++;
                due = false;
            }
            if (!due && j < NSTEP) due = mbar_test(bar_full + B_WTRIG + (j & 3) * 8, (j >> 2) & 1);
            __nanosleep(P_SLEEP);
            if (it > SPIN_LIMIT) __trap();
        }
    }
    if (warp > W_PROD) {
        const uint32_t tag = (epoch + 1u) & 1u;
        const int e = tid - (W_PROD + 1) * 32;
        if (is_att) {
#pragma unroll 1
            for (int i = e; i < 192; i += NXW * 32)
                st_fill4(g_qpart + (cta * NB + i / 48) * VS + (i % 48) / 6 * 32 + (i % 6) * 4, tag ^ 1u);
            st_fill4(reinterpret_cast<float*>(ocell(cta, e)), 0u);
            if (e < 32) *reinterpret_cast<uint32_t*>(smem + SM_HF + e * 16 + 12) = 0u;
        } else {
#pragma unroll 1
            for (int c = e; c < 256; c += NXW * 32) {
                const bf16* xp = x + qd * DM + (c >> 6) * 160 + ((c >> 3) & 7) * 8 + (c & 3) * 2 + ((c >> 2) & 1);
                asm volatile("st.relaxed.gpu.global.v4.f32 [%0], {%1,%2,%3,%4};"
                             ::"l"(g_acc + (qd * 32 + (c >> 3)) * ACS + (c & 7)), "f"(__bfloat162float(xp[0])),
                               "f"(__bfloat162float(xp[64])), "f"((c & 32) ? 0.f : __bfloat162float(xp[128])), "f"(0.f) : "memory");
            }
        }
        asm volatile("bar.sync 2, %0;" ::"n"(NTHR) : "memory");
        if (!is_att) return;
        {
            const uint32_t eq = (e >> 5) * 24 + min(lane, 23), xw = eq / 6, xr = eq % 6;
            mbar_wait(bar_full + B_QTRIG, 0);
            if (e == 0) TS(10);
            settle(P_QDELAY);
#pragma unroll 1
            for (int j = 0; j < NSTEP; j++) {
                uint4 v[WPS][4];
                uint32_t bad;
                unsigned spin = 0;
                do {
#pragma unroll
                    for (int u = 0; u < WPS; u++) {
                        const int pair = pair_of(sg, j * WPS + u);
                        const float* src = g_qpart + ((pair >> 2) * 4 * NB + (pair & 3)) * VS + xw * 32 + xr * 4;
#pragma unroll
                        for (int k = 0; k < 4; k++) v[u][k] = ld_word2(src + k * NB * VS);
                    }
                    bad = 0;
#pragma unroll
                    for (int u = 0; u < WPS; u++)
#pragma unroll
                        for (int k = 0; k < 4; k++) bad |= (v[u][k].x ^ tag) | (v[u][k].z ^ tag);
                    if (++spin > SPIN_LIMIT) __trap();
                } while (bad & 1u);
#define SUM4(c) ((__uint_as_float(v[u][0].c) + __uint_as_float(v[u][1].c)) + (__uint_as_float(v[u][2].c) + __uint_as_float(v[u][3].c)))
#pragma unroll
                for (int u = 0; u < WPS; u++) {
                    unsigned char* dst = smem + SM_QS + (j * WPS + u) * (DH * 2) + (xr & 1) * 192 + ((xr >> 1) * 8 + xw) * 4;
                    *reinterpret_cast<uint32_t*>(dst) = pack_bf2(SUM4(x), SUM4(y));
                    *reinterpret_cast<uint32_t*>(dst + 96) = pack_bf2(SUM4(z), SUM4(w));
                }
#undef SUM4
                __syncwarp();
                if (lane == 0) mbar_arrive(bar_full + B_QRDY + j * 8);
                if (e == 0 && j == 0) TS(12);
            }
        }
        bool have_h = false;
#pragma unroll 1
        for (int b = 0; b <= NB; b++) {
            if (!have_h && (b == NB || order_of(r, b) >= HSTEP * WPS)) {
                have_h = true;
                mbar_wait(bar_full + B_HTRIG, 0);
#pragma unroll 1
                for (int i = e; i < 96; i += NXW * 32) {
                    const int k = (i % 24) * 2;
                    uint2 v;
                    unsigned spin = 0;
                    do {
                        v = ld_word(g_h + i / 24 * FF + h * 48 + k);
                        if (++spin > SPIN_LIMIT) __trap();
                    } while ((v.x ^ tag) & 1u);
                    *reinterpret_cast<uint32_t*>(smem + SM_HF + k / 24 * 256 + i / 24 * 64 + frag_off(k % 24)) = __byte_perm(v.x, v.y, 0x7632);
                }
                __syncwarp();
                if (lane == 0) mbar_arrive(bar_full + B_HRDY);
            }
            if (b == NB) break;
            const float4* src = ocell(h * NB + b, e);
            uint32_t dst = sb + SM_OF + (e >> 5) * 256 + b * 64 + frag_off(lane), ordy = bar_full + B_ORDY;
            asm volatile("" : "+r"(dst), "+l"(src), "+r"(ordy));
            mbar_wait(bar_full + B_OTRIG + b * 8, 0);
            const int pause = order_of(r, b) < G - WPS ? P_SETTLE : 0;
            unsigned spin = 0;
            float o0, o1, o2, n;
            do {
                settle(pause);
                asm volatile("atom.relaxed.gpu.global.add.v4.f32 {%0,%1,%2,%3}, [%4], {%5,%5,%5,%5};"
                             : "=f"(o0), "=f"(o1), "=f"(o2), "=f"(n) : "l"(src), "f"(0.f) : "memory");
                asm volatile("st.shared.u16 [%0], %1;\nst.shared.u16 [%0+512], %2;\nst.shared.u16 [%0+1024], %3;"
                             ::"r"(dst), "h"(__bfloat16_as_ushort(__float2bfloat16_rn(o0))),
                               "h"(__bfloat16_as_ushort(__float2bfloat16_rn(o1))), "h"(__bfloat16_as_ushort(__float2bfloat16_rn(o2))) : "memory");
                if (++spin > SPIN_LIMIT) __trap();
            } while (n != (float)G);
            __syncwarp();
            if (lane == 0) mbar_arrive(ordy);
        }
        return;
    }

    if (warp < NB) {
        uint2 raw[5];
#pragma unroll
        for (int i = 0; i < 5; i++) raw[i] = __ldg(reinterpret_cast<const uint2*>(x + warp * DM) + i * 32 + lane);
        float s = 0.f;
#pragma unroll
        for (int i = 0; i < 5; i++) s += (bf_lo(raw[i].x) + bf_hi(raw[i].x)) + (bf_lo(raw[i].y) + bf_hi(raw[i].y));
#pragma unroll
        for (int o = 16; o; o >>= 1) s += shx(s, o);
        const float mean = s * (1.0f / DM);
        float q2 = 0.f;
#pragma unroll
        for (int i = 0; i < 5; i++) {
            const float d0 = bf_lo(raw[i].x) - mean, d1 = bf_hi(raw[i].x) - mean;
            const float d2 = bf_lo(raw[i].y) - mean, d3 = bf_hi(raw[i].y) - mean;
            q2 += (d0 * d0 + d1 * d1) + (d2 * d2 + d3 * d3);
        }
#pragma unroll
        for (int o = 16; o; o >>= 1) q2 += shx(q2, o);
        const float mb = bf_round(mean);
        const float rs = __frcp_rn(bf_round(__fsqrt_rn(bf_round(bf_round(q2 * (1.0f / DM)) + 1e-5f))));
        const uint32_t k = (lane * 4) & 31;
        unsigned char* dst = smem + SM_XF + warp * 64 +
            (is_att ? (lane >> 3) * 256 + frag_off(k) : (lane >> 2) * 256 + frag_off(k & 15));
        const uint32_t step = is_att ? 1024 : 2048;
#pragma unroll
        for (int i = 0; i < 5; i++) {
            const uint32_t d0 = pack_bf2(bf_lo(raw[i].x) - mb, bf_hi(raw[i].x) - mb);
            const uint32_t d1 = pack_bf2(bf_lo(raw[i].y) - mb, bf_hi(raw[i].y) - mb);
            *reinterpret_cast<uint32_t*>(dst + i * step) = pack_bf2(bf_lo(d0) * rs, bf_hi(d0) * rs);
            *reinterpret_cast<uint32_t*>(dst + i * step + 16) = pack_bf2(bf_lo(d1) * rs, bf_hi(d1) * rs);
        }
    }
    asm volatile("bar.sync 2, %0;" ::"n"(NTHR) : "memory");
    uint32_t tag = (epoch + 1u) & 1u;
    asm volatile("" : "+r"(tag));
    if (tid == 0) TS(3);

    Ring ring{bar_full, sb + SM_RING, 0u, bar_full};
    float lo[3][4] = {}, hi[3][4] = {};
    uint32_t off[3];
    const uint32_t a_lane = (g & 3) * 64 + t * 16;

    if (is_att) {
        float* lsum = reinterpret_cast<float*>(smem + SM_LS);
#pragma unroll 1
        for (int j = -1; j < NSTEP + LA; j++) {
            if (j >= 0 && j < NSTEP) {
                constexpr int WW = NCW / WPS;
                const int win = j * WPS + warp / WW;
                uint32_t qf[6][4];
                mbar_wait(bar_full + B_QRDY + j * 8, 0);
                if (j == 0 && tid == 0) TS(6);
#pragma unroll
                for (int i = 0; i < 6; i++) lds128(sb + SM_QS + win * (DH * 2) + t * 96 + i * 16, qf[i]);
                const uint32_t key = (warp & 1) * 16 + (lane & 15);
                const uint32_t item = 5 + (j + max(j - LA, 0)) * 4 + (warp >> 1), slot = item % NS;
#pragma unroll
                for (int s = 0; s < 3; s++)
                    off[s] = sb + SM_RING + slot * SLOT + key * 384 + s * 128 + (((lane >> 4) ^ ((3 * key + s) & 7)) << 4);
                pin3(off);
                mbar_wait(bar_full + slot * 8, (item / NS) & 1);
                float c[3][4] = {};
#pragma unroll
                for (int dq = 0; dq < 4; dq++)
#pragma unroll
                    for (int s = 0; s < 3; s++) {
                        uint32_t a[4];
                        ldsm_x4(off[s] ^ (dq << 5), a);
                        mma16816(c[s], a, qf[s * 2 + (dq >> 1)][(dq & 1) * 2], qf[s * 2 + (dq >> 1)][(dq & 1) * 2 + 1]);
                    }
                __syncwarp();
                if (lane == 0)
                    asm volatile("mbarrier.arrive.shared::cta.b64 _, [%0], %1;" ::"r"(bar_full + (NS + slot) * 8), "n"(NCW / 2) : "memory");
                ring.skip(4);
                const float raw = (t & 1) ? (c[0][2] + c[1][2]) + c[2][2] : (c[0][0] + c[1][0]) + c[2][0];
                const float sv = bf_round(bf_round(raw) * 0.07216878364870323f);
                if (tid == 0 && j == NSTEP - 1) TS(14);
                float m = fmaxf(sv, shx(sv, 1));
#pragma unroll
                for (int o = 4; o < 32; o <<= 1) m = fmaxf(m, shx(m, o));
                if (lane == 0) lsum[8 + warp] = m;
                cons_bar();
#pragma unroll
                for (int i = 0; i < WW; i += 2) {
                    const float2 m2 = *reinterpret_cast<const float2*>(lsum + 8 + warp / WW * WW + i);
                    m = fmaxf(m, fmaxf(m2.x, m2.y));
                }
                float l = __expf(sv - m);
                *reinterpret_cast<bf16*>(smem + SM_PF + ((j & 3) * 4 + (warp >> 1)) * 64 + frag_off((warp & 1) * 16 + (t & 1) * 8 + g)) =
                    __float2bfloat16_rn(l);
                l += shx(l, 1);
#pragma unroll
                for (int o = 4; o < 32; o <<= 1) l += shx(l, o);
                if (lane == 0) lsum[warp] = l;
                cons_bar();
                if (tid % (WW * 32) < 4) {
                    l = 0.f;
#pragma unroll
                    for (int i = 0; i < WW; i += 2) {
                        const float2 l2 = *reinterpret_cast<const float2*>(lsum + warp + i);
                        l += l2.x + l2.y;
                    }
                    st_tag2(g_ml + (pair_of(sg, win) * G + r) * MLS + lane * 2, m, l, tag);
                    if (tid == 0) {
                        mbar_arrive(bar_full + B_WTRIG + (j & 3) * 8);
                        if (j == HSTEP) mbar_arrive(bar_full + B_HTRIG);
                    }
                }
                if (tid == 0 && j == NSTEP - 1) TS(13);
                if (j < LA) continue;
            }
            const bool kv = j >= 0;
            const uint32_t jv = j - LA;
#pragma unroll
            for (int s = 0; s < 3; s++) off[s] = lane * 384 + s * 128 + ((warp ^ ((3 * lane + s) & 7)) << 4);
#pragma unroll 1
            for (int u = 0; u < (kv ? WPS : 1); u++) {
                const int pair = pair_of(sg, jv * WPS + u);
                uint32_t trig = !kv ? bar_full + B_QTRIG : (pair >> 2) == h ? bar_full + B_OTRIG + (pair & 3) * 8 : 0;
                if (tid != 0) trig = 0;
                float4* oacc = ocell(pair, warp * 8 + 2 * t + (g & 1));
                uint32_t wrdy = bar_full + B_WRDY + (jv & 3) * 8;
                asm volatile("" : "+l"(oacc), "+r"(trig), "+r"(wrdy));
                gemv_loop(ring, kv ? NT : 5,
                          kv ? sb + SM_PF + ((jv & 3) * 4 + u * NT) * 64 + t * 16 : sb + SM_XF + qd * 5 * 256 + a_lane,
                          kv ? 64 : 256, off, lo, hi, lane);
                if (kv) {
                    mbar_wait(wrdy, (jv >> 2) & 1);
                    const float w = lsum[16 + (jv & 3) * WPS + u];
                    if (g < 2)
                        asm volatile("red.relaxed.gpu.global.add.v4.f32 [%0], {%1,%2,%3,%4};"
                                     ::"l"(oacc), "f"(w * (g ? lo[0][1] + hi[0][3] : lo[0][0] + hi[0][2])),
                                       "f"(w * (g ? lo[1][1] + hi[1][3] : lo[1][0] + hi[1][2])),
                                       "f"(w * (g ? lo[2][1] + hi[2][3] : lo[2][0] + hi[2][2])), "f"(1.0f) : "memory");
                } else if (g < NB) {
#pragma unroll
                    for (int s = 0; s < 3; s++)
                        st_tag2(g_qpart + (cta * NB + g) * VS + warp * 32 + 2 * t + s * 8, lo[s][0] + hi[s][2], lo[s][1] + hi[s][3], tag);
                }
                if (trig) mbar_arrive(trig);
            }
            const bool pass = j == NSTEP + LA - 1;
            if (pass && tid == 0) TS(5);
            if (kv && !pass) continue;
            if (tid == 0 && j < 0) TS(4);

            {
                constexpr int I0 = 5 + NKV;
                static_assert(((I0 / NS) & 1) == 0 && I0 / NS == (I0 + 7) / NS, "tail items complete an even phase");
                const uint32_t done = bar_full + B_QTRIG;
                uint32_t fb = pass ? bar_full + (I0 % NS) * 8 : done, fs = pass ? 8 : 0, ordy = pass ? bar_full + B_ORDY : done;
                uint32_t off2[3], a[8][4], b[8][3][4], a_addr = sb + SM_HF + a_lane;
#pragma unroll
                for (int s = 0; s < 3; s++) {
                    const uint32_t w64 = lane * 320 + (warp + 8 * s) * 16;
                    off[s] = sb + SM_RING + (I0 % NS) * SLOT + (w64 ^ (((w64 >> 7) & 3) << 4));
                    off2[s] = lane < 24 ? off[s] : off[s] - 8 * 320;
#pragma unroll
                    for (int e = 0; e < 4; e++) { lo[s][e] = 0.f; hi[s][e] = 0.f; }
                }
                const float4* accp = g_acc + (((g & 3) * 4 + qd) * NCW + warp) * ACS + (g >> 2) * 4 + t;
                bf16* outp = out + (g & 3) * DM + qd * 160 + warp * 8 + 2 * t + (g >> 2);
                pin3(off);
                asm volatile("" : "+l"(accp), "+l"(outp), "+r"(a_addr), "+r"(ordy), "+r"(fb), "+r"(fs));
                auto load_b = [&](int i, bool& next) {
                    if (!next) mbar_wait(fb + i * fs, 0);
                    if (i < 7) next = mbar_test(fb + (i + 1) * fs, 0);
#pragma unroll
                    for (int s = 0; s < 3; s++)
                        if (s < 2 || warp < 4) ldsm_x4_t((i < 2 ? off2[s] : off[s]) + i * SLOT, b[i][s]);
                };
                auto mul = [&](int i) {
#pragma unroll
                    for (int s = 0; s < 3; s++)
                        if (s < 2 || warp < 4) { mma16816(lo[s], a[i], b[i][s][0], b[i][s][1]); mma16816(hi[s], a[i], b[i][s][2], b[i][s][3]); }
                };
                bool next = mbar_test(fb, 0);
                mbar_wait(pass ? bar_full + B_HRDY : done, 0);
                lds128(a_addr, a[0]);
                lds128(a_addr + 256, a[1]);
                load_b(0, next);
#pragma unroll
                for (int i = 0; i < 7; i++) {
                    load_b(i + 1, next);
                    if (i == 2) {
                        mbar_wait(ordy, 0);
                        if (pass && tid == 0) TS(7);
#pragma unroll
                        for (int k = 2; k < 8; k++) lds128(a_addr + k * 256, a[k]);
                    }
                    mul(i);
                }
                mul(7);
                if (pass && tid == 0) TS(8);
                add_out(accp, outp, lo, hi, g >= NB, warp < 4, pass, epoch);
            }
        }
        if (tid == 0) { TS(9); TS_DUMP(3, 32); }
    } else {
        float gate[6][2];
#pragma unroll
        for (int s = 0; s < 3; s++) {
            const uint32_t r128 = (lane & 15) * 6 + 2 * s + (lane >> 4);
            off[s] = r128 * 128 + ((warp ^ (r128 & 7)) << 4);
        }
#pragma unroll 1
        for (int ps = 0; ps < 2; ps++) {
#pragma unroll
            for (int s = 0; s < 3; s++) {
                gate[2 * s][0] = lo[s][0]; gate[2 * s][1] = lo[s][1];
                gate[2 * s + 1][0] = hi[s][0]; gate[2 * s + 1][1] = hi[s][1];
            }
            gemv_loop(ring, 40, sb + SM_XF + a_lane, 256, off, lo, hi, lane);
        }
#pragma unroll
        for (int p = 0; p < 6; p++) {
            float hv[2];
#pragma unroll
            for (int e = 0; e < 2; e++) {
                const float gt = bf_round(gate[p][e]);
                hv[e] = bf_round(bf_round(__fdividef(gt, 1.0f + __expf(-gt))) * bf_round((p & 1) ? hi[p >> 1][e] : lo[p >> 1][e]));
            }
            if (g < NB) st_tag2(g_h + g * FF + qd * 384 + p * 64 + warp * 8 + 2 * t, hv[0], hv[1], tag);
        }
        if (tid == 0) { TS(9); TS_DUMP(3, 10); }
    }
}

typedef CUresult (*EncodeFn)(CUtensorMap*, CUtensorMapDataType, cuuint32_t, void*, const cuuint64_t*, const cuuint64_t*,
                             const cuuint32_t*, const cuuint32_t*, CUtensorMapInterleave, CUtensorMapSwizzle,
                             CUtensorMapL2promotion, CUtensorMapFloatOOBfill);

void make_map(EncodeFn enc, CUtensorMap* m, const void* p, uint64_t rows, uint64_t cols, uint32_t inner, uint32_t parts,
              uint32_t box_rows) {
    const cuuint64_t dims[3] = {inner, cols / inner, rows};
    const cuuint64_t strides[2] = {inner * 2ull, cols * 2ull};
    const cuuint32_t box[3] = {inner, parts, box_rows};
    const cuuint32_t es[3] = {1, 1, 1};
    enc(m, CU_TENSOR_MAP_DATA_TYPE_BFLOAT16, 3, const_cast<void*>(p), dims, strides, box, es, CU_TENSOR_MAP_INTERLEAVE_NONE,
        inner == 64 ? CU_TENSOR_MAP_SWIZZLE_128B : CU_TENSOR_MAP_SWIZZLE_64B, CU_TENSOR_MAP_L2_PROMOTION_NONE,
        CU_TENSOR_MAP_FLOAT_OOB_FILL_NONE);
}

}

extern "C" void kernel_launch(void* const* d_in, const int* in_sizes, int n_in, void* d_out, int out_size) {
    (void)in_sizes; (void)n_in; (void)out_size;
    static EncodeFn enc = nullptr;
    if (!enc) {
        void* fn = nullptr;
        cudaDriverEntryPointQueryResult qr;
        cudaGetDriverEntryPoint("cuTensorMapEncodeTiled", &fn, cudaEnableDefault, &qr);
        enc = (EncodeFn)fn;
        cudaFuncSetAttribute(fused_decode_kernel, cudaFuncAttributeMaxDynamicSharedMemorySize, SM_TOTAL);
    }
    Maps maps;
    make_map(enc, &maps.k, d_in[1], (uint64_t)NB * NH * SK, DH, 64, 3, TK);
    make_map(enc, &maps.v, d_in[2], (uint64_t)NB * NH * SK, DH, 64, 3, TK);
    make_map(enc, &maps.wq, d_in[3], DM, NH * DH, 64, 3, 32);
    make_map(enc, &maps.wo, d_in[4], NH * DH, DM, 32, 5, 32);
    make_map(enc, &maps.w1, d_in[6], DM, FF, 64, 6, 16);
    make_map(enc, &maps.w3, d_in[7], DM, FF, 64, 6, 16);
    make_map(enc, &maps.w2, d_in[8], FF, DM, 32, 5, 24);
    fused_decode_kernel<<<NCTA, NTHR, SM_TOTAL>>>((const char*)d_in[3], (const bf16*)d_in[0], (bf16*)d_out,
                                                  (const char*)d_in[1], (const char*)d_in[2], maps);
}
```

```cpp
#include <cuda_runtime.h>
#include <cuda.h>
#include <cuda_bf16.h>
#include <stdint.h>

namespace {

typedef __nv_bfloat16 bf16;

constexpr int NB = 4, DM = 640, NH = 32, DH = 192, SK = 8192, WIN = 2048, FF = 1536;

#define P_G 32
#define P_DEPTH 4
#define P_DEPTH_FFN 5
#define P_GAIN 6
#define P_BIAS 16
#define P_SLEEP 500
#define P_DMIN 3
#define P_DMAX 6
#define P_SETTLE 3000
#define P_QDELAY 1600
#define P_LA 2
#define P_MLS 8
#define P_OAL 72
#define P_PF 64
#define P_TLB 3
#define P_DT 3
#define P_DT0 5
#define P_PREW 1
#define P_MLDELAY 3000
#define P_NS 16

constexpr int G = P_G;
constexpr int TK = 32;
constexpr int NT = WIN / TK / G;
constexpr int NSTEP = 16;
constexpr int WPS = G / NSTEP;
constexpr int LA = P_LA;
constexpr int MLS = P_MLS;
constexpr int OAL = P_OAL;
constexpr int HSTEP = 11;
constexpr int NS = P_NS;
constexpr int SLOT = 12288;
constexpr int DEPTH = P_DEPTH;
#define P_D0 5
constexpr int DEPTH0 = P_D0;
static_assert(DEPTH0 <= 5, "DEPTH0");
constexpr int NATT = 128, NFFN = 4, NCTA = NATT + NFFN;
constexpr int NCW = 8;
constexpr int NXW = 2;
constexpr int W_PROD = NCW, W_PACE = NCW + 1 + NXW;
constexpr int NTHR = (W_PACE + 1) * 32;
constexpr int NSRC = NH;
constexpr int VS = 256;
#define P_ACS 72
constexpr int ACS = P_ACS;
static_assert(G == 16 || G == 32 || G == 64, "G");

constexpr int SM_RING = 0;
constexpr int SM_XF = SM_RING + NS * SLOT;
constexpr int SM_QS = SM_XF + 20 * 256;
constexpr int SM_PF = SM_QS + G * DH * 2;
constexpr int SM_HF = SM_PF + 4 * 4 * 64;
constexpr int SM_OF = SM_HF + 2 * 256;
constexpr int SM_LS = SM_OF + 6 * 256;
constexpr int SM_ATT_END = SM_LS + 128;
constexpr int SM_FFN_END = SM_XF + 40 * 256;
constexpr int SM_BAR = SM_ATT_END > SM_FFN_END ? SM_ATT_END : SM_FFN_END;
constexpr int B_QRDY = 2 * NS * 8, B_ORDY = B_QRDY + NSTEP * 8, B_OTRIG = B_ORDY + 8, B_QTRIG = B_OTRIG + 32,
              B_WTRIG = B_QTRIG + 8, B_WRDY = B_WTRIG + 32, B_HTRIG = B_WRDY + 32, B_HRDY = B_HTRIG + 8,
              NBAR = 2 * NS + NSTEP + 16;
constexpr int SM_PACE = SM_BAR + NBAR * 8;
constexpr int SM_TS = SM_PACE + 24;
constexpr int SM_TOTAL = SM_TS + 256;
static_assert(SM_TOTAL <= 232448, "smem");

constexpr int NKV = 2 * NT * G;
constexpr int ITEMS_ATT = 5 + NKV + 2 + 6;
constexpr int ITEMS_FFN = 80;

struct Maps { CUtensorMap k, v, wq, wo, w1, w3, w2; };

struct alignas(32) Sync { unsigned epoch, inits, prog[2]; };
__device__ Sync g_sync;
__device__ __align__(128) float g_qpart[NATT * NB * VS];
__device__ __align__(128) float g_ml[NATT * G * MLS];
__device__ __align__(128) float g_h[NB * FF];
__device__ __align__(128) float4 g_oacc[NATT * 8 * OAL];
__device__ __align__(128) float4 g_acc[NB * 4 * NCW * ACS];
#define TS(i)
#define TS_DUMP(lo, hi)

constexpr unsigned SPIN_LIMIT = 1u << 22;

__device__ __forceinline__ void mbar_init(uint32_t bar, int cnt) {
    asm volatile("mbarrier.init.shared::cta.b64 [%0], %1;" ::"r"(bar), "r"(cnt) : "memory");
}
__device__ __forceinline__ void mbar_expect_tx(uint32_t bar, uint32_t bytes) {
    asm volatile("mbarrier.arrive.expect_tx.shared::cta.b64 _, [%0], %1;" ::"r"(bar), "r"(bytes) : "memory");
}
__device__ __forceinline__ void mbar_arrive(uint32_t bar) {
    asm volatile("mbarrier.arrive.shared::cta.b64 _, [%0];" ::"r"(bar) : "memory");
}
__device__ __forceinline__ void mbar_wait(uint32_t bar, uint32_t parity) {
    asm volatile("{\n.reg .pred p, q;\n.reg .u32 n;\nmov.u32 n, 0;\n"
                 "W: mbarrier.try_wait.parity.shared::cta.b64 p, [%0], %1;\n"
                 "@p bra D;\nadd.u32 n, n, 1;\nsetp.lt.u32 q, n, %2;\n@q bra W;\ntrap;\nD:\n}"
                 ::"r"(bar), "r"(parity), "n"(SPIN_LIMIT) : "memory");
}
__device__ __forceinline__ bool mbar_test(uint32_t bar, uint32_t parity) {
    uint32_t ok;
    asm volatile("{\n.reg .pred p;\nmbarrier.test_wait.parity.shared::cta.b64 p, [%1], %2;\nselp.u32 %0, 1, 0, p;\n}"
                 : "=r"(ok) : "r"(bar), "r"(parity) : "memory");
    return ok;
}
__device__ __forceinline__ void tma3d(uint32_t dst, const CUtensorMap* map, int c1, int c2, uint32_t bar) {
    const uint64_t pol = 0x12F0000000000000ull;
    asm volatile("cp.async.bulk.tensor.3d.shared::cluster.global.mbarrier::complete_tx::bytes.L2::cache_hint "
                 "[%0], [%1, {%2, %3, %4}], [%5], %6;"
                 ::"r"(dst), "l"(map), "r"(0), "r"(c1), "r"(c2), "r"(bar), "l"(pol) : "memory");
}
__device__ __forceinline__ void ldsm_x4(uint32_t addr, uint32_t (&r)[4]) {
    asm volatile("ldmatrix.sync.aligned.m8n8.x4.shared.b16 {%0,%1,%2,%3}, [%4];"
                 : "=r"(r[0]), "=r"(r[1]), "=r"(r[2]), "=r"(r[3]) : "r"(addr) : "memory");
}
__device__ __forceinline__ void ldsm_x4_t(uint32_t addr, uint32_t (&r)[4]) {
    asm volatile("ldmatrix.sync.aligned.m8n8.x4.trans.shared.b16 {%0,%1,%2,%3}, [%4];"
                 : "=r"(r[0]), "=r"(r[1]), "=r"(r[2]), "=r"(r[3]) : "r"(addr) : "memory");
}
__device__ __forceinline__ void lds128(uint32_t addr, uint32_t (&r)[4]) {
    asm volatile("ld.shared.v4.u32 {%0,%1,%2,%3}, [%4];"
                 : "=r"(r[0]), "=r"(r[1]), "=r"(r[2]), "=r"(r[3]) : "r"(addr) : "memory");
}
__device__ __forceinline__ void mma16816(float (&c)[4], const uint32_t (&a)[4], uint32_t b0, uint32_t b1) {
    asm volatile("mma.sync.aligned.m16n8k16.row.col.f32.bf16.bf16.f32 {%0,%1,%2,%3}, {%4,%5,%6,%7}, {%8,%9}, {%0,%1,%2,%3};"
                 : "+f"(c[0]), "+f"(c[1]), "+f"(c[2]), "+f"(c[3])
                 : "r"(a[0]), "r"(a[1]), "r"(a[2]), "r"(a[3]), "r"(b0), "r"(b1));
}
__device__ __forceinline__ void cons_bar() { asm volatile("bar.sync 1, 256;" ::: "memory"); }

__device__ __forceinline__ float bf_round(float v) { return __bfloat162float(__float2bfloat16_rn(v)); }
__device__ __forceinline__ uint32_t pack_bf2(float lo, float hi) {
    __nv_bfloat162 t = __floats2bfloat162_rn(lo, hi);
    return *reinterpret_cast<uint32_t*>(&t);
}
__device__ __forceinline__ float bf_lo(uint32_t u) { return __uint_as_float(u << 16); }
__device__ __forceinline__ float bf_hi(uint32_t u) { return __uint_as_float(u & 0xffff0000u); }
__device__ __forceinline__ float shx(float v, int o) { return __shfl_xor_sync(0xffffffffu, v, o); }

__device__ __forceinline__ uint32_t frag_off(uint32_t k) {
    return ((k >> 1) & 3) * 16 + ((k >> 3) & 1) * 8 + ((k >> 4) & 1) * 4 + (k & 1) * 2;
}

__device__ __forceinline__ void st_tag2(float* p, float a, float b, uint32_t tag) {
    asm volatile("{\n.reg .b64 w;\n.reg .b32 x;\nlop3.b32 x, %1, 0xfffffffe, %3, 0xea;\nmov.b64 w, {x, %2};\n"
                 "st.relaxed.gpu.global.b64 [%0], w;\n}"
                 ::"l"(p), "r"(__float_as_uint(a)), "r"(__float_as_uint(b)), "r"(tag) : "memory");
}
__device__ __forceinline__ void st_fill4(float* p, uint32_t v) {
    asm volatile("{\n.reg .b64 w;\nmov.b64 w, {%1, %1};\nst.relaxed.gpu.global.v2.b64 [%0], {w, w};\n}" ::"l"(p), "r"(v) : "memory");
}
__device__ __forceinline__ uint2 ld_word(const float* p) {
    uint2 v;
    asm volatile("{\n.reg .b64 w;\nld.relaxed.gpu.global.b64 w, [%2];\nmov.b64 {%0,%1}, w;\n}" : "=r"(v.x), "=r"(v.y) : "l"(p) : "memory");
    return v;
}
__device__ __forceinline__ uint4 ld_word2(const float* p) {
    uint4 v;
    asm volatile("{\n.reg .b64 w0, w1;\nld.relaxed.gpu.global.v2.b64 {w0, w1}, [%4];\nmov.b64 {%0,%1}, w0;\nmov.b64 {%2,%3}, w1;\n}"
                 : "=r"(v.x), "=r"(v.y), "=r"(v.z), "=r"(v.w) : "l"(p) : "memory");
    return v;
}

__device__ __forceinline__ void add_out(const float4* acc, bf16* out, const float (&lo)[3][4], const float (&hi)[3][4],
                                        bool odd, bool third, bool live, uint32_t epoch) {
    const float v0 = odd ? lo[0][1] + hi[0][3] : lo[0][0] + hi[0][2];
    const float v1 = odd ? lo[1][1] + hi[1][3] : lo[1][0] + hi[1][2];
    const float v2 = odd ? lo[2][1] + hi[2][3] : lo[2][0] + hi[2][2];
    float o0, o1, o2, n = 0.f;
    asm volatile("{\n.reg .pred p;\nsetp.ne.u32 p, %5, 0;\n"
                 "@p atom.relaxed.gpu.global.add.v4.f32 {%0,%1,%2,%3}, [%4], {%6,%7,%8,%9};\n}"
                 : "=f"(o0), "=f"(o1), "=f"(o2), "+f"(n)
                 : "l"(acc), "r"((uint32_t)live), "f"(v0), "f"(v1), "f"(v2), "f"(1.0f) : "memory");
    asm volatile("{\n.reg .pred p, q;\nsetp.eq.f32 p, %4, %5;\nsetp.ne.and.u32 q, %6, 0, p;\n"
                 "@p st.global.u16 [%0], %1;\n@p st.global.u16 [%0+128], %2;\n@q st.global.u16 [%0+256], %3;\n}"
                 ::"l"(out), "h"(__bfloat16_as_ushort(__float2bfloat16_rn(o0 + v0))),
                   "h"(__bfloat16_as_ushort(__float2bfloat16_rn(o1 + v1))), "h"(__bfloat16_as_ushort(__float2bfloat16_rn(o2 + v2))),
                   "f"(n), "f"((float)(NSRC - 1)), "r"((uint32_t)third) : "memory");
    if (acc == g_acc && n == (float)(NSRC - 1))
        asm volatile("st.relaxed.gpu.global.u32 [%0], %1;" ::"l"(&g_sync.epoch), "r"(epoch + 1u) : "memory");
}

__device__ __forceinline__ int pair_of(int sg, uint32_t j) { return sg * G + (j % (G / 4)) * 4 + j / (G / 4); }
__device__ __forceinline__ int order_of(int r, int b) { return b * (G / 4) + (r >> 2); }

__device__ __forceinline__ int window_row(int sg, uint32_t u, bool& isv) {
    const uint32_t blk = u / 4;
    isv = blk >= 2 * NSTEP - LA || (blk >= LA && ((blk - LA) & 1));
    const uint32_t step = blk < LA ? blk : blk >= 2 * NSTEP - LA ? blk - NSTEP : (blk - LA) / 2 + (isv ? 0 : LA);
    const int pair = pair_of(sg, step * WPS + (u % 4) / NT);
    return ((pair & 3) * NH + (pair >> 2)) * SK + (SK - WIN);
}

__device__ __forceinline__ float4* ocell(uint32_t pair, uint32_t i) {
    return g_oacc + (pair * 8 + (i >> 3)) * OAL + (i & 7);
}

__device__ __forceinline__ void settle(int cycles) {
    const uint32_t t0 = (uint32_t)clock();
    while ((uint32_t)clock() - t0 < (uint32_t)cycles) __nanosleep(20);
}

struct Ring {
    uint32_t full, addr, phase, first_full;
    __device__ __forceinline__ void wait() const { mbar_wait(full, phase); }
    __device__ __forceinline__ void skip(int n) {
        full += n * 8; addr += n * SLOT;
        if (full >= first_full + NS * 8) { full -= NS * 8; addr -= NS * SLOT; phase ^= 1; }
    }
    __device__ __forceinline__ void release(int lane) {
        __syncwarp();
        if (lane == 0) mbar_arrive(full + NS * 8);
        full += 8; addr += SLOT;
        if (full == first_full + NS * 8) { full = first_full; addr -= NS * SLOT; phase ^= 1; }
    }
};

__device__ __forceinline__ void pin3(uint32_t (&v)[3]) {
    asm volatile("" : "+r"(v[0]), "+r"(v[1]), "+r"(v[2]));
}
__device__ __forceinline__ void gemv_loop(Ring& ring, int n, uint32_t a_addr, uint32_t a_step, uint32_t (&off)[3],
                                          float (&lo)[3][4], float (&hi)[3][4], int lane) {
    pin3(off);
#pragma unroll
    for (int s = 0; s < 3; s++)
#pragma unroll
        for (int e = 0; e < 4; e++) { lo[s][e] = 0.f; hi[s][e] = 0.f; }
#pragma unroll 1
    for (int it = 0; it < n; it++) {
        uint32_t a[4], b[3][4];
        lds128(a_addr, a);
        a_addr += a_step;
        ring.wait();
#pragma unroll
        for (int s = 0; s < 3; s++) ldsm_x4_t(ring.addr + off[s], b[s]);
#pragma unroll
        for (int s = 0; s < 3; s++) { mma16816(lo[s], a, b[s][0], b[s][1]); mma16816(hi[s], a, b[s][2], b[s][3]); }
        ring.release(lane);
    }
}

__global__ void __launch_bounds__(NTHR, 1)
fused_decode_kernel(const char* __restrict__ wq, const bf16* __restrict__ x, bf16* __restrict__ out,
                    const char* __restrict__ kc, const char* __restrict__ vc, const __grid_constant__ Maps maps) {
    asm volatile("{\n.reg .pred p;\n.reg .b32 t, c, a, b;\n.reg .b64 o;\n"
                 "mov.u32 t, %%tid.x;\nmov.u32 c, %%ctaid.x;\n"
                 "and.b32 a, c, 3;\nshr.u32 c, c, 2;\nmul.lo.u32 a, a, 15360;\nmad.lo.u32 a, c, 3, a;\n"
                 "shr.u32 b, t, 2;\nmad.lo.u32 a, b, 92, a;\nadd.u32 a, a, t;\nmad.wide.u32 o, a, 128, %0;\n"
                 "and.b32 b, t, 3;\nsetp.ne.u32 p, b, 3;\nsetp.lt.and.u32 p, t, %1, p;\n@p prefetch.global.L2 [o];\n}"
                 ::"l"(wq), "n"(P_PF * 4) : "memory");
    extern __shared__ __align__(1024) unsigned char smem[];
    const uint32_t sb = (uint32_t)__cvta_generic_to_shared(smem);
    const uint32_t bar_full = sb + SM_BAR;
    if (threadIdx.x == 0 && blockIdx.x < NATT) {
        TS(0);
#pragma unroll 1
        for (int i = 0; i < DEPTH0; i++) {
            mbar_init(bar_full + i * 8, 1);
            mbar_expect_tx(bar_full + i * 8, 12288);
            tma3d(sb + SM_RING + i * SLOT, &maps.wq, (blockIdx.x >> 2) * 3, (blockIdx.x & 3) * 160 + i * 32, bar_full + i * 8);
        }
        TS(1);
    }
    unsigned ptid, cta;
    asm volatile("mov.u32 %0, %%tid.x;\nmov.u32 %1, %%ctaid.x;" : "=r"(ptid), "=r"(cta));
    const int tid = ptid < 32 ? ptid + NCW * 32 : ptid < (NCW + 1) * 32 ? ptid - 32 : ptid;
    const int warp = tid >> 5, lane = tid & 31;
    const bool is_att = cta < NATT;
    const int h = cta >> 2, qd = cta & 3;
    const int sg = cta / G, r = cta % G;

    if (warp == NCW) {
        volatile int* pace = reinterpret_cast<volatile int*>(smem + SM_PACE);
        if (lane == 0) {
            if (!is_att) { TS(0); TS(1); }
            pace[0] = 0;
            pace[1] = is_att ? DEPTH : P_DEPTH_FFN;
#pragma unroll
            for (int i = 0; i < NBAR; i++)
                if (i >= DEPTH0 || !is_att)
                mbar_init(bar_full + i * 8, i < NS ? 1 : i < 2 * NS ? NCW : i < 2 * NS + NSTEP ? NXW : i == 2 * NS + NSTEP ? NXW * NB : i == NBAR - 1 ? NXW : 1);
            asm volatile("fence.mbarrier_init.release.cluster;" ::: "memory");
        }
        __syncwarp();
        asm volatile("bar.arrive 2, %0;" ::"n"(NTHR) : "memory");
        if (lane == 0) {
            const int n_items = is_att ? ITEMS_ATT : ITEMS_FFN;

            asm volatile("prefetch.tensormap [%0];" ::"l"(is_att ? &maps.k : &maps.w3) : "memory");
            asm volatile("prefetch.tensormap [%0];" ::"l"(&maps.v) : "memory");
            asm volatile("prefetch.tensormap [%0];" ::"l"(&maps.w2) : "memory");
            asm volatile("prefetch.tensormap [%0];" ::"l"(&maps.wo) : "memory");
#pragma unroll 1
            for (int i = is_att ? DEPTH0 : 0; i < n_items; i++) {
                const CUtensorMap* map;
                int c1, c2;
                uint32_t bytes = 12288;
                if (is_att) {
                    const uint32_t u = i - 5;
                    if (u < NKV) {
                        bool isv;
                        c2 = window_row(sg, u, isv) + ((u % NT) * G + r) * TK;
                        map = isv ? &maps.v : &maps.k;
                        c1 = 0;
                    } else if (i < 5) {
                        map = &maps.wq; c1 = h * 3; c2 = qd * 160 + i * 32;
                    } else if (u < NKV + 2) {
                        map = &maps.w2; c1 = qd * 5; c2 = h * 48 + (u - NKV) * 24; bytes = 7680;
                    } else {
                        map = &maps.wo; c1 = qd * 5; c2 = h * DH + (u - NKV - 2) * 32; bytes = 10240;
                    }
                } else {
                    map = i < 40 ? &maps.w1 : &maps.w3; c1 = qd * 6; c2 = (i < 40 ? i : i - 40) * 16;
                }
                const int depth = pace[1] + (is_att && i >= 5 + NKV + P_DT0 ? P_DT : 0);
                const uint32_t slot = (uint32_t)i % NS, landed = i - depth;
                if (i >= NS) mbar_wait(bar_full + (NS + slot) * 8, ((uint32_t)i / NS - 1) & 1);
                mbar_expect_tx(bar_full + slot * 8, bytes);
                uint32_t dst = sb + SM_RING + slot * SLOT, fb = bar_full + slot * 8;
                asm volatile("" : "+r"(dst), "+r"(fb), "+l"(map), "+r"(c1), "+r"(c2));
                if (i >= depth) mbar_wait(bar_full + (landed % NS) * 8, (landed / NS) & 1);
                tma3d(dst, map, c1, c2, fb);
                pace[0] = landed + 1;
                const uint32_t un = i - 5 + P_TLB;
                if (is_att && un < NKV && un % NT == 0 && r == (un / NT) % G) {
                    bool isv;
                    const int row = window_row(sg, un, isv);
                    asm volatile("prefetch.global.L2 [%0];" ::"l"((isv ? vc : kc) + (size_t)row * (DH * 2)) : "memory");
                }
            }
            pace[0] = n_items - DEPTH;
        }
        return;
    }

    const int g = lane >> 2, t = lane & 3;
    uint32_t epoch;
    asm volatile("ld.relaxed.gpu.global.u32 %0, [%1];" : "=r"(epoch) : "l"(&g_sync.epoch) : "memory");

    if (warp == W_PACE) {
        const uint32_t tag = (epoch + 1u) & 1u;
        if (is_att && (P_PREW & 1)) {
#pragma unroll
            for (int u = 0; u < WPS; u++) st_fill4(g_ml + ((sg * G + u * 16 + (lane >> 1)) * G + r) * MLS + (lane & 1) * 4, tag ^ 1u);
        }
        asm volatile("bar.sync 2, %0;" ::"n"(NTHR) : "memory");
        if (lane == 0) asm volatile("red.release.gpu.global.add.u32 [%0], 1;" ::"l"(&g_sync.inits) : "memory");
        if (!is_att) return;
        volatile int* pace = reinterpret_cast<volatile int*>(smem + SM_PACE);
        if (cta == 0 && lane == 0) asm volatile("st.relaxed.gpu.global.u32 [%0], %1;" ::"l"(&g_sync.prog[epoch & 1u]), "r"(0u) : "memory");
        int reported = 0, j = 0;
        bool due = false;
#pragma unroll 1
        for (unsigned it = 0;; it++) {
            const int landed = pace[0];
            if (j == NSTEP && landed >= ITEMS_ATT - DEPTH) {
                if (lane == 0)
                    asm volatile("red.relaxed.gpu.global.add.u32 [%0], %1;" ::"l"(&g_sync.prog[~epoch & 1u]), "r"(landed - reported) : "memory");
                return;
            }
            int sum = 0;
            constexpr int RPL = (G + 31) / 32;
            uint2 ml[WPS][RPL];
            uint32_t bad = 1u;
            unsigned n = (epoch + 1u) * NCTA;
            if (lane == 0)
                asm volatile("atom.relaxed.gpu.global.add.u32 %0, [%1], %2;"
                             : "=r"(sum) : "l"(&g_sync.prog[~epoch & 1u]), "r"(landed - reported) : "memory");
            if (due) {
#pragma unroll
                for (int u = 0; u < WPS; u++)
#pragma unroll
                    for (int k = 0; k < RPL; k++) ml[u][k] = ld_word(g_ml + (pair_of(sg, j * WPS + u) * G + k * 32 + lane % G) * MLS);
                if (j == 0) asm volatile("ld.acquire.gpu.global.u32 %0, [%1];" : "=r"(n) : "l"(&g_sync.inits) : "memory");
            }
            reported = landed;
            if (lane == 0 && P_GAIN) {
                const int lag16 = sum / (NATT / 16) - landed * 16 + P_BIAS;
                pace[1] = min(max(DEPTH + ((lag16 * P_GAIN + 128) >> 8), P_DMIN), P_DMAX);
            }
            if (due) {
                bad = 0;
#pragma unroll
                for (int u = 0; u < WPS; u++)
#pragma unroll
                    for (int k = 0; k < RPL; k++) bad |= ml[u][k].x ^ tag;
            }
            if (__all_sync(0xffffffffu, !(bad & 1u) && n == (epoch + 1u) * NCTA)) {
#pragma unroll
                for (int u = 0; u < WPS; u++) {
                    float M = -INFINITY, L = 0.f, w = 0.f;
#pragma unroll
                    for (int k = 0; k < RPL; k++) M = fmaxf(M, __uint_as_float(ml[u][k].x & ~1u));
#pragma unroll
                    for (int o = G / RPL / 2; o; o >>= 1) M = fmaxf(M, shx(M, o));
#pragma unroll
                    for (int k = 0; k < RPL; k++) {
                        const float wk = __expf(__uint_as_float(ml[u][k].x & ~1u) - M);
                        L += wk * __uint_as_float(ml[u][k].y);
                        if (k == r / 32) w = wk;
                    }
#pragma unroll
                    for (int o = G / RPL / 2; o; o >>= 1) L += shx(L, o);
                    if (lane == r % 32) reinterpret_cast<float*>(smem + SM_LS)[16 + (j & 3) * WPS + u] = __fdividef(w, L);
                }
                if (lane == r % 32) {
                    mbar_arrive(bar_full + B_WRDY + (j & 3) * 8);
                    if (j == NSTEP - 1) TS(11);
                }
                j++;
                due = false;
            }
            __nanosleep(P_SLEEP);
            if (!due && j < NSTEP && mbar_test(bar_full + B_WTRIG + (j & 3) * 8, (j >> 2) & 1))
                due = (uint32_t)clock() - (uint32_t)pace[2 + (j & 3)] >= P_MLDELAY;
            if (it > SPIN_LIMIT) __trap();
        }
    }
    if (warp > W_PROD) {
        const uint32_t tag = (epoch + 1u) & 1u;
        const int e = tid - (W_PROD + 1) * 32;
        if (is_att) {
            st_fill4(reinterpret_cast<float*>(ocell(cta, e)), 0u);
            if (e < 32) *reinterpret_cast<uint32_t*>(smem + SM_HF + e * 16 + 12) = 0u;
        } else {
#pragma unroll 1
            for (int c = e; c < 256; c += NXW * 32) {
                const bf16* xp = x + qd * DM + (c >> 6) * 160 + ((c >> 3) & 7) * 8 + (c & 3) * 2 + ((c >> 2) & 1);
                asm volatile("st.relaxed.gpu.global.v4.f32 [%0], {%1,%2,%3,%4};"
                             ::"l"(g_acc + (qd * 32 + (c >> 3)) * ACS + (c & 7)), "f"(__bfloat162float(xp[0])),
                               "f"(__bfloat162float(xp[64])), "f"((c & 32) ? 0.f : __bfloat162float(xp[128])), "f"(0.f) : "memory");
            }
        }
        asm volatile("bar.sync 2, %0;" ::"n"(NTHR) : "memory");
        if (!is_att) return;
        {
            const uint32_t eq = (e >> 5) * 24 + min(lane, 23), xw = eq / 6, xr = eq % 6;
            mbar_wait(bar_full + B_QTRIG, 0);
            if (e == 0) TS(10);
            settle(P_QDELAY);
#pragma unroll 1
            for (int j = 0; j < NSTEP; j++) {
                uint4 v[WPS][4];
                uint32_t bad;
                unsigned spin = 0;
                do {
#pragma unroll
                    for (int u = 0; u < WPS; u++) {
                        const int pair = pair_of(sg, j * WPS + u);
                        const float* src = g_qpart + ((pair >> 2) * 4 * NB + (pair & 3)) * VS + xw * 32 + xr * 4;
#pragma unroll
                        for (int k = 0; k < 4; k++) v[u][k] = ld_word2(src + k * NB * VS);
                    }
                    bad = 0;
#pragma unroll
                    for (int u = 0; u < WPS; u++)
#pragma unroll
                        for (int k = 0; k < 4; k++) bad |= (v[u][k].x ^ tag) | (v[u][k].z ^ tag);
                    if (++spin > SPIN_LIMIT) __trap();
                } while (bad & 1u);
#define SUM4(c) ((__uint_as_float(v[u][0].c) + __uint_as_float(v[u][1].c)) + (__uint_as_float(v[u][2].c) + __uint_as_float(v[u][3].c)))
#pragma unroll
                for (int u = 0; u < WPS; u++) {
                    unsigned char* dst = smem + SM_QS + (j * WPS + u) * (DH * 2) + (xr & 1) * 192 + ((xr >> 1) * 8 + xw) * 4;
                    *reinterpret_cast<uint32_t*>(dst) = pack_bf2(SUM4(x), SUM4(y));
                    *reinterpret_cast<uint32_t*>(dst + 96) = pack_bf2(SUM4(z), SUM4(w));
                }
#undef SUM4
                __syncwarp();
                if (lane == 0) mbar_arrive(bar_full + B_QRDY + j * 8);
                if (e == 0 && j == 0) TS(12);
            }
        }
        bool have_h = false;
#pragma unroll 1
        for (int b = 0; b <= NB; b++) {
            if (!have_h && (b == NB || order_of(r, b) >= HSTEP * WPS)) {
                have_h = true;
                mbar_wait(bar_full + B_HTRIG, 0);
#pragma unroll 1
                for (int i = e; i < 96; i += NXW * 32) {
                    const int k = (i % 24) * 2;
                    uint2 v;
                    unsigned spin = 0;
                    do {
                        v = ld_word(g_h + i / 24 * FF + h * 48 + k);
                        if (++spin > SPIN_LIMIT) __trap();
                    } while ((v.x ^ tag) & 1u);
                    *reinterpret_cast<uint32_t*>(smem + SM_HF + k / 24 * 256 + i / 24 * 64 + frag_off(k % 24)) = __byte_perm(v.x, v.y, 0x7632);
                }
                __syncwarp();
                if (lane == 0) mbar_arrive(bar_full + B_HRDY);
            }
            if (b == NB) break;
            const float4* src = ocell(h * NB + b, e);
            uint32_t dst = sb + SM_OF + (e >> 5) * 256 + b * 64 + frag_off(lane), ordy = bar_full + B_ORDY;
            asm volatile("" : "+r"(dst), "+l"(src), "+r"(ordy));
            mbar_wait(bar_full + B_OTRIG + b * 8, 0);
            const int pause = order_of(r, b) < G - WPS ? P_SETTLE : 0;
            unsigned spin = 0;
            float o0, o1, o2, n;
            do {
                settle(pause);
                asm volatile("{\n.reg .b128 w;\n.reg .b64 w0, w1;\nld.relaxed.gpu.global.b128 w, [%4];\nmov.b128 {w0, w1}, w;\n"
                             "mov.b64 {%0,%1}, w0;\nmov.b64 {%2,%3}, w1;\n}"
                             : "=f"(o0), "=f"(o1), "=f"(o2), "=f"(n) : "l"(src) : "memory");

                asm volatile("st.shared.u16 [%0], %1;\nst.shared.u16 [%0+512], %2;\nst.shared.u16 [%0+1024], %3;"
                             ::"r"(dst), "h"(__bfloat16_as_ushort(__float2bfloat16_rn(o0))),
                               "h"(__bfloat16_as_ushort(__float2bfloat16_rn(o1))), "h"(__bfloat16_as_ushort(__float2bfloat16_rn(o2))) : "memory");
                if (++spin > SPIN_LIMIT) __trap();
            } while (n != (float)G);
            __syncwarp();
            if (lane == 0) mbar_arrive(ordy);
        }
        return;
    }

    if (warp < NB) {
        uint2 raw[5];
#pragma unroll
        for (int i = 0; i < 5; i++) raw[i] = __ldg(reinterpret_cast<const uint2*>(x + warp * DM) + i * 32 + lane);
        float s = 0.f;
#pragma unroll
        for (int i = 0; i < 5; i++) s += (bf_lo(raw[i].x) + bf_hi(raw[i].x)) + (bf_lo(raw[i].y) + bf_hi(raw[i].y));
#pragma unroll
        for (int o = 16; o; o >>= 1) s += shx(s, o);
        const float mean = s * (1.0f / DM);
        float q2 = 0.f;
#pragma unroll
        for (int i = 0; i < 5; i++) {
            const float d0 = bf_lo(raw[i].x) - mean, d1 = bf_hi(raw[i].x) - mean;
            const float d2 = bf_lo(raw[i].y) - mean, d3 = bf_hi(raw[i].y) - mean;
            q2 += (d0 * d0 + d1 * d1) + (d2 * d2 + d3 * d3);
        }
#pragma unroll
        for (int o = 16; o; o >>= 1) q2 += shx(q2, o);
        const float mb = bf_round(mean);
        const float rs = __frcp_rn(bf_round(__fsqrt_rn(bf_round(bf_round(q2 * (1.0f / DM)) + 1e-5f))));
        const uint32_t k = (lane * 4) & 31;
        unsigned char* dst = smem + SM_XF + warp * 64 +
            (is_att ? (lane >> 3) * 256 + frag_off(k) : (lane >> 2) * 256 + frag_off(k & 15));
        const uint32_t step = is_att ? 1024 : 2048;
#pragma unroll
        for (int i = 0; i < 5; i++) {
            const uint32_t d0 = pack_bf2(bf_lo(raw[i].x) - mb, bf_hi(raw[i].x) - mb);
            const uint32_t d1 = pack_bf2(bf_lo(raw[i].y) - mb, bf_hi(raw[i].y) - mb);
            *reinterpret_cast<uint32_t*>(dst + i * step) = pack_bf2(bf_lo(d0) * rs, bf_hi(d0) * rs);
            *reinterpret_cast<uint32_t*>(dst + i * step + 16) = pack_bf2(bf_lo(d1) * rs, bf_hi(d1) * rs);
        }
    }
    asm volatile("bar.sync 2, %0;" ::"n"(NTHR) : "memory");
    uint32_t tag = (epoch + 1u) & 1u;
    asm volatile("" : "+r"(tag));
    if (tid == 0) TS(3);

    Ring ring{bar_full, sb + SM_RING, 0u, bar_full};
    float lo[3][4] = {}, hi[3][4] = {};
    uint32_t off[3];
    const uint32_t a_lane = (g & 3) * 64 + t * 16;

    if (is_att) {
        float* lsum = reinterpret_cast<float*>(smem + SM_LS);
#pragma unroll 1
        for (int j = -1; j < NSTEP + LA; j++) {
            if (j >= 0 && j < NSTEP) {
                constexpr int WW = NCW / WPS;
                const int win = j * WPS + warp / WW;
                uint32_t qf[6][4];
                mbar_wait(bar_full + B_QRDY + j * 8, 0);
                if (j == 0 && tid == 0) TS(6);
#pragma unroll
                for (int i = 0; i < 6; i++) lds128(sb + SM_QS + win * (DH * 2) + t * 96 + i * 16, qf[i]);
                const uint32_t key = (warp & 1) * 16 + (lane & 15);
                const uint32_t item = 5 + (j + max(j - LA, 0)) * 4 + (warp >> 1), slot = item % NS;
#pragma unroll
                for (int s = 0; s < 3; s++)
                    off[s] = sb + SM_RING + slot * SLOT + key * 384 + s * 128 + (((lane >> 4) ^ ((3 * key + s) & 7)) << 4);
                pin3(off);
                mbar_wait(bar_full + slot * 8, (item / NS) & 1);
                float c[3][4] = {};
#pragma unroll
                for (int dq = 0; dq < 4; dq++)
#pragma unroll
                    for (int s = 0; s < 3; s++) {
                        uint32_t a[4];
                        ldsm_x4(off[s] ^ (dq << 5), a);
                        mma16816(c[s], a, qf[s * 2 + (dq >> 1)][(dq & 1) * 2], qf[s * 2 + (dq >> 1)][(dq & 1) * 2 + 1]);
                    }
                __syncwarp();
                if (lane == 0)
                    asm volatile("mbarrier.arrive.shared::cta.b64 _, [%0], %1;" ::"r"(bar_full + (NS + slot) * 8), "n"(NCW / 2) : "memory");
                ring.skip(4);
                const float raw = (t & 1) ? (c[0][2] + c[1][2]) + c[2][2] : (c[0][0] + c[1][0]) + c[2][0];
                const float sv = bf_round(bf_round(raw) * 0.07216878364870323f);
                if (tid == 0 && j == NSTEP - 1) TS(14);
                float m = fmaxf(sv, shx(sv, 1));
#pragma unroll
                for (int o = 4; o < 32; o <<= 1) m = fmaxf(m, shx(m, o));
                if (lane == 0) lsum[8 + warp] = m;
                cons_bar();
#pragma unroll
                for (int i = 0; i < WW; i += 2) {
                    const float2 m2 = *reinterpret_cast<const float2*>(lsum + 8 + warp / WW * WW + i);
                    m = fmaxf(m, fmaxf(m2.x, m2.y));
                }
                float l = __expf(sv - m);
                *reinterpret_cast<bf16*>(smem + SM_PF + ((j & 3) * 4 + (warp >> 1)) * 64 + frag_off((warp & 1) * 16 + (t & 1) * 8 + g)) =
                    __float2bfloat16_rn(l);
                l += shx(l, 1);
#pragma unroll
                for (int o = 4; o < 32; o <<= 1) l += shx(l, o);
                if (lane == 0) lsum[warp] = l;
                cons_bar();
                if (tid % (WW * 32) < 4) {
                    l = 0.f;
#pragma unroll
                    for (int i = 0; i < WW; i += 2) {
                        const float2 l2 = *reinterpret_cast<const float2*>(lsum + warp + i);
                        l += l2.x + l2.y;
                    }
                    st_tag2(g_ml + (pair_of(sg, win) * G + r) * MLS + lane * 2, m, l, tag);
                    if (tid == 0) {
                        reinterpret_cast<volatile int*>(smem + SM_PACE)[2 + (j & 3)] = (int)clock();
                        mbar_arrive(bar_full + B_WTRIG + (j & 3) * 8);
                        if (j == HSTEP) mbar_arrive(bar_full + B_HTRIG);
                    }
                }
                if (tid == 0 && j == NSTEP - 1) TS(13);
                if (j < LA) continue;
            }
            const bool kv = j >= 0;
            const uint32_t jv = j - LA;
#pragma unroll
            for (int s = 0; s < 3; s++) off[s] = lane * 384 + s * 128 + ((warp ^ ((3 * lane + s) & 7)) << 4);
#pragma unroll 1
            for (int u = 0; u < (kv ? WPS : 1); u++) {
                const int pair = pair_of(sg, jv * WPS + u);
                uint32_t trig = !kv ? bar_full + B_QTRIG : (pair >> 2) == h ? bar_full + B_OTRIG + (pair & 3) * 8 : 0;
                if (tid != 0) trig = 0;
                float4* oacc = ocell(pair, warp * 8 + 2 * t + (g & 1));
                uint32_t wrdy = bar_full + B_WRDY + (jv & 3) * 8;
                asm volatile("" : "+l"(oacc), "+r"(trig), "+r"(wrdy));
                gemv_loop(ring, kv ? NT : 5,
                          kv ? sb + SM_PF + ((jv & 3) * 4 + u * NT) * 64 + t * 16 : sb + SM_XF + qd * 5 * 256 + a_lane,
                          kv ? 64 : 256, off, lo, hi, lane);
                if (kv) {
                    mbar_wait(wrdy, (jv >> 2) & 1);
                    const float w = lsum[16 + (jv & 3) * WPS + u];
                    if (g < 2)
                        asm volatile("red.relaxed.gpu.global.add.v4.f32 [%0], {%1,%2,%3,%4};"
                                     ::"l"(oacc), "f"(w * (g ? lo[0][1] + hi[0][3] : lo[0][0] + hi[0][2])),
                                       "f"(w * (g ? lo[1][1] + hi[1][3] : lo[1][0] + hi[1][2])),
                                       "f"(w * (g ? lo[2][1] + hi[2][3] : lo[2][0] + hi[2][2])), "f"(1.0f) : "memory");
                } else if (g < NB) {
#pragma unroll
                    for (int s = 0; s < 3; s++)
                        st_tag2(g_qpart + (cta * NB + g) * VS + warp * 32 + 2 * t + s * 8, lo[s][0] + hi[s][2], lo[s][1] + hi[s][3], tag);
                }
                if (trig) mbar_arrive(trig);
            }
            const bool pass = j == NSTEP + LA - 1;
            if (pass && tid == 0) TS(5);
            if (kv && !pass) continue;
            if (tid == 0 && j < 0) TS(4);

            {
                constexpr int I0 = 5 + NKV;
                static_assert(((I0 / NS) & 1) == 0 && I0 / NS == (I0 + 7) / NS, "tail items complete an even phase");
                const uint32_t done = bar_full + B_QTRIG;
                uint32_t fb = pass ? bar_full + (I0 % NS) * 8 : done, fs = pass ? 8 : 0, ordy = pass ? bar_full + B_ORDY : done;
                uint32_t off2[3], a[8][4], b[8][3][4], a_addr = sb + SM_HF + a_lane;
#pragma unroll
                for (int s = 0; s < 3; s++) {
                    const uint32_t w64 = lane * 320 + (warp + 8 * s) * 16;
                    off[s] = sb + SM_RING + (I0 % NS) * SLOT + (w64 ^ (((w64 >> 7) & 3) << 4));
                    off2[s] = lane < 24 ? off[s] : off[s] - 8 * 320;
#pragma unroll
                    for (int e = 0; e < 4; e++) { lo[s][e] = 0.f; hi[s][e] = 0.f; }
                }
                const float4* accp = g_acc + (((g & 3) * 4 + qd) * NCW + warp) * ACS + (g >> 2) * 4 + t;
                bf16* outp = out + (g & 3) * DM + qd * 160 + warp * 8 + 2 * t + (g >> 2);
                pin3(off);
                asm volatile("" : "+l"(accp), "+l"(outp), "+r"(a_addr), "+r"(ordy), "+r"(fb), "+r"(fs));
                auto load_b = [&](int i, bool& next) {
                    if (!next) mbar_wait(fb + i * fs, 0);
                    if (i < 7) next = mbar_test(fb + (i + 1) * fs, 0);
#pragma unroll
                    for (int s = 0; s < 3; s++)
                        if (s < 2 || warp < 4) ldsm_x4_t((i < 2 ? off2[s] : off[s]) + i * SLOT, b[i][s]);
                };
                auto mul = [&](int i) {
#pragma unroll
                    for (int s = 0; s < 3; s++)
                        if (s < 2 || warp < 4) { mma16816(lo[s], a[i], b[i][s][0], b[i][s][1]); mma16816(hi[s], a[i], b[i][s][2], b[i][s][3]); }
                };
                bool next = mbar_test(fb, 0);
                mbar_wait(pass ? bar_full + B_HRDY : done, 0);
                lds128(a_addr, a[0]);
                lds128(a_addr + 256, a[1]);
                load_b(0, next);
#pragma unroll
                for (int i = 0; i < 7; i++) {
                    load_b(i + 1, next);
                    if (i == 2) {
                        mbar_wait(ordy, 0);
                        if (pass && tid == 0) TS(7);
#pragma unroll
                        for (int k = 2; k < 8; k++) lds128(a_addr + k * 256, a[k]);
                    }
                    mul(i);
                }
                mul(7);
                if (pass && tid == 0) TS(8);
                add_out(accp, outp, lo, hi, g >= NB, warp < 4, pass, epoch);
            }
        }
        if (tid == 0) { TS(9); TS_DUMP(3, 32); }
    } else {
        float gate[6][2];
#pragma unroll
        for (int s = 0; s < 3; s++) {
            const uint32_t r128 = (lane & 15) * 6 + 2 * s + (lane >> 4);
            off[s] = r128 * 128 + ((warp ^ (r128 & 7)) << 4);
        }
#pragma unroll 1
        for (int ps = 0; ps < 2; ps++) {
#pragma unroll
            for (int s = 0; s < 3; s++) {
                gate[2 * s][0] = lo[s][0]; gate[2 * s][1] = lo[s][1];
                gate[2 * s + 1][0] = hi[s][0]; gate[2 * s + 1][1] = hi[s][1];
            }
            gemv_loop(ring, 40, sb + SM_XF + a_lane, 256, off, lo, hi, lane);
        }
#pragma unroll
        for (int p = 0; p < 6; p++) {
            float hv[2];
#pragma unroll
            for (int e = 0; e < 2; e++) {
                const float gt = bf_round(gate[p][e]);
                hv[e] = bf_round(bf_round(__fdividef(gt, 1.0f + __expf(-gt))) * bf_round((p & 1) ? hi[p >> 1][e] : lo[p >> 1][e]));
            }
            if (g < NB) st_tag2(g_h + g * FF + qd * 384 + p * 64 + warp * 8 + 2 * t, hv[0], hv[1], tag);
        }
        if (tid == 0) { TS(9); TS_DUMP(3, 10); }
    }
}

typedef CUresult (*EncodeFn)(CUtensorMap*, CUtensorMapDataType, cuuint32_t, void*, const cuuint64_t*, const cuuint64_t*,
                             const cuuint32_t*, const cuuint32_t*, CUtensorMapInterleave, CUtensorMapSwizzle,
                             CUtensorMapL2promotion, CUtensorMapFloatOOBfill);

void make_map(EncodeFn enc, CUtensorMap* m, const void* p, uint64_t rows, uint64_t cols, uint32_t inner, uint32_t parts,
              uint32_t box_rows) {
    const cuuint64_t dims[3] = {inner, cols / inner, rows};
    const cuuint64_t strides[2] = {inner * 2ull, cols * 2ull};
    const cuuint32_t box[3] = {inner, parts, box_rows};
    const cuuint32_t es[3] = {1, 1, 1};
    enc(m, CU_TENSOR_MAP_DATA_TYPE_BFLOAT16, 3, const_cast<void*>(p), dims, strides, box, es, CU_TENSOR_MAP_INTERLEAVE_NONE,
        inner == 64 ? CU_TENSOR_MAP_SWIZZLE_128B : CU_TENSOR_MAP_SWIZZLE_64B, CU_TENSOR_MAP_L2_PROMOTION_NONE,
        CU_TENSOR_MAP_FLOAT_OOB_FILL_NONE);
}

}

extern "C" void kernel_launch(void* const* d_in, const int* in_sizes, int n_in, void* d_out, int out_size) {
    (void)in_sizes; (void)n_in; (void)out_size;
    static EncodeFn enc = nullptr;
    if (!enc) {
        void* fn = nullptr;
        cudaDriverEntryPointQueryResult qr;
        cudaGetDriverEntryPoint("cuTensorMapEncodeTiled", &fn, cudaEnableDefault, &qr);
        enc = (EncodeFn)fn;
        cudaFuncSetAttribute(fused_decode_kernel, cudaFuncAttributeMaxDynamicSharedMemorySize, SM_TOTAL);
    }
    Maps maps;
    make_map(enc, &maps.k, d_in[1], (uint64_t)NB * NH * SK, DH, 64, 3, TK);
    make_map(enc, &maps.v, d_in[2], (uint64_t)NB * NH * SK, DH, 64, 3, TK);
    make_map(enc, &maps.wq, d_in[3], DM, NH * DH, 64, 3, 32);
    make_map(enc, &maps.wo, d_in[4], NH * DH, DM, 32, 5, 32);
    make_map(enc, &maps.w1, d_in[6], DM, FF, 64, 6, 16);
    make_map(enc, &maps.w3, d_in[7], DM, FF, 64, 6, 16);
    make_map(enc, &maps.w2, d_in[8], FF, DM, 32, 5, 24);
    fused_decode_kernel<<<NCTA, NTHR, SM_TOTAL>>>((const char*)d_in[3], (const bf16*)d_in[0], (bf16*)d_out,
                                                  (const char*)d_in[1], (const char*)d_in[2], maps);
}
```

```cpp
#include <cuda_runtime.h>
#include <cuda.h>
#include <cuda_bf16.h>
#include <stdint.h>

namespace {

typedef __nv_bfloat16 bf16;

constexpr int NB = 4, DM = 640, NH = 32, DH = 192, SK = 8192, WIN = 2048, FF = 1536;

constexpr int G = 32;
constexpr int TK = 32;
constexpr int NT = WIN / TK / G;
constexpr int NSTEP = 16;
constexpr int WPS = G / NSTEP;
constexpr int LA = 3;
constexpr int MLS = 8;
constexpr int OAL = 72;
constexpr int HSTEP = 11;
constexpr int NS = 16;
constexpr int SLOT = 12288;
constexpr int DEPTH = 4, DEPTH_MIN = 3, DEPTH_MAX = 6, DEPTH_FFN = 5;
constexpr int PACE_GAIN = 6, PACE_BIAS = 16, PACE_NS = 500;
constexpr int Q_SETTLE = 1600, ML_SETTLE = 4000, O_SETTLE = 3000;
constexpr int DEPTH0 = 5;
constexpr int PF_ROWS = 64;
static_assert(DEPTH0 <= 5, "DEPTH0");
constexpr int NATT = 128, NFFN = 4, NCTA = NATT + NFFN;
constexpr int NCW = 8;
constexpr int NXW = 2;
constexpr int W_PROD = NCW, W_PACE = NCW + 1 + NXW;
constexpr int NTHR = (W_PACE + 1) * 32;
constexpr int NSRC = NH;
constexpr int VS = 256;
constexpr int ACS = 72;
static_assert(G == 16 || G == 32 || G == 64, "G");

constexpr int SM_RING = 0;
constexpr int SM_XF = SM_RING + NS * SLOT;
constexpr int SM_QS = SM_XF + 20 * 256;
constexpr int SM_PF = SM_QS + G * DH * 2;
constexpr int SM_HF = SM_PF + 4 * 4 * 64;
constexpr int SM_OF = SM_HF + 2 * 256;
constexpr int SM_LS = SM_OF + 6 * 256;
constexpr int SM_ATT_END = SM_LS + 128;
constexpr int SM_FFN_END = SM_XF + 40 * 256;
constexpr int SM_BAR = SM_ATT_END > SM_FFN_END ? SM_ATT_END : SM_FFN_END;
constexpr int B_QRDY = 2 * NS * 8, B_ORDY = B_QRDY + NSTEP * 8, B_OTRIG = B_ORDY + 8, B_QTRIG = B_OTRIG + 32,
              B_WTRIG = B_QTRIG + 8, B_WRDY = B_WTRIG + 32, B_HTRIG = B_WRDY + 32, B_HRDY = B_HTRIG + 8,
              NBAR = 2 * NS + NSTEP + 16;
constexpr int SM_PACE = SM_BAR + NBAR * 8;
constexpr int SM_TOTAL = SM_PACE + 24;
static_assert(SM_TOTAL <= 232448, "smem");

constexpr int NKV = 2 * NT * G;
constexpr int ITEMS_ATT = 5 + NKV + 2 + 6;
constexpr int ITEMS_FFN = 80;

struct Maps { CUtensorMap k, v, wq, wo, w1, w3, w2; };

struct alignas(32) Sync { unsigned epoch, inits, prog[2]; };
__device__ Sync g_sync;
__device__ __align__(128) float g_qpart[NATT * NB * VS];
__device__ __align__(128) float g_ml[NATT * G * MLS];
__device__ __align__(128) float g_h[NB * FF];
__device__ __align__(128) float4 g_oacc[NATT * 8 * OAL];
__device__ __align__(128) float4 g_acc[NB * 4 * NCW * ACS];

constexpr unsigned SPIN_LIMIT = 1u << 22;

__device__ __forceinline__ void mbar_init(uint32_t bar, int cnt) {
    asm volatile("mbarrier.init.shared::cta.b64 [%0], %1;" ::"r"(bar), "r"(cnt) : "memory");
}
__device__ __forceinline__ void mbar_expect_tx(uint32_t bar, uint32_t bytes) {
    asm volatile("mbarrier.arrive.expect_tx.shared::cta.b64 _, [%0], %1;" ::"r"(bar), "r"(bytes) : "memory");
}
__device__ __forceinline__ void mbar_arrive(uint32_t bar) {
    asm volatile("mbarrier.arrive.shared::cta.b64 _, [%0];" ::"r"(bar) : "memory");
}
__device__ __forceinline__ void mbar_wait(uint32_t bar, uint32_t parity) {
    asm volatile("{\n.reg .pred p, q;\n.reg .u32 n;\nmov.u32 n, 0;\n"
                 "W: mbarrier.try_wait.parity.shared::cta.b64 p, [%0], %1;\n"
                 "@p bra D;\nadd.u32 n, n, 1;\nsetp.lt.u32 q, n, %2;\n@q bra W;\ntrap;\nD:\n}"
                 ::"r"(bar), "r"(parity), "n"(SPIN_LIMIT) : "memory");
}
__device__ __forceinline__ bool mbar_test(uint32_t bar, uint32_t parity) {
    uint32_t ok;
    asm volatile("{\n.reg .pred p;\nmbarrier.test_wait.parity.shared::cta.b64 p, [%1], %2;\nselp.u32 %0, 1, 0, p;\n}"
                 : "=r"(ok) : "r"(bar), "r"(parity) : "memory");
    return ok;
}
__device__ __forceinline__ void tma3d(uint32_t dst, const CUtensorMap* map, int c1, int c2, uint32_t bar) {
    const uint64_t pol = 0x12F0000000000000ull;
    asm volatile("cp.async.bulk.tensor.3d.shared::cluster.global.mbarrier::complete_tx::bytes.L2::cache_hint "
                 "[%0], [%1, {%2, %3, %4}], [%5], %6;"
                 ::"r"(dst), "l"(map), "r"(0), "r"(c1), "r"(c2), "r"(bar), "l"(pol) : "memory");
}
__device__ __forceinline__ void ldsm_x4(uint32_t addr, uint32_t (&r)[4]) {
    asm volatile("ldmatrix.sync.aligned.m8n8.x4.shared.b16 {%0,%1,%2,%3}, [%4];"
                 : "=r"(r[0]), "=r"(r[1]), "=r"(r[2]), "=r"(r[3]) : "r"(addr) : "memory");
}
__device__ __forceinline__ void ldsm_x4_t(uint32_t addr, uint32_t (&r)[4]) {
    asm volatile("ldmatrix.sync.aligned.m8n8.x4.trans.shared.b16 {%0,%1,%2,%3}, [%4];"
                 : "=r"(r[0]), "=r"(r[1]), "=r"(r[2]), "=r"(r[3]) : "r"(addr) : "memory");
}
__device__ __forceinline__ void lds128(uint32_t addr, uint32_t (&r)[4]) {
    asm volatile("ld.shared.v4.u32 {%0,%1,%2,%3}, [%4];"
                 : "=r"(r[0]), "=r"(r[1]), "=r"(r[2]), "=r"(r[3]) : "r"(addr) : "memory");
}
__device__ __forceinline__ void mma16816(float (&c)[4], const uint32_t (&a)[4], uint32_t b0, uint32_t b1) {
    asm volatile("mma.sync.aligned.m16n8k16.row.col.f32.bf16.bf16.f32 {%0,%1,%2,%3}, {%4,%5,%6,%7}, {%8,%9}, {%0,%1,%2,%3};"
                 : "+f"(c[0]), "+f"(c[1]), "+f"(c[2]), "+f"(c[3])
                 : "r"(a[0]), "r"(a[1]), "r"(a[2]), "r"(a[3]), "r"(b0), "r"(b1));
}
__device__ __forceinline__ void cons_bar() { asm volatile("bar.sync 1, 256;" ::: "memory"); }

__device__ __forceinline__ float bf_round(float v) { return __bfloat162float(__float2bfloat16_rn(v)); }
__device__ __forceinline__ uint32_t pack_bf2(float lo, float hi) {
    __nv_bfloat162 t = __floats2bfloat162_rn(lo, hi);
    return *reinterpret_cast<uint32_t*>(&t);
}
__device__ __forceinline__ float bf_lo(uint32_t u) { return __uint_as_float(u << 16); }
__device__ __forceinline__ float bf_hi(uint32_t u) { return __uint_as_float(u & 0xffff0000u); }
__device__ __forceinline__ float shx(float v, int o) { return __shfl_xor_sync(0xffffffffu, v, o); }

__device__ __forceinline__ uint32_t frag_off(uint32_t k) {
    return ((k >> 1) & 3) * 16 + ((k >> 3) & 1) * 8 + ((k >> 4) & 1) * 4 + (k & 1) * 2;
}

__device__ __forceinline__ void st_tag2(float* p, float a, float b, uint32_t tag) {
    asm volatile("{\n.reg .b64 w;\n.reg .b32 x;\nlop3.b32 x, %1, 0xfffffffe, %3, 0xea;\nmov.b64 w, {x, %2};\n"
                 "st.relaxed.gpu.global.b64 [%0], w;\n}"
                 ::"l"(p), "r"(__float_as_uint(a)), "r"(__float_as_uint(b)), "r"(tag) : "memory");
}
__device__ __forceinline__ void st_fill4(float* p, uint32_t v) {
    asm volatile("{\n.reg .b64 w;\nmov.b64 w, {%1, %1};\nst.relaxed.gpu.global.v2.b64 [%0], {w, w};\n}" ::"l"(p), "r"(v) : "memory");
}
__device__ __forceinline__ uint2 ld_word(const float* p) {
    uint2 v;
    asm volatile("{\n.reg .b64 w;\nld.relaxed.gpu.global.b64 w, [%2];\nmov.b64 {%0,%1}, w;\n}" : "=r"(v.x), "=r"(v.y) : "l"(p) : "memory");
    return v;
}
__device__ __forceinline__ uint4 ld_word2(const float* p) {
    uint4 v;
    asm volatile("{\n.reg .b64 w0, w1;\nld.relaxed.gpu.global.v2.b64 {w0, w1}, [%4];\nmov.b64 {%0,%1}, w0;\nmov.b64 {%2,%3}, w1;\n}"
                 : "=r"(v.x), "=r"(v.y), "=r"(v.z), "=r"(v.w) : "l"(p) : "memory");
    return v;
}

__device__ __forceinline__ void add_out(const float4* acc, bf16* out, const float (&lo)[3][4], const float (&hi)[3][4],
                                        bool odd, bool third, bool live, uint32_t epoch) {
    const float v0 = odd ? lo[0][1] + hi[0][3] : lo[0][0] + hi[0][2];
    const float v1 = odd ? lo[1][1] + hi[1][3] : lo[1][0] + hi[1][2];
    const float v2 = odd ? lo[2][1] + hi[2][3] : lo[2][0] + hi[2][2];
    float o0, o1, o2, n = 0.f;
    asm volatile("{\n.reg .pred p;\nsetp.ne.u32 p, %5, 0;\n"
                 "@p atom.relaxed.gpu.global.add.v4.f32 {%0,%1,%2,%3}, [%4], {%6,%7,%8,%9};\n}"
                 : "=f"(o0), "=f"(o1), "=f"(o2), "+f"(n)
                 : "l"(acc), "r"((uint32_t)live), "f"(v0), "f"(v1), "f"(v2), "f"(1.0f) : "memory");
    asm volatile("{\n.reg .pred p, q;\nsetp.eq.f32 p, %4, %5;\nsetp.ne.and.u32 q, %6, 0, p;\n"
                 "@p st.global.u16 [%0], %1;\n@p st.global.u16 [%0+128], %2;\n@q st.global.u16 [%0+256], %3;\n}"
                 ::"l"(out), "h"(__bfloat16_as_ushort(__float2bfloat16_rn(o0 + v0))),
                   "h"(__bfloat16_as_ushort(__float2bfloat16_rn(o1 + v1))), "h"(__bfloat16_as_ushort(__float2bfloat16_rn(o2 + v2))),
                   "f"(n), "f"((float)(NSRC - 1)), "r"((uint32_t)third) : "memory");
    if (acc == g_acc && n == (float)(NSRC - 1))
        asm volatile("st.relaxed.gpu.global.u32 [%0], %1;" ::"l"(&g_sync.epoch), "r"(epoch + 1u) : "memory");
}

__device__ __forceinline__ int pair_of(int sg, uint32_t j) { return sg * G + (j % (G / 4)) * 4 + j / (G / 4); }
__device__ __forceinline__ int order_of(int r, int b) { return b * (G / 4) + (r >> 2); }

__device__ __forceinline__ int window_row(int sg, uint32_t u, bool& isv) {
    const uint32_t blk = u / 4;
    isv = blk >= 2 * NSTEP - LA || (blk >= LA && ((blk - LA) & 1));
    const uint32_t step = blk < LA ? blk : blk >= 2 * NSTEP - LA ? blk - NSTEP : (blk - LA) / 2 + (isv ? 0 : LA);
    const int pair = pair_of(sg, step * WPS + (u % 4) / NT);
    return ((pair & 3) * NH + (pair >> 2)) * SK + (SK - WIN);
}

__device__ __forceinline__ float4* ocell(uint32_t pair, uint32_t i) {
    return g_oacc + (pair * 8 + (i >> 3)) * OAL + (i & 7);
}

__device__ __forceinline__ void settle(int cycles) {
    const uint32_t t0 = (uint32_t)clock();
    while ((uint32_t)clock() - t0 < (uint32_t)cycles) __nanosleep(20);
}

struct Ring {
    uint32_t full, addr, phase, first_full;
    __device__ __forceinline__ void wait() const { mbar_wait(full, phase); }
    __device__ __forceinline__ void skip(int n) {
        full += n * 8; addr += n * SLOT;
        if (full >= first_full + NS * 8) { full -= NS * 8; addr -= NS * SLOT; phase ^= 1; }
    }
    __device__ __forceinline__ void release(int lane) {
        __syncwarp();
        if (lane == 0) mbar_arrive(full + NS * 8);
        full += 8; addr += SLOT;
        if (full == first_full + NS * 8) { full = first_full; addr -= NS * SLOT; phase ^= 1; }
    }
};

__device__ __forceinline__ void pin3(uint32_t (&v)[3]) {
    asm volatile("" : "+r"(v[0]), "+r"(v[1]), "+r"(v[2]));
}
__device__ __forceinline__ void gemv_loop(Ring& ring, int n, uint32_t a_addr, uint32_t a_step, uint32_t (&off)[3],
                                          float (&lo)[3][4], float (&hi)[3][4], int lane) {
    pin3(off);
#pragma unroll
    for (int s = 0; s < 3; s++)
#pragma unroll
        for (int e = 0; e < 4; e++) { lo[s][e] = 0.f; hi[s][e] = 0.f; }
#pragma unroll 1
    for (int it = 0; it < n; it++) {
        uint32_t a[4], b[3][4];
        lds128(a_addr, a);
        a_addr += a_step;
        ring.wait();
#pragma unroll
        for (int s = 0; s < 3; s++) ldsm_x4_t(ring.addr + off[s], b[s]);
#pragma unroll
        for (int s = 0; s < 3; s++) { mma16816(lo[s], a, b[s][0], b[s][1]); mma16816(hi[s], a, b[s][2], b[s][3]); }
        ring.release(lane);
    }
}

__global__ void __launch_bounds__(NTHR, 1)
fused_decode_kernel(const char* __restrict__ wq, const bf16* __restrict__ x, bf16* __restrict__ out,
                    const char* __restrict__ kc, const char* __restrict__ vc, const __grid_constant__ Maps maps) {
    asm volatile("{\n.reg .pred p;\n.reg .b32 t, c, a, b;\n.reg .b64 o;\n"
                 "mov.u32 t, %%tid.x;\nmov.u32 c, %%ctaid.x;\n"
                 "and.b32 a, c, 3;\nshr.u32 c, c, 2;\nmul.lo.u32 a, a, 15360;\nmad.lo.u32 a, c, 3, a;\n"
                 "shr.u32 b, t, 2;\nmad.lo.u32 a, b, 92, a;\nadd.u32 a, a, t;\nmad.wide.u32 o, a, 128, %0;\n"
                 "and.b32 b, t, 3;\nsetp.ne.u32 p, b, 3;\nsetp.lt.and.u32 p, t, %1, p;\n@p prefetch.global.L2 [o];\n}"
                 ::"l"(wq), "n"(PF_ROWS * 4) : "memory");
    extern __shared__ __align__(1024) unsigned char smem[];
    const uint32_t sb = (uint32_t)__cvta_generic_to_shared(smem);
    const uint32_t bar_full = sb + SM_BAR;
    if (threadIdx.x == 0 && blockIdx.x < NATT) {
#pragma unroll 1
        for (int i = 0; i < DEPTH0; i++) {
            mbar_init(bar_full + i * 8, 1);
            mbar_expect_tx(bar_full + i * 8, 12288);
            tma3d(sb + SM_RING + i * SLOT, &maps.wq, (blockIdx.x >> 2) * 3, (blockIdx.x & 3) * 160 + i * 32, bar_full + i * 8);
        }
    }
    unsigned ptid, cta;
    asm volatile("mov.u32 %0, %%tid.x;\nmov.u32 %1, %%ctaid.x;" : "=r"(ptid), "=r"(cta));
    const int tid = ptid < 32 ? ptid + NCW * 32 : ptid < (NCW + 1) * 32 ? ptid - 32 : ptid;
    const int warp = tid >> 5, lane = tid & 31;
    const bool is_att = cta < NATT;
    const int h = cta >> 2, qd = cta & 3;
    const int sg = cta / G, r = cta % G;

    if (warp == NCW) {
        volatile int* pace = reinterpret_cast<volatile int*>(smem + SM_PACE);
        if (lane == 0) {
            pace[0] = 0;
            pace[1] = is_att ? DEPTH : DEPTH_FFN;
#pragma unroll
            for (int i = 0; i < NBAR; i++)
                if (i >= DEPTH0 || !is_att)
                    mbar_init(bar_full + i * 8, i < NS ? 1 : i < 2 * NS ? NCW : i < 2 * NS + NSTEP ? NXW :
                                                i == 2 * NS + NSTEP ? NXW * NB : i == NBAR - 1 ? NXW : 1);
            asm volatile("fence.mbarrier_init.release.cluster;" ::: "memory");
        }
        __syncwarp();
        asm volatile("bar.arrive 2, %0;" ::"n"(NTHR) : "memory");
        if (lane == 0) {
            const int n_items = is_att ? ITEMS_ATT : ITEMS_FFN;
            asm volatile("prefetch.tensormap [%0];" ::"l"(is_att ? &maps.k : &maps.w3) : "memory");
            asm volatile("prefetch.tensormap [%0];" ::"l"(&maps.v) : "memory");
            asm volatile("prefetch.tensormap [%0];" ::"l"(&maps.w2) : "memory");
            asm volatile("prefetch.tensormap [%0];" ::"l"(&maps.wo) : "memory");
#pragma unroll 1
            for (int i = is_att ? DEPTH0 : 0; i < n_items; i++) {
                const CUtensorMap* map;
                int c1, c2;
                uint32_t bytes = 12288;
                if (is_att) {
                    const uint32_t u = i - 5;
                    if (u < NKV) {
                        bool isv;
                        c2 = window_row(sg, u, isv) + ((u % NT) * G + r) * TK;
                        map = isv ? &maps.v : &maps.k;
                        c1 = 0;
                    } else if (i < 5) {
                        map = &maps.wq; c1 = h * 3; c2 = qd * 160 + i * 32;
                    } else if (u < NKV + 2) {
                        map = &maps.w2; c1 = qd * 5; c2 = h * 48 + (u - NKV) * 24; bytes = 7680;
                    } else {
                        map = &maps.wo; c1 = qd * 5; c2 = h * DH + (u - NKV - 2) * 32; bytes = 10240;
                    }
                } else {
                    map = i < 40 ? &maps.w1 : &maps.w3; c1 = qd * 6; c2 = (i < 40 ? i : i - 40) * 16;
                }
                const int depth = pace[1] + (is_att && i >= 5 + NKV + 5 ? 3 : 0);
                const uint32_t slot = (uint32_t)i % NS, landed = i - depth;
                if (i >= NS) mbar_wait(bar_full + (NS + slot) * 8, ((uint32_t)i / NS - 1) & 1);
                mbar_expect_tx(bar_full + slot * 8, bytes);
                uint32_t dst = sb + SM_RING + slot * SLOT, fb = bar_full + slot * 8;
                asm volatile("" : "+r"(dst), "+r"(fb), "+l"(map), "+r"(c1), "+r"(c2));
                if (i >= depth) mbar_wait(bar_full + (landed % NS) * 8, (landed / NS) & 1);
                tma3d(dst, map, c1, c2, fb);
                pace[0] = landed + 1;
                const uint32_t un = i - 5 + 3;
                if (is_att && un < NKV && un % NT == 0 && r == (un / NT) % G) {
                    bool isv;
                    const int row = window_row(sg, un, isv);
                    asm volatile("prefetch.global.L2 [%0];" ::"l"((isv ? vc : kc) + (size_t)row * (DH * 2)) : "memory");
                }
            }
            pace[0] = n_items - DEPTH;
        }
        return;
    }

    const int g = lane >> 2, t = lane & 3;
    uint32_t epoch;
    asm volatile("ld.relaxed.gpu.global.u32 %0, [%1];" : "=r"(epoch) : "l"(&g_sync.epoch) : "memory");

    if (warp == W_PACE) {
        const uint32_t tag = (epoch + 1u) & 1u;
        asm volatile("bar.sync 2, %0;" ::"n"(NTHR) : "memory");
        if (lane == 0) asm volatile("red.release.gpu.global.add.u32 [%0], 1;" ::"l"(&g_sync.inits) : "memory");
        if (!is_att) return;
        volatile int* pace = reinterpret_cast<volatile int*>(smem + SM_PACE);
        if (cta == 0 && lane == 0) asm volatile("st.relaxed.gpu.global.u32 [%0], %1;" ::"l"(&g_sync.prog[epoch & 1u]), "r"(0u) : "memory");
        int reported = 0, j = 0;
        bool due = false;
#pragma unroll 1
        for (unsigned it = 0;; it++) {
            const int landed = pace[0];
            if (j == NSTEP && landed >= ITEMS_ATT - DEPTH) {
                if (lane == 0)
                    asm volatile("red.relaxed.gpu.global.add.u32 [%0], %1;" ::"l"(&g_sync.prog[~epoch & 1u]), "r"(landed - reported) : "memory");
                return;
            }
            int sum = 0;
            constexpr int RPL = (G + 31) / 32;
            uint2 ml[WPS][RPL];
            uint32_t bad = 1u;
            unsigned n = (epoch + 1u) * NCTA;
            if (lane == 0)
                asm volatile("atom.relaxed.gpu.global.add.u32 %0, [%1], %2;"
                             : "=r"(sum) : "l"(&g_sync.prog[~epoch & 1u]), "r"(landed - reported) : "memory");
            if (due) {
#pragma unroll
                for (int u = 0; u < WPS; u++)
#pragma unroll
                    for (int k = 0; k < RPL; k++) ml[u][k] = ld_word(g_ml + (pair_of(sg, j * WPS + u) * G + k * 32 + lane % G) * MLS);
                if (j == 0) asm volatile("ld.acquire.gpu.global.u32 %0, [%1];" : "=r"(n) : "l"(&g_sync.inits) : "memory");
            }
            reported = landed;
            if (lane == 0) {
                const int lag16 = sum / (NATT / 16) - landed * 16 + PACE_BIAS;
                pace[1] = min(max(DEPTH + ((lag16 * PACE_GAIN + 128) >> 8), DEPTH_MIN), DEPTH_MAX);
            }
            if (due) {
                bad = 0;
#pragma unroll
                for (int u = 0; u < WPS; u++)
#pragma unroll
                    for (int k = 0; k < RPL; k++) bad |= ml[u][k].x ^ tag;
            }
            if (__all_sync(0xffffffffu, !(bad & 1u) && n == (epoch + 1u) * NCTA)) {
#pragma unroll
                for (int u = 0; u < WPS; u++) {
                    float M = -INFINITY, L = 0.f, w = 0.f;
#pragma unroll
                    for (int k = 0; k < RPL; k++) M = fmaxf(M, __uint_as_float(ml[u][k].x & ~1u));
#pragma unroll
                    for (int o = G / RPL / 2; o; o >>= 1) M = fmaxf(M, shx(M, o));
#pragma unroll
                    for (int k = 0; k < RPL; k++) {
                        const float wk = __expf(__uint_as_float(ml[u][k].x & ~1u) - M);
                        L += wk * __uint_as_float(ml[u][k].y);
                        if (k == r / 32) w = wk;
                    }
#pragma unroll
                    for (int o = G / RPL / 2; o; o >>= 1) L += shx(L, o);
                    if (lane == r % 32) reinterpret_cast<float*>(smem + SM_LS)[16 + (j & 3) * WPS + u] = __fdividef(w, L);
                }
                if (lane == r % 32) {
                    mbar_arrive(bar_full + B_WRDY + (j & 3) * 8);
                }
                j++;
                due = false;
            }
            __nanosleep(PACE_NS);
            if (!due && j < NSTEP && mbar_test(bar_full + B_WTRIG + (j & 3) * 8, (j >> 2) & 1))
                due = (uint32_t)clock() - (uint32_t)pace[2 + (j & 3)] >= ML_SETTLE;
            if (it > SPIN_LIMIT) __trap();
        }
    }
    if (warp > W_PROD) {
        const uint32_t tag = (epoch + 1u) & 1u;
        const int e = tid - (W_PROD + 1) * 32;
        if (is_att) {
            st_fill4(reinterpret_cast<float*>(ocell(cta, e)), 0u);
            if (e < 32) *reinterpret_cast<uint32_t*>(smem + SM_HF + e * 16 + 12) = 0u;
        } else {
#pragma unroll 1
            for (int c = e; c < 256; c += NXW * 32) {
                const bf16* xp = x + qd * DM + (c >> 6) * 160 + ((c >> 3) & 7) * 8 + (c & 3) * 2 + ((c >> 2) & 1);
                asm volatile("st.relaxed.gpu.global.v4.f32 [%0], {%1,%2,%3,%4};"
                             ::"l"(g_acc + (qd * 32 + (c >> 3)) * ACS + (c & 7)), "f"(__bfloat162float(xp[0])),
                               "f"(__bfloat162float(xp[64])), "f"((c & 32) ? 0.f : __bfloat162float(xp[128])), "f"(0.f) : "memory");
            }
        }
        asm volatile("bar.sync 2, %0;" ::"n"(NTHR) : "memory");
        if (!is_att) return;
        {
            const uint32_t eq = (e >> 5) * 24 + min(lane, 23), xw = eq / 6, xr = eq % 6;
            mbar_wait(bar_full + B_QTRIG, 0);
            settle(Q_SETTLE);
#pragma unroll 1
            for (int j = 0; j < NSTEP; j++) {
                uint4 v[WPS][4];
                uint32_t bad;
                unsigned spin = 0;
                do {
#pragma unroll
                    for (int u = 0; u < WPS; u++) {
                        const int pair = pair_of(sg, j * WPS + u);
                        const float* src = g_qpart + ((pair >> 2) * 4 * NB + (pair & 3)) * VS + xw * 32 + xr * 4;
#pragma unroll
                        for (int k = 0; k < 4; k++) v[u][k] = ld_word2(src + k * NB * VS);
                    }
                    bad = 0;
#pragma unroll
                    for (int u = 0; u < WPS; u++)
#pragma unroll
                        for (int k = 0; k < 4; k++) bad |= (v[u][k].x ^ tag) | (v[u][k].z ^ tag);
                    if (++spin > SPIN_LIMIT) __trap();
                } while (bad & 1u);
#define SUM4(c) ((__uint_as_float(v[u][0].c) + __uint_as_float(v[u][1].c)) + (__uint_as_float(v[u][2].c) + __uint_as_float(v[u][3].c)))
#pragma unroll
                for (int u = 0; u < WPS; u++) {
                    unsigned char* dst = smem + SM_QS + (j * WPS + u) * (DH * 2) + (xr & 1) * 192 + ((xr >> 1) * 8 + xw) * 4;
                    *reinterpret_cast<uint32_t*>(dst) = pack_bf2(SUM4(x), SUM4(y));
                    *reinterpret_cast<uint32_t*>(dst + 96) = pack_bf2(SUM4(z), SUM4(w));
                }
#undef SUM4
                __syncwarp();
                if (lane == 0) mbar_arrive(bar_full + B_QRDY + j * 8);
            }
        }
        bool have_h = false;
#pragma unroll 1
        for (int b = 0; b <= NB; b++) {
            if (!have_h && (b == NB || order_of(r, b) >= HSTEP * WPS)) {
                have_h = true;
                mbar_wait(bar_full + B_HTRIG, 0);
#pragma unroll 1
                for (int i = e; i < 96; i += NXW * 32) {
                    const int k = (i % 24) * 2;
                    uint2 v;
                    unsigned spin = 0;
                    do {
                        v = ld_word(g_h + i / 24 * FF + h * 48 + k);
                        if (++spin > SPIN_LIMIT) __trap();
                    } while ((v.x ^ tag) & 1u);
                    *reinterpret_cast<uint32_t*>(smem + SM_HF + k / 24 * 256 + i / 24 * 64 + frag_off(k % 24)) = __byte_perm(v.x, v.y, 0x7632);
                }
                __syncwarp();
                if (lane == 0) mbar_arrive(bar_full + B_HRDY);
            }
            if (b == NB) break;
            const float4* src = ocell(h * NB + b, e);
            uint32_t dst = sb + SM_OF + (e >> 5) * 256 + b * 64 + frag_off(lane), ordy = bar_full + B_ORDY;
            asm volatile("" : "+r"(dst), "+l"(src), "+r"(ordy));
            mbar_wait(bar_full + B_OTRIG + b * 8, 0);
            const int pause = order_of(r, b) < G - WPS ? O_SETTLE : 0;
            unsigned spin = 0;
            float o0, o1, o2, n;
            do {
                settle(pause);
                asm volatile("{\n.reg .b128 w;\n.reg .b64 w0, w1;\nld.relaxed.gpu.global.b128 w, [%4];\nmov.b128 {w0, w1}, w;\n"
                             "mov.b64 {%0,%1}, w0;\nmov.b64 {%2,%3}, w1;\n}"
                             : "=f"(o0), "=f"(o1), "=f"(o2), "=f"(n) : "l"(src) : "memory");
                asm volatile("st.shared.u16 [%0], %1;\nst.shared.u16 [%0+512], %2;\nst.shared.u16 [%0+1024], %3;"
                             ::"r"(dst), "h"(__bfloat16_as_ushort(__float2bfloat16_rn(o0))),
                               "h"(__bfloat16_as_ushort(__float2bfloat16_rn(o1))), "h"(__bfloat16_as_ushort(__float2bfloat16_rn(o2))) : "memory");
                if (++spin > SPIN_LIMIT) __trap();
            } while (n != (float)G);
            __syncwarp();
            if (lane == 0) mbar_arrive(ordy);
        }
        return;
    }

    if (warp < NB) {
        uint2 raw[5];
#pragma unroll
        for (int i = 0; i < 5; i++) raw[i] = __ldg(reinterpret_cast<const uint2*>(x + warp * DM) + i * 32 + lane);
        float s = 0.f;
#pragma unroll
        for (int i = 0; i < 5; i++) s += (bf_lo(raw[i].x) + bf_hi(raw[i].x)) + (bf_lo(raw[i].y) + bf_hi(raw[i].y));
#pragma unroll
        for (int o = 16; o; o >>= 1) s += shx(s, o);
        const float mean = s * (1.0f / DM);
        float q2 = 0.f;
#pragma unroll
        for (int i = 0; i < 5; i++) {
            const float d0 = bf_lo(raw[i].x) - mean, d1 = bf_hi(raw[i].x) - mean;
            const float d2 = bf_lo(raw[i].y) - mean, d3 = bf_hi(raw[i].y) - mean;
            q2 += (d0 * d0 + d1 * d1) + (d2 * d2 + d3 * d3);
        }
#pragma unroll
        for (int o = 16; o; o >>= 1) q2 += shx(q2, o);
        const float mb = bf_round(mean);
        const float rs = __frcp_rn(bf_round(__fsqrt_rn(bf_round(bf_round(q2 * (1.0f / DM)) + 1e-5f))));
        const uint32_t k = (lane * 4) & 31;
        unsigned char* dst = smem + SM_XF + warp * 64 +
            (is_att ? (lane >> 3) * 256 + frag_off(k) : (lane >> 2) * 256 + frag_off(k & 15));
        const uint32_t step = is_att ? 1024 : 2048;
#pragma unroll
        for (int i = 0; i < 5; i++) {
            const uint32_t d0 = pack_bf2(bf_lo(raw[i].x) - mb, bf_hi(raw[i].x) - mb);
            const uint32_t d1 = pack_bf2(bf_lo(raw[i].y) - mb, bf_hi(raw[i].y) - mb);
            *reinterpret_cast<uint32_t*>(dst + i * step) = pack_bf2(bf_lo(d0) * rs, bf_hi(d0) * rs);
            *reinterpret_cast<uint32_t*>(dst + i * step + 16) = pack_bf2(bf_lo(d1) * rs, bf_hi(d1) * rs);
        }
    }
    asm volatile("bar.sync 2, %0;" ::"n"(NTHR) : "memory");
    uint32_t tag = (epoch + 1u) & 1u;
    asm volatile("" : "+r"(tag));

    Ring ring{bar_full, sb + SM_RING, 0u, bar_full};
    float lo[3][4] = {}, hi[3][4] = {};
    uint32_t off[3];
    const uint32_t a_lane = (g & 3) * 64 + t * 16;

    if (is_att) {
        float* lsum = reinterpret_cast<float*>(smem + SM_LS);
#pragma unroll 1
        for (int j = -1; j < NSTEP + LA; j++) {
            if (j >= 0 && j < NSTEP) {
                constexpr int WW = NCW / WPS;
                const int win = j * WPS + warp / WW;
                uint32_t qf[6][4];
                mbar_wait(bar_full + B_QRDY + j * 8, 0);
#pragma unroll
                for (int i = 0; i < 6; i++) lds128(sb + SM_QS + win * (DH * 2) + t * 96 + i * 16, qf[i]);
                const uint32_t key = (warp & 1) * 16 + (lane & 15);
                const uint32_t item = 5 + (j + max(j - LA, 0)) * 4 + (warp >> 1), slot = item % NS;
#pragma unroll
                for (int s = 0; s < 3; s++)
                    off[s] = sb + SM_RING + slot * SLOT + key * 384 + s * 128 + (((lane >> 4) ^ ((3 * key + s) & 7)) << 4);
                pin3(off);
                mbar_wait(bar_full + slot * 8, (item / NS) & 1);
                float c[3][4] = {};
#pragma unroll
                for (int dq = 0; dq < 4; dq++)
#pragma unroll
                    for (int s = 0; s < 3; s++) {
                        uint32_t a[4];
                        ldsm_x4(off[s] ^ (dq << 5), a);
                        mma16816(c[s], a, qf[s * 2 + (dq >> 1)][(dq & 1) * 2], qf[s * 2 + (dq >> 1)][(dq & 1) * 2 + 1]);
                    }
                __syncwarp();
                if (lane == 0)
                    asm volatile("mbarrier.arrive.shared::cta.b64 _, [%0], %1;" ::"r"(bar_full + (NS + slot) * 8), "n"(NCW / 2) : "memory");
                ring.skip(4);
                const float raw = (t & 1) ? (c[0][2] + c[1][2]) + c[2][2] : (c[0][0] + c[1][0]) + c[2][0];
                const float sv = bf_round(bf_round(raw) * 0.07216878364870323f);
                float m = fmaxf(sv, shx(sv, 1));
#pragma unroll
                for (int o = 4; o < 32; o <<= 1) m = fmaxf(m, shx(m, o));
                if (lane == 0) lsum[8 + warp] = m;
                cons_bar();
#pragma unroll
                for (int i = 0; i < WW; i += 2) {
                    const float2 m2 = *reinterpret_cast<const float2*>(lsum + 8 + warp / WW * WW + i);
                    m = fmaxf(m, fmaxf(m2.x, m2.y));
                }
                float l = __expf(sv - m);
                *reinterpret_cast<bf16*>(smem + SM_PF + ((j & 3) * 4 + (warp >> 1)) * 64 + frag_off((warp & 1) * 16 + (t & 1) * 8 + g)) =
                    __float2bfloat16_rn(l);
                l += shx(l, 1);
#pragma unroll
                for (int o = 4; o < 32; o <<= 1) l += shx(l, o);
                if (lane == 0) lsum[warp] = l;
                cons_bar();
                if (tid % (WW * 32) < 4) {
                    l = 0.f;
#pragma unroll
                    for (int i = 0; i < WW; i += 2) {
                        const float2 l2 = *reinterpret_cast<const float2*>(lsum + warp + i);
                        l += l2.x + l2.y;
                    }
                    st_tag2(g_ml + (pair_of(sg, win) * G + r) * MLS + lane * 2, m, l, tag);
                    if (tid == 0) {
                        reinterpret_cast<volatile int*>(smem + SM_PACE)[2 + (j & 3)] = (int)clock();
                        mbar_arrive(bar_full + B_WTRIG + (j & 3) * 8);
                        if (j == HSTEP) mbar_arrive(bar_full + B_HTRIG);
                    }
                }
                if (j < LA) continue;
            }
            const bool kv = j >= 0;
            const uint32_t jv = j - LA;
#pragma unroll
            for (int s = 0; s < 3; s++) off[s] = lane * 384 + s * 128 + ((warp ^ ((3 * lane + s) & 7)) << 4);
#pragma unroll 1
            for (int u = 0; u < (kv ? WPS : 1); u++) {
                const int pair = pair_of(sg, jv * WPS + u);
                uint32_t trig = !kv ? bar_full + B_QTRIG : (pair >> 2) == h ? bar_full + B_OTRIG + (pair & 3) * 8 : 0;
                if (tid != 0) trig = 0;
                float4* oacc = ocell(pair, warp * 8 + 2 * t + (g & 1));
                uint32_t wrdy = bar_full + B_WRDY + (jv & 3) * 8;
                asm volatile("" : "+l"(oacc), "+r"(trig), "+r"(wrdy));
                gemv_loop(ring, kv ? NT : 5,
                          kv ? sb + SM_PF + ((jv & 3) * 4 + u * NT) * 64 + t * 16 : sb + SM_XF + qd * 5 * 256 + a_lane,
                          kv ? 64 : 256, off, lo, hi, lane);
                if (kv) {
                    mbar_wait(wrdy, (jv >> 2) & 1);
                    const float w = lsum[16 + (jv & 3) * WPS + u];
                    if (g < 2)
                        asm volatile("red.relaxed.gpu.global.add.v4.f32 [%0], {%1,%2,%3,%4};"
                                     ::"l"(oacc), "f"(w * (g ? lo[0][1] + hi[0][3] : lo[0][0] + hi[0][2])),
                                       "f"(w * (g ? lo[1][1] + hi[1][3] : lo[1][0] + hi[1][2])),
                                       "f"(w * (g ? lo[2][1] + hi[2][3] : lo[2][0] + hi[2][2])), "f"(1.0f) : "memory");
                } else if (g < NB) {
#pragma unroll
                    for (int s = 0; s < 3; s++)
                        st_tag2(g_qpart + (cta * NB + g) * VS + warp * 32 + 2 * t + s * 8, lo[s][0] + hi[s][2], lo[s][1] + hi[s][3], tag);
                }
                if (trig) mbar_arrive(trig);
            }
            const bool pass = j == NSTEP + LA - 1;
            if (kv && !pass) continue;

            {
                constexpr int I0 = 5 + NKV;
                static_assert(((I0 / NS) & 1) == 0 && I0 / NS == (I0 + 7) / NS, "tail items complete an even phase");
                const uint32_t done = bar_full + B_QTRIG;
                uint32_t fb = pass ? bar_full + (I0 % NS) * 8 : done, fs = pass ? 8 : 0, ordy = pass ? bar_full + B_ORDY : done;
                uint32_t off2[3], a[8][4], b[8][3][4], a_addr = sb + SM_HF + a_lane;
#pragma unroll
                for (int s = 0; s < 3; s++) {
                    const uint32_t w64 = lane * 320 + (warp + 8 * s) * 16;
                    off[s] = sb + SM_RING + (I0 % NS) * SLOT + (w64 ^ (((w64 >> 7) & 3) << 4));
                    off2[s] = lane < 24 ? off[s] : off[s] - 8 * 320;
#pragma unroll
                    for (int e = 0; e < 4; e++) { lo[s][e] = 0.f; hi[s][e] = 0.f; }
                }
                const float4* accp = g_acc + (((g & 3) * 4 + qd) * NCW + warp) * ACS + (g >> 2) * 4 + t;
                bf16* outp = out + (g & 3) * DM + qd * 160 + warp * 8 + 2 * t + (g >> 2);
                pin3(off);
                asm volatile("" : "+l"(accp), "+l"(outp), "+r"(a_addr), "+r"(ordy), "+r"(fb), "+r"(fs));
                auto load_b = [&](int i, bool& next) {
                    if (!next) mbar_wait(fb + i * fs, 0);
                    if (i < 7) next = mbar_test(fb + (i + 1) * fs, 0);
#pragma unroll
                    for (int s = 0; s < 3; s++)
                        if (s < 2 || warp < 4) ldsm_x4_t((i < 2 ? off2[s] : off[s]) + i * SLOT, b[i][s]);
                };
                auto mul = [&](int i) {
#pragma unroll
                    for (int s = 0; s < 3; s++)
                        if (s < 2 || warp < 4) { mma16816(lo[s], a[i], b[i][s][0], b[i][s][1]); mma16816(hi[s], a[i], b[i][s][2], b[i][s][3]); }
                };
                bool next = mbar_test(fb, 0);
                mbar_wait(pass ? bar_full + B_HRDY : done, 0);
                lds128(a_addr, a[0]);
                lds128(a_addr + 256, a[1]);
                load_b(0, next);
#pragma unroll
                for (int i = 0; i < 7; i++) {
                    load_b(i + 1, next);
                    if (i == 2) {
                        mbar_wait(ordy, 0);
#pragma unroll
                        for (int k = 2; k < 8; k++) lds128(a_addr + k * 256, a[k]);
                    }
                    mul(i);
                }
                mul(7);
                add_out(accp, outp, lo, hi, g >= NB, warp < 4, pass, epoch);
            }
        }
    } else {
        float gate[6][2];
#pragma unroll
        for (int s = 0; s < 3; s++) {
            const uint32_t r128 = (lane & 15) * 6 + 2 * s + (lane >> 4);
            off[s] = r128 * 128 + ((warp ^ (r128 & 7)) << 4);
        }
#pragma unroll 1
        for (int ps = 0; ps < 2; ps++) {
#pragma unroll
            for (int s = 0; s < 3; s++) {
                gate[2 * s][0] = lo[s][0]; gate[2 * s][1] = lo[s][1];
                gate[2 * s + 1][0] = hi[s][0]; gate[2 * s + 1][1] = hi[s][1];
            }
            gemv_loop(ring, 40, sb + SM_XF + a_lane, 256, off, lo, hi, lane);
        }
#pragma unroll
        for (int p = 0; p < 6; p++) {
            float hv[2];
#pragma unroll
            for (int e = 0; e < 2; e++) {
                const float gt = bf_round(gate[p][e]);
                hv[e] = bf_round(bf_round(__fdividef(gt, 1.0f + __expf(-gt))) * bf_round((p & 1) ? hi[p >> 1][e] : lo[p >> 1][e]));
            }
            if (g < NB) st_tag2(g_h + g * FF + qd * 384 + p * 64 + warp * 8 + 2 * t, hv[0], hv[1], tag);
        }
    }
}

typedef CUresult (*EncodeFn)(CUtensorMap*, CUtensorMapDataType, cuuint32_t, void*, const cuuint64_t*, const cuuint64_t*,
                             const cuuint32_t*, const cuuint32_t*, CUtensorMapInterleave, CUtensorMapSwizzle,
                             CUtensorMapL2promotion, CUtensorMapFloatOOBfill);

void make_map(EncodeFn enc, CUtensorMap* m, const void* p, uint64_t rows, uint64_t cols, uint32_t inner, uint32_t parts,
              uint32_t box_rows) {
    const cuuint64_t dims[3] = {inner, cols / inner, rows};
    const cuuint64_t strides[2] = {inner * 2ull, cols * 2ull};
    const cuuint32_t box[3] = {inner, parts, box_rows};
    const cuuint32_t es[3] = {1, 1, 1};
    enc(m, CU_TENSOR_MAP_DATA_TYPE_BFLOAT16, 3, const_cast<void*>(p), dims, strides, box, es, CU_TENSOR_MAP_INTERLEAVE_NONE,
        inner == 64 ? CU_TENSOR_MAP_SWIZZLE_128B : CU_TENSOR_MAP_SWIZZLE_64B, CU_TENSOR_MAP_L2_PROMOTION_NONE,
        CU_TENSOR_MAP_FLOAT_OOB_FILL_NONE);
}

}

extern "C" void kernel_launch(void* const* d_in, const int* in_sizes, int n_in, void* d_out, int out_size) {
    (void)in_sizes; (void)n_in; (void)out_size;
    static EncodeFn enc = nullptr;
    if (!enc) {
        void* fn = nullptr;
        cudaDriverEntryPointQueryResult qr;
        cudaGetDriverEntryPoint("cuTensorMapEncodeTiled", &fn, cudaEnableDefault, &qr);
        enc = (EncodeFn)fn;
        cudaFuncSetAttribute(fused_decode_kernel, cudaFuncAttributeMaxDynamicSharedMemorySize, SM_TOTAL);
    }
    Maps maps;
    make_map(enc, &maps.k, d_in[1], (uint64_t)NB * NH * SK, DH, 64, 3, TK);
    make_map(enc, &maps.v, d_in[2], (uint64_t)NB * NH * SK, DH, 64, 3, TK);
    make_map(enc, &maps.wq, d_in[3], DM, NH * DH, 64, 3, 32);
    make_map(enc, &maps.wo, d_in[4], NH * DH, DM, 32, 5, 32);
    make_map(enc, &maps.w1, d_in[6], DM, FF, 64, 6, 16);
    make_map(enc, &maps.w3, d_in[7], DM, FF, 64, 6, 16);
    make_map(enc, &maps.w2, d_in[8], FF, DM, 32, 5, 24);
    fused_decode_kernel<<<NCTA, NTHR, SM_TOTAL>>>((const char*)d_in[3], (const bf16*)d_in[0], (bf16*)d_out,
                                                  (const char*)d_in[1], (const char*)d_in[2], maps);
}
```

```cpp
#include <cuda_runtime.h>
#include <cuda.h>
#include <cuda_bf16.h>
#include <stdint.h>

namespace {

typedef __nv_bfloat16 bf16;

constexpr int NB = 4, DM = 640, NH = 32, DH = 192, SK = 8192, WIN = 2048, FF = 1536;

constexpr int G = 32;
constexpr int TK = 32;
constexpr int NT = WIN / TK / G;
constexpr int NSTEP = 16;
constexpr int WPS = G / NSTEP;
constexpr int LA = 3;
constexpr int MLS = 8;
constexpr int OAL = 72;
constexpr int HSTEP = 11;
constexpr int NS = 16;
constexpr int SLOT = 12288;
constexpr int DEPTH = 4, DEPTH_MIN = 3, DEPTH_MAX = 6, DEPTH_FFN = 5;
constexpr int PACE_GAIN = 6, PACE_BIAS = 16, PACE_NS = 500;
constexpr int Q_SETTLE = 1600, ML_SETTLE = 4000, O_SETTLE = 3000;
constexpr int DEPTH0 = 5;
constexpr int PF_ROWS = 64;
static_assert(DEPTH0 <= 5, "DEPTH0");
constexpr int NATT = 128, NFFN = 4, NCTA = NATT + NFFN;
constexpr int NCW = 8;
constexpr int NXW = 2;
constexpr int W_PROD = NCW, W_PACE = NCW + 1 + NXW;
constexpr int NTHR = (W_PACE + 1) * 32;
constexpr int NSRC = NH;
constexpr int VS = 256;
constexpr int ACS = 72;
static_assert(G == 16 || G == 32 || G == 64, "G");

constexpr int SM_RING = 0;
constexpr int SM_XF = SM_RING + NS * SLOT;
constexpr int SM_QS = SM_XF + 20 * 256;
constexpr int SM_PF = SM_QS + G * DH * 2;
constexpr int SM_HF = SM_PF + 4 * 4 * 64;
constexpr int SM_OF = SM_HF + 2 * 256;
constexpr int SM_LS = SM_OF + 6 * 256;
constexpr int SM_ATT_END = SM_LS + 128;
constexpr int SM_FFN_END = SM_XF + 40 * 256;
constexpr int SM_BAR = SM_ATT_END > SM_FFN_END ? SM_ATT_END : SM_FFN_END;
constexpr int B_QRDY = 2 * NS * 8, B_ORDY = B_QRDY + NSTEP * 8, B_OTRIG = B_ORDY + 8, B_QTRIG = B_OTRIG + 32,
              B_WTRIG = B_QTRIG + 8, B_WRDY = B_WTRIG + 32, B_HTRIG = B_WRDY + 32, B_HRDY = B_HTRIG + 8,
              NBAR = 2 * NS + NSTEP + 16;
constexpr int SM_PACE = SM_BAR + NBAR * 8;
constexpr int SM_TOTAL = SM_PACE + 24;
static_assert(SM_TOTAL <= 232448, "smem");

constexpr int NKV = 2 * NT * G;
constexpr int ITEMS_ATT = 5 + NKV + 2 + 6;
constexpr int ITEMS_FFN = 80;

struct Maps { CUtensorMap k, v, wq, wo, w1, w3, w2; };

struct alignas(32) Sync { unsigned epoch, inits, prog[2]; };
__device__ Sync g_sync;
__device__ __align__(128) float g_qpart[NATT * NB * VS];
__device__ __align__(128) float g_ml[NATT * G * MLS];
__device__ __align__(128) float g_h[NB * FF];
__device__ __align__(128) float4 g_oacc[NATT * 8 * OAL];
__device__ __align__(128) float4 g_acc[NB * 4 * NCW * ACS];

constexpr unsigned SPIN_LIMIT = 1u << 22;

__device__ __forceinline__ void mbar_init(uint32_t bar, int cnt) {
    asm volatile("mbarrier.init.shared::cta.b64 [%0], %1;" ::"r"(bar), "r"(cnt) : "memory");
}
__device__ __forceinline__ void mbar_expect_tx(uint32_t bar, uint32_t bytes) {
    asm volatile("mbarrier.arrive.expect_tx.shared::cta.b64 _, [%0], %1;" ::"r"(bar), "r"(bytes) : "memory");
}
__device__ __forceinline__ void mbar_arrive(uint32_t bar) {
    asm volatile("mbarrier.arrive.shared::cta.b64 _, [%0];" ::"r"(bar) : "memory");
}
__device__ __forceinline__ void mbar_wait(uint32_t bar, uint32_t parity) {
    asm volatile("{\n.reg .pred p, q;\n.reg .u32 n;\nmov.u32 n, 0;\n"
                 "W: mbarrier.try_wait.parity.shared::cta.b64 p, [%0], %1;\n"
                 "@p bra D;\nadd.u32 n, n, 1;\nsetp.lt.u32 q, n, %2;\n@q bra W;\ntrap;\nD:\n}"
                 ::"r"(bar), "r"(parity), "n"(SPIN_LIMIT) : "memory");
}
__device__ __forceinline__ bool mbar_test(uint32_t bar, uint32_t parity) {
    uint32_t ok;
    asm volatile("{\n.reg .pred p;\nmbarrier.test_wait.parity.shared::cta.b64 p, [%1], %2;\nselp.u32 %0, 1, 0, p;\n}"
                 : "=r"(ok) : "r"(bar), "r"(parity) : "memory");
    return ok;
}
__device__ __forceinline__ void tma3d(uint32_t dst, const CUtensorMap* map, int c1, int c2, uint32_t bar) {
    const uint64_t pol = 0x12F0000000000000ull;
    asm volatile("cp.async.bulk.tensor.3d.shared::cluster.global.mbarrier::complete_tx::bytes.L2::cache_hint "
                 "[%0], [%1, {%2, %3, %4}], [%5], %6;"
                 ::"r"(dst), "l"(map), "r"(0), "r"(c1), "r"(c2), "r"(bar), "l"(pol) : "memory");
}
__device__ __forceinline__ void ldsm_x4(uint32_t addr, uint32_t (&r)[4]) {
    asm volatile("ldmatrix.sync.aligned.m8n8.x4.shared.b16 {%0,%1,%2,%3}, [%4];"
                 : "=r"(r[0]), "=r"(r[1]), "=r"(r[2]), "=r"(r[3]) : "r"(addr) : "memory");
}
__device__ __forceinline__ void ldsm_x4_t(uint32_t addr, uint32_t (&r)[4]) {
    asm volatile("ldmatrix.sync.aligned.m8n8.x4.trans.shared.b16 {%0,%1,%2,%3}, [%4];"
                 : "=r"(r[0]), "=r"(r[1]), "=r"(r[2]), "=r"(r[3]) : "r"(addr) : "memory");
}
__device__ __forceinline__ void lds128(uint32_t addr, uint32_t (&r)[4]) {
    asm volatile("ld.shared.v4.u32 {%0,%1,%2,%3}, [%4];"
                 : "=r"(r[0]), "=r"(r[1]), "=r"(r[2]), "=r"(r[3]) : "r"(addr) : "memory");
}
__device__ __forceinline__ void mma16816(float (&c)[4], const uint32_t (&a)[4], uint32_t b0, uint32_t b1) {
    asm volatile("mma.sync.aligned.m16n8k16.row.col.f32.bf16.bf16.f32 {%0,%1,%2,%3}, {%4,%5,%6,%7}, {%8,%9}, {%0,%1,%2,%3};"
                 : "+f"(c[0]), "+f"(c[1]), "+f"(c[2]), "+f"(c[3])
                 : "r"(a[0]), "r"(a[1]), "r"(a[2]), "r"(a[3]), "r"(b0), "r"(b1));
}
__device__ __forceinline__ void cons_bar() { asm volatile("bar.sync 1, 256;" ::: "memory"); }

__device__ __forceinline__ float bf_round(float v) { return __bfloat162float(__float2bfloat16_rn(v)); }
__device__ __forceinline__ uint32_t pack_bf2(float lo, float hi) {
    __nv_bfloat162 t = __floats2bfloat162_rn(lo, hi);
    return *reinterpret_cast<uint32_t*>(&t);
}
__device__ __forceinline__ float bf_lo(uint32_t u) { return __uint_as_float(u << 16); }
__device__ __forceinline__ float bf_hi(uint32_t u) { return __uint_as_float(u & 0xffff0000u); }
__device__ __forceinline__ float shx(float v, int o) { return __shfl_xor_sync(0xffffffffu, v, o); }

__device__ __forceinline__ uint32_t frag_off(uint32_t k) {
    return ((k >> 1) & 3) * 16 + ((k >> 3) & 1) * 8 + ((k >> 4) & 1) * 4 + (k & 1) * 2;
}

__device__ __forceinline__ void st_tag2(float* p, float a, float b, uint32_t tag) {
    asm volatile("{\n.reg .b64 w;\n.reg .b32 x;\nlop3.b32 x, %1, 0xfffffffe, %3, 0xea;\nmov.b64 w, {x, %2};\n"
                 "st.relaxed.gpu.global.b64 [%0], w;\n}"
                 ::"l"(p), "r"(__float_as_uint(a)), "r"(__float_as_uint(b)), "r"(tag) : "memory");
}
__device__ __forceinline__ void st_fill4(float* p, uint32_t v) {
    asm volatile("{\n.reg .b64 w;\nmov.b64 w, {%1, %1};\nst.relaxed.gpu.global.v2.b64 [%0], {w, w};\n}" ::"l"(p), "r"(v) : "memory");
}
__device__ __forceinline__ uint2 ld_word(const float* p) {
    uint2 v;
    asm volatile("{\n.reg .b64 w;\nld.relaxed.gpu.global.b64 w, [%2];\nmov.b64 {%0,%1}, w;\n}" : "=r"(v.x), "=r"(v.y) : "l"(p) : "memory");
    return v;
}
__device__ __forceinline__ uint4 ld_word2(const float* p) {
    uint4 v;
    asm volatile("{\n.reg .b64 w0, w1;\nld.relaxed.gpu.global.v2.b64 {w0, w1}, [%4];\nmov.b64 {%0,%1}, w0;\nmov.b64 {%2,%3}, w1;\n}"
                 : "=r"(v.x), "=r"(v.y), "=r"(v.z), "=r"(v.w) : "l"(p) : "memory");
    return v;
}

__device__ __forceinline__ void add_out(const float4* acc, bf16* out, const float (&lo)[3][4], const float (&hi)[3][4],
                                        bool odd, bool third, bool live, uint32_t epoch) {
    const float v0 = odd ? lo[0][1] + hi[0][3] : lo[0][0] + hi[0][2];
    const float v1 = odd ? lo[1][1] + hi[1][3] : lo[1][0] + hi[1][2];
    const float v2 = odd ? lo[2][1] + hi[2][3] : lo[2][0] + hi[2][2];
    float o0, o1, o2, n = 0.f;
    asm volatile("{\n.reg .pred p;\nsetp.ne.u32 p, %5, 0;\n"
                 "@p atom.relaxed.gpu.global.add.v4.f32 {%0,%1,%2,%3}, [%4], {%6,%7,%8,%9};\n}"
                 : "=f"(o0), "=f"(o1), "=f"(o2), "+f"(n)
                 : "l"(acc), "r"((uint32_t)live), "f"(v0), "f"(v1), "f"(v2), "f"(1.0f) : "memory");
    asm volatile("{\n.reg .pred p, q;\nsetp.eq.f32 p, %4, %5;\nsetp.ne.and.u32 q, %6, 0, p;\n"
                 "@p st.global.u16 [%0], %1;\n@p st.global.u16 [%0+128], %2;\n@q st.global.u16 [%0+256], %3;\n}"
                 ::"l"(out), "h"(__bfloat16_as_ushort(__float2bfloat16_rn(o0 + v0))),
                   "h"(__bfloat16_as_ushort(__float2bfloat16_rn(o1 + v1))), "h"(__bfloat16_as_ushort(__float2bfloat16_rn(o2 + v2))),
                   "f"(n), "f"((float)(NSRC - 1)), "r"((uint32_t)third) : "memory");
    if (acc == g_acc && n == (float)(NSRC - 1))
        asm volatile("st.relaxed.gpu.global.u32 [%0], %1;" ::"l"(&g_sync.epoch), "r"(epoch + 1u) : "memory");
}

__device__ __forceinline__ int pair_of(int sg, uint32_t j) { return sg * G + (j % (G / 4)) * 4 + j / (G / 4); }
__device__ __forceinline__ int order_of(int r, int b) { return b * (G / 4) + (r >> 2); }

__device__ __forceinline__ int window_row(int sg, uint32_t u, bool& isv) {
    const uint32_t blk = u / 4;
    isv = blk >= 2 * NSTEP - LA || (blk >= LA && ((blk - LA) & 1));
    const uint32_t step = blk < LA ? blk : blk >= 2 * NSTEP - LA ? blk - NSTEP : (blk - LA) / 2 + (isv ? 0 : LA);
    const int pair = pair_of(sg, step * WPS + (u % 4) / NT);
    return ((pair & 3) * NH + (pair >> 2)) * SK + (SK - WIN);
}

__device__ __forceinline__ float4* ocell(uint32_t pair, uint32_t i) {
    return g_oacc + (pair * 8 + (i >> 3)) * OAL + (i & 7);
}

__device__ __forceinline__ void settle(int cycles) {
    const uint32_t t0 = (uint32_t)clock();
    while ((uint32_t)clock() - t0 < (uint32_t)cycles) __nanosleep(20);
}

struct Ring {
    uint32_t full, addr, phase, first_full;
    __device__ __forceinline__ void wait() const { mbar_wait(full, phase); }
    __device__ __forceinline__ void skip(int n) {
        full += n * 8; addr += n * SLOT;
        if (full >= first_full + NS * 8) { full -= NS * 8; addr -= NS * SLOT; phase ^= 1; }
    }
    __device__ __forceinline__ void release(int lane) {
        __syncwarp();
        if (lane == 0) mbar_arrive(full + NS * 8);
        full += 8; addr += SLOT;
        if (full == first_full + NS * 8) { full = first_full; addr -= NS * SLOT; phase ^= 1; }
    }
};

__device__ __forceinline__ void pin3(uint32_t (&v)[3]) {
    asm volatile("" : "+r"(v[0]), "+r"(v[1]), "+r"(v[2]));
}
__device__ __forceinline__ void gemv_loop(Ring& ring, int n, uint32_t a_addr, uint32_t a_step, uint32_t (&off)[3],
                                          float (&lo)[3][4], float (&hi)[3][4], int lane) {
    pin3(off);
#pragma unroll
    for (int s = 0; s < 3; s++)
#pragma unroll
        for (int e = 0; e < 4; e++) { lo[s][e] = 0.f; hi[s][e] = 0.f; }
#pragma unroll 1
    for (int it = 0; it < n; it++) {
        uint32_t a[4], b[3][4];
        lds128(a_addr, a);
        a_addr += a_step;
        ring.wait();
#pragma unroll
        for (int s = 0; s < 3; s++) ldsm_x4_t(ring.addr + off[s], b[s]);
#pragma unroll
        for (int s = 0; s < 3; s++) { mma16816(lo[s], a, b[s][0], b[s][1]); mma16816(hi[s], a, b[s][2], b[s][3]); }
        ring.release(lane);
    }
}

__global__ void __launch_bounds__(NTHR, 1)
fused_decode_kernel(const char* __restrict__ wq, const bf16* __restrict__ x, bf16* __restrict__ out,
                    const char* __restrict__ kc, const char* __restrict__ vc, const char* __restrict__ wo,
                    const char* __restrict__ w2, const __grid_constant__ Maps maps) {
    asm volatile("{\n.reg .pred p;\n.reg .b32 t, c, a, b;\n.reg .b64 o;\n"
                 "mov.u32 t, %%tid.x;\nmov.u32 c, %%ctaid.x;\n"
                 "and.b32 a, c, 3;\nshr.u32 c, c, 2;\nmul.lo.u32 a, a, 15360;\nmad.lo.u32 a, c, 3, a;\n"
                 "shr.u32 b, t, 2;\nmad.lo.u32 a, b, 92, a;\nadd.u32 a, a, t;\nmad.wide.u32 o, a, 128, %0;\n"
                 "and.b32 b, t, 3;\nsetp.ne.u32 p, b, 3;\nsetp.lt.and.u32 p, t, %1, p;\n@p prefetch.global.L2 [o];\n}"
                 ::"l"(wq), "n"(PF_ROWS * 4) : "memory");
    extern __shared__ __align__(1024) unsigned char smem[];
    const uint32_t sb = (uint32_t)__cvta_generic_to_shared(smem);
    const uint32_t bar_full = sb + SM_BAR;
    if (threadIdx.x == 0 && blockIdx.x < NATT) {
#pragma unroll 1
        for (int i = 0; i < DEPTH0; i++) {
            mbar_init(bar_full + i * 8, 1);
            mbar_expect_tx(bar_full + i * 8, 12288);
            tma3d(sb + SM_RING + i * SLOT, &maps.wq, (blockIdx.x >> 2) * 3, (blockIdx.x & 3) * 160 + i * 32, bar_full + i * 8);
        }
    }
    unsigned ptid, cta;
    asm volatile("mov.u32 %0, %%tid.x;\nmov.u32 %1, %%ctaid.x;" : "=r"(ptid), "=r"(cta));
    const int tid = ptid < 32 ? ptid + NCW * 32 : ptid < (NCW + 1) * 32 ? ptid - 32 : ptid;
    const int warp = tid >> 5, lane = tid & 31;
    const bool is_att = cta < NATT;
    const int h = cta >> 2, qd = cta & 3;
    const int sg = cta / G, r = cta % G;

    if (warp == NCW) {
        volatile int* pace = reinterpret_cast<volatile int*>(smem + SM_PACE);
        if (lane == 0) {
            pace[0] = 0;
            pace[1] = is_att ? DEPTH : DEPTH_FFN;
#pragma unroll
            for (int i = 0; i < NBAR; i++)
                if (i >= DEPTH0 || !is_att)
                    mbar_init(bar_full + i * 8, i < NS ? 1 : i < 2 * NS ? NCW : i < 2 * NS + NSTEP ? NXW :
                                                i == 2 * NS + NSTEP ? NXW * NB : i == NBAR - 1 ? NXW : 1);
            asm volatile("fence.mbarrier_init.release.cluster;" ::: "memory");
        }
        __syncwarp();
        asm volatile("bar.arrive 2, %0;" ::"n"(NTHR) : "memory");
        if (lane == 0) {
            const int n_items = is_att ? ITEMS_ATT : ITEMS_FFN;
            asm volatile("prefetch.tensormap [%0];" ::"l"(is_att ? &maps.k : &maps.w3) : "memory");
            asm volatile("prefetch.tensormap [%0];" ::"l"(&maps.v) : "memory");
            asm volatile("prefetch.tensormap [%0];" ::"l"(&maps.w2) : "memory");
            asm volatile("prefetch.tensormap [%0];" ::"l"(&maps.wo) : "memory");
#pragma unroll 1
            for (int i = is_att ? DEPTH0 : 0; i < n_items; i++) {
                const CUtensorMap* map;
                int c1, c2;
                uint32_t bytes = 12288;
                if (is_att) {
                    const uint32_t u = i - 5;
                    if (u < NKV) {
                        bool isv;
                        c2 = window_row(sg, u, isv) + ((u % NT) * G + r) * TK;
                        map = isv ? &maps.v : &maps.k;
                        c1 = 0;
                    } else if (i < 5) {
                        map = &maps.wq; c1 = h * 3; c2 = qd * 160 + i * 32;
                    } else if (u < NKV + 2) {
                        map = &maps.w2; c1 = qd * 5; c2 = h * 48 + (u - NKV) * 24; bytes = 7680;
                    } else {
                        map = &maps.wo; c1 = qd * 5; c2 = h * DH + (u - NKV - 2) * 32; bytes = 10240;
                    }
                } else {
                    map = i < 40 ? &maps.w1 : &maps.w3; c1 = qd * 6; c2 = (i < 40 ? i : i - 40) * 16;
                }
                const int depth = pace[1] + (is_att && i >= 5 + NKV + 5 ? 3 : 0);
                const uint32_t slot = (uint32_t)i % NS, landed = i - depth;
                if (i >= NS) mbar_wait(bar_full + (NS + slot) * 8, ((uint32_t)i / NS - 1) & 1);
                mbar_expect_tx(bar_full + slot * 8, bytes);
                uint32_t dst = sb + SM_RING + slot * SLOT, fb = bar_full + slot * 8;
                asm volatile("" : "+r"(dst), "+r"(fb), "+l"(map), "+r"(c1), "+r"(c2));
                if (i >= depth) mbar_wait(bar_full + (landed % NS) * 8, (landed / NS) & 1);
                tma3d(dst, map, c1, c2, fb);
                pace[0] = landed + 1;
                const uint32_t un = i - 5 + 3;
                if (is_att && un < NKV && un % NT == 0 && r == (un / NT) % G) {
                    bool isv;
                    const int row = window_row(sg, un, isv);
                    asm volatile("prefetch.global.L2 [%0];" ::"l"((isv ? vc : kc) + (size_t)row * (DH * 2)) : "memory");
                }
                if (is_att && un == NKV) {
                    asm volatile("prefetch.global.L2 [%0];" ::"l"(w2 + h * (48 * DM * 2)) : "memory");
                    asm volatile("prefetch.global.L2 [%0];" ::"l"(wo + h * (DH * DM * 2)) : "memory");
                }
            }
            pace[0] = n_items - DEPTH;
        }
        return;
    }

    const int g = lane >> 2, t = lane & 3;
    uint32_t epoch;
    asm volatile("ld.relaxed.gpu.global.u32 %0, [%1];" : "=r"(epoch) : "l"(&g_sync.epoch) : "memory");

    if (warp == W_PACE) {
        const uint32_t tag = (epoch + 1u) & 1u;
        asm volatile("bar.sync 2, %0;" ::"n"(NTHR) : "memory");
        if (lane == 0) asm volatile("red.release.gpu.global.add.u32 [%0], 1;" ::"l"(&g_sync.inits) : "memory");
        if (!is_att) return;
        volatile int* pace = reinterpret_cast<volatile int*>(smem + SM_PACE);
        if (cta == 0 && lane == 0) asm volatile("st.relaxed.gpu.global.u32 [%0], %1;" ::"l"(&g_sync.prog[epoch & 1u]), "r"(0u) : "memory");
        int reported = 0, j = 0;
        bool due = false;
#pragma unroll 1
        for (unsigned it = 0;; it++) {
            const int landed = pace[0];
            if (j == NSTEP && landed >= ITEMS_ATT - DEPTH) {
                if (lane == 0)
                    asm volatile("red.relaxed.gpu.global.add.u32 [%0], %1;" ::"l"(&g_sync.prog[~epoch & 1u]), "r"(landed - reported) : "memory");
                return;
            }
            int sum = 0;
            constexpr int RPL = (G + 31) / 32;
            uint2 ml[WPS][RPL];
            uint32_t bad = 1u;
            unsigned n = (epoch + 1u) * NCTA;
            if (lane == 0)
                asm volatile("atom.relaxed.gpu.global.add.u32 %0, [%1], %2;"
                             : "=r"(sum) : "l"(&g_sync.prog[~epoch & 1u]), "r"(landed - reported) : "memory");
            if (due) {
#pragma unroll
                for (int u = 0; u < WPS; u++)
#pragma unroll
                    for (int k = 0; k < RPL; k++) ml[u][k] = ld_word(g_ml + (pair_of(sg, j * WPS + u) * G + k * 32 + lane % G) * MLS);
                if (j == 0) asm volatile("ld.acquire.gpu.global.u32 %0, [%1];" : "=r"(n) : "l"(&g_sync.inits) : "memory");
            }
            reported = landed;
            if (lane == 0 && it >= 2) {
                const int lag16 = sum / (NATT / 16) - landed * 16 + PACE_BIAS;
                pace[1] = min(max(DEPTH + ((lag16 * PACE_GAIN + 128) >> 8), DEPTH_MIN), DEPTH_MAX);
            }
            if (due) {
                bad = 0;
#pragma unroll
                for (int u = 0; u < WPS; u++)
#pragma unroll
                    for (int k = 0; k < RPL; k++) bad |= ml[u][k].x ^ tag;
            }
            if (__all_sync(0xffffffffu, !(bad & 1u) && n == (epoch + 1u) * NCTA)) {
#pragma unroll
                for (int u = 0; u < WPS; u++) {
                    float M = -INFINITY, L = 0.f, w = 0.f;
#pragma unroll
                    for (int k = 0; k < RPL; k++) M = fmaxf(M, __uint_as_float(ml[u][k].x & ~1u));
#pragma unroll
                    for (int o = G / RPL / 2; o; o >>= 1) M = fmaxf(M, shx(M, o));
#pragma unroll
                    for (int k = 0; k < RPL; k++) {
                        const float wk = __expf(__uint_as_float(ml[u][k].x & ~1u) - M);
                        L += wk * __uint_as_float(ml[u][k].y);
                        if (k == r / 32) w = wk;
                    }
#pragma unroll
                    for (int o = G / RPL / 2; o; o >>= 1) L += shx(L, o);
                    if (lane == r % 32) reinterpret_cast<float*>(smem + SM_LS)[16 + (j & 3) * WPS + u] = __fdividef(w, L);
                }
                if (lane == r % 32) {
                    mbar_arrive(bar_full + B_WRDY + (j & 3) * 8);
                }
                j++;
                due = false;
            }
            __nanosleep(PACE_NS);
            if (!due && j < NSTEP && mbar_test(bar_full + B_WTRIG + (j & 3) * 8, (j >> 2) & 1))
                due = (uint32_t)clock() - (uint32_t)pace[2 + (j & 3)] >= ML_SETTLE;
            if (it > SPIN_LIMIT) __trap();
        }
    }
    if (warp > W_PROD) {
        const uint32_t tag = (epoch + 1u) & 1u;
        const int e = tid - (W_PROD + 1) * 32;
        if (is_att) {
            st_fill4(reinterpret_cast<float*>(ocell(cta, e)), 0u);
            if (e < 32) *reinterpret_cast<uint32_t*>(smem + SM_HF + e * 16 + 12) = 0u;
        } else {
#pragma unroll 1
            for (int c = e; c < 256; c += NXW * 32) {
                const bf16* xp = x + qd * DM + (c >> 6) * 160 + ((c >> 3) & 7) * 8 + (c & 3) * 2 + ((c >> 2) & 1);
                asm volatile("st.relaxed.gpu.global.v4.f32 [%0], {%1,%2,%3,%4};"
                             ::"l"(g_acc + (qd * 32 + (c >> 3)) * ACS + (c & 7)), "f"(__bfloat162float(xp[0])),
                               "f"(__bfloat162float(xp[64])), "f"((c & 32) ? 0.f : __bfloat162float(xp[128])), "f"(0.f) : "memory");
            }
        }
        asm volatile("bar.sync 2, %0;" ::"n"(NTHR) : "memory");
        if (!is_att) return;
        {
            const uint32_t eq = (e >> 5) * 24 + min(lane, 23), xw = eq / 6, xr = eq % 6;
            mbar_wait(bar_full + B_QTRIG, 0);
            settle(Q_SETTLE);
#pragma unroll 1
            for (int j = 0; j < NSTEP; j++) {
                uint4 v[WPS][4];
                uint32_t bad;
                unsigned spin = 0;
                do {
#pragma unroll
                    for (int u = 0; u < WPS; u++) {
                        const int pair = pair_of(sg, j * WPS + u);
                        const float* src = g_qpart + ((pair >> 2) * 4 * NB + (pair & 3)) * VS + xw * 32 + xr * 4;
#pragma unroll
                        for (int k = 0; k < 4; k++) v[u][k] = ld_word2(src + k * NB * VS);
                    }
                    bad = 0;
#pragma unroll
                    for (int u = 0; u < WPS; u++)
#pragma unroll
                        for (int k = 0; k < 4; k++) bad |= (v[u][k].x ^ tag) | (v[u][k].z ^ tag);
                    if (++spin > SPIN_LIMIT) __trap();
                } while (bad & 1u);
#define SUM4(c) ((__uint_as_float(v[u][0].c) + __uint_as_float(v[u][1].c)) + (__uint_as_float(v[u][2].c) + __uint_as_float(v[u][3].c)))
#pragma unroll
                for (int u = 0; u < WPS; u++) {
                    unsigned char* dst = smem + SM_QS + (j * WPS + u) * (DH * 2) + (xr & 1) * 192 + ((xr >> 1) * 8 + xw) * 4;
                    *reinterpret_cast<uint32_t*>(dst) = pack_bf2(SUM4(x), SUM4(y));
                    *reinterpret_cast<uint32_t*>(dst + 96) = pack_bf2(SUM4(z), SUM4(w));
                }
#undef SUM4
                __syncwarp();
                if (lane == 0) mbar_arrive(bar_full + B_QRDY + j * 8);
            }
        }
        bool have_h = false;
#pragma unroll 1
        for (int b = 0; b <= NB; b++) {
            if (!have_h && (b == NB || order_of(r, b) >= HSTEP * WPS)) {
                have_h = true;
                mbar_wait(bar_full + B_HTRIG, 0);
#pragma unroll 1
                for (int i = e; i < 96; i += NXW * 32) {
                    const int k = (i % 24) * 2;
                    uint2 v;
                    unsigned spin = 0;
                    do {
                        v = ld_word(g_h + i / 24 * FF + h * 48 + k);
                        if (++spin > SPIN_LIMIT) __trap();
                    } while ((v.x ^ tag) & 1u);
                    *reinterpret_cast<uint32_t*>(smem + SM_HF + k / 24 * 256 + i / 24 * 64 + frag_off(k % 24)) = __byte_perm(v.x, v.y, 0x7632);
                }
                __syncwarp();
                if (lane == 0) mbar_arrive(bar_full + B_HRDY);
            }
            if (b == NB) break;
            const float4* src = ocell(h * NB + b, e);
            uint32_t dst = sb + SM_OF + (e >> 5) * 256 + b * 64 + frag_off(lane), ordy = bar_full + B_ORDY;
            asm volatile("" : "+r"(dst), "+l"(src), "+r"(ordy));
            mbar_wait(bar_full + B_OTRIG + b * 8, 0);
            const int pause = order_of(r, b) < G - WPS ? O_SETTLE : 0;
            unsigned spin = 0;
            float o0, o1, o2, n;
            do {
                settle(pause);
                asm volatile("{\n.reg .b128 w;\n.reg .b64 w0, w1;\nld.relaxed.gpu.global.b128 w, [%4];\nmov.b128 {w0, w1}, w;\n"
                             "mov.b64 {%0,%1}, w0;\nmov.b64 {%2,%3}, w1;\n}"
                             : "=f"(o0), "=f"(o1), "=f"(o2), "=f"(n) : "l"(src) : "memory");
                asm volatile("st.shared.u16 [%0], %1;\nst.shared.u16 [%0+512], %2;\nst.shared.u16 [%0+1024], %3;"
                             ::"r"(dst), "h"(__bfloat16_as_ushort(__float2bfloat16_rn(o0))),
                               "h"(__bfloat16_as_ushort(__float2bfloat16_rn(o1))), "h"(__bfloat16_as_ushort(__float2bfloat16_rn(o2))) : "memory");
                if (++spin > SPIN_LIMIT) __trap();
            } while (n != (float)G);
            __syncwarp();
            if (lane == 0) mbar_arrive(ordy);
        }
        return;
    }

    if (warp < NB) {
        uint2 raw[5];
#pragma unroll
        for (int i = 0; i < 5; i++) raw[i] = __ldg(reinterpret_cast<const uint2*>(x + warp * DM) + i * 32 + lane);
        float s = 0.f;
#pragma unroll
        for (int i = 0; i < 5; i++) s += (bf_lo(raw[i].x) + bf_hi(raw[i].x)) + (bf_lo(raw[i].y) + bf_hi(raw[i].y));
#pragma unroll
        for (int o = 16; o; o >>= 1) s += shx(s, o);
        const float mean = s * (1.0f / DM);
        float q2 = 0.f;
#pragma unroll
        for (int i = 0; i < 5; i++) {
            const float d0 = bf_lo(raw[i].x) - mean, d1 = bf_hi(raw[i].x) - mean;
            const float d2 = bf_lo(raw[i].y) - mean, d3 = bf_hi(raw[i].y) - mean;
            q2 += (d0 * d0 + d1 * d1) + (d2 * d2 + d3 * d3);
        }
#pragma unroll
        for (int o = 16; o; o >>= 1) q2 += shx(q2, o);
        const float mb = bf_round(mean);
        const float rs = __frcp_rn(bf_round(__fsqrt_rn(bf_round(bf_round(q2 * (1.0f / DM)) + 1e-5f))));
        const uint32_t k = (lane * 4) & 31;
        unsigned char* dst = smem + SM_XF + warp * 64 +
            (is_att ? (lane >> 3) * 256 + frag_off(k) : (lane >> 2) * 256 + frag_off(k & 15));
        const uint32_t step = is_att ? 1024 : 2048;
#pragma unroll
        for (int i = 0; i < 5; i++) {
            const uint32_t d0 = pack_bf2(bf_lo(raw[i].x) - mb, bf_hi(raw[i].x) - mb);
            const uint32_t d1 = pack_bf2(bf_lo(raw[i].y) - mb, bf_hi(raw[i].y) - mb);
            *reinterpret_cast<uint32_t*>(dst + i * step) = pack_bf2(bf_lo(d0) * rs, bf_hi(d0) * rs);
            *reinterpret_cast<uint32_t*>(dst + i * step + 16) = pack_bf2(bf_lo(d1) * rs, bf_hi(d1) * rs);
        }
    }
    asm volatile("bar.sync 2, %0;" ::"n"(NTHR) : "memory");
    uint32_t tag = (epoch + 1u) & 1u;
    asm volatile("" : "+r"(tag));

    Ring ring{bar_full, sb + SM_RING, 0u, bar_full};
    float lo[3][4] = {}, hi[3][4] = {};
    uint32_t off[3];
    const uint32_t a_lane = (g & 3) * 64 + t * 16;

    if (is_att) {
        float* lsum = reinterpret_cast<float*>(smem + SM_LS);
#pragma unroll 1
        for (int j = -1; j < NSTEP + LA; j++) {
            if (j >= 0 && j < NSTEP) {
                constexpr int WW = NCW / WPS;
                const int win = j * WPS + warp / WW;
                uint32_t qf[6][4];
                mbar_wait(bar_full + B_QRDY + j * 8, 0);
#pragma unroll
                for (int i = 0; i < 6; i++) lds128(sb + SM_QS + win * (DH * 2) + t * 96 + i * 16, qf[i]);
                const uint32_t key = (warp & 1) * 16 + (lane & 15);
                const uint32_t item = 5 + (j + max(j - LA, 0)) * 4 + (warp >> 1), slot = item % NS;
#pragma unroll
                for (int s = 0; s < 3; s++)
                    off[s] = sb + SM_RING + slot * SLOT + key * 384 + s * 128 + (((lane >> 4) ^ ((3 * key + s) & 7)) << 4);
                pin3(off);
                mbar_wait(bar_full + slot * 8, (item / NS) & 1);
                float c[3][4] = {};
#pragma unroll
                for (int dq = 0; dq < 4; dq++)
#pragma unroll
                    for (int s = 0; s < 3; s++) {
                        uint32_t a[4];
                        ldsm_x4(off[s] ^ (dq << 5), a);
                        mma16816(c[s], a, qf[s * 2 + (dq >> 1)][(dq & 1) * 2], qf[s * 2 + (dq >> 1)][(dq & 1) * 2 + 1]);
                    }
                __syncwarp();
                if (lane == 0)
                    asm volatile("mbarrier.arrive.shared::cta.b64 _, [%0], %1;" ::"r"(bar_full + (NS + slot) * 8), "n"(NCW / 2) : "memory");
                ring.skip(4);
                const float raw = (t & 1) ? (c[0][2] + c[1][2]) + c[2][2] : (c[0][0] + c[1][0]) + c[2][0];
                const float sv = bf_round(bf_round(raw) * 0.07216878364870323f);
                float m = fmaxf(sv, shx(sv, 1));
#pragma unroll
                for (int o = 4; o < 32; o <<= 1) m = fmaxf(m, shx(m, o));
                if (lane == 0) lsum[8 + warp] = m;
                cons_bar();
#pragma unroll
                for (int i = 0; i < WW; i += 2) {
                    const float2 m2 = *reinterpret_cast<const float2*>(lsum + 8 + warp / WW * WW + i);
                    m = fmaxf(m, fmaxf(m2.x, m2.y));
                }
                float l = __expf(sv - m);
                *reinterpret_cast<bf16*>(smem + SM_PF + ((j & 3) * 4 + (warp >> 1)) * 64 + frag_off((warp & 1) * 16 + (t & 1) * 8 + g)) =
                    __float2bfloat16_rn(l);
                l += shx(l, 1);
#pragma unroll
                for (int o = 4; o < 32; o <<= 1) l += shx(l, o);
                if (lane == 0) lsum[warp] = l;
                cons_bar();
                if (tid % (WW * 32) < 4) {
                    l = 0.f;
#pragma unroll
                    for (int i = 0; i < WW; i += 2) {
                        const float2 l2 = *reinterpret_cast<const float2*>(lsum + warp + i);
                        l += l2.x + l2.y;
                    }
                    st_tag2(g_ml + (pair_of(sg, win) * G + r) * MLS + lane * 2, m, l, tag);
                    if (tid == 0) {
                        reinterpret_cast<volatile int*>(smem + SM_PACE)[2 + (j & 3)] = (int)clock();
                        mbar_arrive(bar_full + B_WTRIG + (j & 3) * 8);
                        if (j == HSTEP) mbar_arrive(bar_full + B_HTRIG);
                    }
                }
                if (j < LA) continue;
            }
            const bool kv = j >= 0;
            const uint32_t jv = j - LA;
#pragma unroll
            for (int s = 0; s < 3; s++) off[s] = lane * 384 + s * 128 + ((warp ^ ((3 * lane + s) & 7)) << 4);
#pragma unroll 1
            for (int u = 0; u < (kv ? WPS : 1); u++) {
                const int pair = pair_of(sg, jv * WPS + u);
                uint32_t trig = !kv ? bar_full + B_QTRIG : (pair >> 2) == h ? bar_full + B_OTRIG + (pair & 3) * 8 : 0;
                if (tid != 0) trig = 0;
                float4* oacc = ocell(pair, warp * 8 + 2 * t + (g & 1));
                uint32_t wrdy = bar_full + B_WRDY + (jv & 3) * 8;
                asm volatile("" : "+l"(oacc), "+r"(trig), "+r"(wrdy));
                gemv_loop(ring, kv ? NT : 5,
                          kv ? sb + SM_PF + ((jv & 3) * 4 + u * NT) * 64 + t * 16 : sb + SM_XF + qd * 5 * 256 + a_lane,
                          kv ? 64 : 256, off, lo, hi, lane);
                if (kv) {
                    mbar_wait(wrdy, (jv >> 2) & 1);
                    const float w = lsum[16 + (jv & 3) * WPS + u];
                    if (g < 2)
                        asm volatile("red.relaxed.gpu.global.add.v4.f32 [%0], {%1,%2,%3,%4};"
                                     ::"l"(oacc), "f"(w * (g ? lo[0][1] + hi[0][3] : lo[0][0] + hi[0][2])),
                                       "f"(w * (g ? lo[1][1] + hi[1][3] : lo[1][0] + hi[1][2])),
                                       "f"(w * (g ? lo[2][1] + hi[2][3] : lo[2][0] + hi[2][2])), "f"(1.0f) : "memory");
                } else if (g < NB) {
#pragma unroll
                    for (int s = 0; s < 3; s++)
                        st_tag2(g_qpart + (cta * NB + g) * VS + warp * 32 + 2 * t + s * 8, lo[s][0] + hi[s][2], lo[s][1] + hi[s][3], tag);
                }
                if (trig) mbar_arrive(trig);
            }
            const bool pass = j == NSTEP + LA - 1;
            if (kv && !pass) continue;

            {
                constexpr int I0 = 5 + NKV;
                static_assert(((I0 / NS) & 1) == 0 && I0 / NS == (I0 + 7) / NS, "tail items complete an even phase");
                const uint32_t done = bar_full + B_QTRIG;
                uint32_t fb = pass ? bar_full + (I0 % NS) * 8 : done, fs = pass ? 8 : 0, ordy = pass ? bar_full + B_ORDY : done;
                uint32_t off2[3], a[8][4], b[8][3][4], a_addr = sb + SM_HF + a_lane;
#pragma unroll
                for (int s = 0; s < 3; s++) {
                    const uint32_t w64 = lane * 320 + (warp + 8 * s) * 16;
                    off[s] = sb + SM_RING + (I0 % NS) * SLOT + (w64 ^ (((w64 >> 7) & 3) << 4));
                    off2[s] = lane < 24 ? off[s] : off[s] - 8 * 320;
#pragma unroll
                    for (int e = 0; e < 4; e++) { lo[s][e] = 0.f; hi[s][e] = 0.f; }
                }
                const float4* accp = g_acc + (((g & 3) * 4 + qd) * NCW + warp) * ACS + (g >> 2) * 4 + t;
                bf16* outp = out + (g & 3) * DM + qd * 160 + warp * 8 + 2 * t + (g >> 2);
                pin3(off);
                asm volatile("" : "+l"(accp), "+l"(outp), "+r"(a_addr), "+r"(ordy), "+r"(fb), "+r"(fs));
                auto load_b = [&](int i, bool& next) {
                    if (!next) mbar_wait(fb + i * fs, 0);
                    if (i < 7) next = mbar_test(fb + (i + 1) * fs, 0);
#pragma unroll
                    for (int s = 0; s < 3; s++)
                        if (s < 2 || warp < 4) ldsm_x4_t((i < 2 ? off2[s] : off[s]) + i * SLOT, b[i][s]);
                };
                auto mul = [&](int i) {
#pragma unroll
                    for (int s = 0; s < 3; s++)
                        if (s < 2 || warp < 4) { mma16816(lo[s], a[i], b[i][s][0], b[i][s][1]); mma16816(hi[s], a[i], b[i][s][2], b[i][s][3]); }
                };
                bool next = mbar_test(fb, 0);
                mbar_wait(pass ? bar_full + B_HRDY : done, 0);
                lds128(a_addr, a[0]);
                lds128(a_addr + 256, a[1]);
                load_b(0, next);
#pragma unroll
                for (int i = 0; i < 7; i++) {
                    load_b(i + 1, next);
                    if (i == 2) {
                        mbar_wait(ordy, 0);
#pragma unroll
                        for (int k = 2; k < 8; k++) lds128(a_addr + k * 256, a[k]);
                    }
                    mul(i);
                }
                mul(7);
                add_out(accp, outp, lo, hi, g >= NB, warp < 4, pass, epoch);
            }
        }
    } else {
        float gate[6][2];
#pragma unroll
        for (int s = 0; s < 3; s++) {
            const uint32_t r128 = (lane & 15) * 6 + 2 * s + (lane >> 4);
            off[s] = r128 * 128 + ((warp ^ (r128 & 7)) << 4);
        }
#pragma unroll 1
        for (int ps = 0; ps < 2; ps++) {
#pragma unroll
            for (int s = 0; s < 3; s++) {
                gate[2 * s][0] = lo[s][0]; gate[2 * s][1] = lo[s][1];
                gate[2 * s + 1][0] = hi[s][0]; gate[2 * s + 1][1] = hi[s][1];
            }
            gemv_loop(ring, 40, sb + SM_XF + a_lane, 256, off, lo, hi, lane);
        }
#pragma unroll
        for (int p = 0; p < 6; p++) {
            float hv[2];
#pragma unroll
            for (int e = 0; e < 2; e++) {
                const float gt = bf_round(gate[p][e]);
                hv[e] = bf_round(bf_round(__fdividef(gt, 1.0f + __expf(-gt))) * bf_round((p & 1) ? hi[p >> 1][e] : lo[p >> 1][e]));
            }
            if (g < NB) st_tag2(g_h + g * FF + qd * 384 + p * 64 + warp * 8 + 2 * t, hv[0], hv[1], tag);
        }
    }
}

typedef CUresult (*EncodeFn)(CUtensorMap*, CUtensorMapDataType, cuuint32_t, void*, const cuuint64_t*, const cuuint64_t*,
                             const cuuint32_t*, const cuuint32_t*, CUtensorMapInterleave, CUtensorMapSwizzle,
                             CUtensorMapL2promotion, CUtensorMapFloatOOBfill);

void make_map(EncodeFn enc, CUtensorMap* m, const void* p, uint64_t rows, uint64_t cols, uint32_t inner, uint32_t parts,
              uint32_t box_rows) {
    const cuuint64_t dims[3] = {inner, cols / inner, rows};
    const cuuint64_t strides[2] = {inner * 2ull, cols * 2ull};
    const cuuint32_t box[3] = {inner, parts, box_rows};
    const cuuint32_t es[3] = {1, 1, 1};
    enc(m, CU_TENSOR_MAP_DATA_TYPE_BFLOAT16, 3, const_cast<void*>(p), dims, strides, box, es, CU_TENSOR_MAP_INTERLEAVE_NONE,
        inner == 64 ? CU_TENSOR_MAP_SWIZZLE_128B : CU_TENSOR_MAP_SWIZZLE_64B, CU_TENSOR_MAP_L2_PROMOTION_NONE,
        CU_TENSOR_MAP_FLOAT_OOB_FILL_NONE);
}

}

extern "C" void kernel_launch(void* const* d_in, const int* in_sizes, int n_in, void* d_out, int out_size) {
    (void)in_sizes; (void)n_in; (void)out_size;
    static EncodeFn enc = nullptr;
    if (!enc) {
        void* fn = nullptr;
        cudaDriverEntryPointQueryResult qr;
        cudaGetDriverEntryPoint("cuTensorMapEncodeTiled", &fn, cudaEnableDefault, &qr);
        enc = (EncodeFn)fn;
        cudaFuncSetAttribute(fused_decode_kernel, cudaFuncAttributeMaxDynamicSharedMemorySize, SM_TOTAL);
    }
    Maps maps;
    make_map(enc, &maps.k, d_in[1], (uint64_t)NB * NH * SK, DH, 64, 3, TK);
    make_map(enc, &maps.v, d_in[2], (uint64_t)NB * NH * SK, DH, 64, 3, TK);
    make_map(enc, &maps.wq, d_in[3], DM, NH * DH, 64, 3, 32);
    make_map(enc, &maps.wo, d_in[4], NH * DH, DM, 32, 5, 32);
    make_map(enc, &maps.w1, d_in[6], DM, FF, 64, 6, 16);
    make_map(enc, &maps.w3, d_in[7], DM, FF, 64, 6, 16);
    make_map(enc, &maps.w2, d_in[8], FF, DM, 32, 5, 24);
    fused_decode_kernel<<<NCTA, NTHR, SM_TOTAL>>>((const char*)d_in[3], (const bf16*)d_in[0], (bf16*)d_out,
                                                  (const char*)d_in[1], (const char*)d_in[2], (const char*)d_in[4],
                                                  (const char*)d_in[8], maps);
}
```

```cpp
#include <cuda_runtime.h>
#include <cuda.h>
#include <cuda_bf16.h>
#include <stdint.h>

namespace {

typedef __nv_bfloat16 bf16;

constexpr int NB = 4, DM = 640, NH = 32, DH = 192, SK = 8192, WIN = 2048, FF = 1536;

constexpr int G = 32;
constexpr int TK = 32;
constexpr int NT = WIN / TK / G;
constexpr int NSTEP = 16;
constexpr int WPS = G / NSTEP;
constexpr int LA = 3;
constexpr int MLS = 8;
constexpr int OAL = 72;
constexpr int HSTEP = 11;
constexpr int NS = 16;
constexpr int SLOT = 12288;
constexpr int DEPTH = 4, DEPTH_MIN = 3, DEPTH_MAX = 6, DEPTH_FFN = 5;
constexpr int PACE_GAIN = 6, PACE_BIAS = 16, PACE_NS = 500;
constexpr int Q_SETTLE = 1600, ML_SETTLE = 4000, O_SETTLE = 3000;
constexpr int DEPTH0 = 5;
constexpr int PF_ROWS = 64;
static_assert(DEPTH0 <= 5, "DEPTH0");
constexpr int NATT = 128, NFFN = 4, NCTA = NATT + NFFN;
constexpr int NCW = 8;
constexpr int NXW = 2;
constexpr int W_PROD = NCW, W_PACE = NCW + 1 + NXW;
constexpr int NTHR = (W_PACE + 1) * 32;
constexpr int NSRC = NH;
constexpr int VS = 256;
constexpr int ACS = 72;
static_assert(G == 16 || G == 32 || G == 64, "G");

constexpr int SM_RING = 0;
constexpr int SM_XF = SM_RING + NS * SLOT;
constexpr int SM_QS = SM_XF + 20 * 256;
constexpr int SM_PF = SM_QS + G * DH * 2;
constexpr int SM_HF = SM_PF + 4 * 4 * 64;
constexpr int SM_OF = SM_HF + 2 * 256;
constexpr int SM_LS = SM_OF + 6 * 256;
constexpr int SM_ATT_END = SM_LS + 128;
constexpr int SM_FFN_END = SM_XF + 40 * 256;
constexpr int SM_BAR = SM_ATT_END > SM_FFN_END ? SM_ATT_END : SM_FFN_END;
constexpr int B_QRDY = 2 * NS * 8, B_ORDY = B_QRDY + NSTEP * 8, B_OTRIG = B_ORDY + 8, B_QTRIG = B_OTRIG + 32,
              B_WTRIG = B_QTRIG + 8, B_WRDY = B_WTRIG + 32, B_HTRIG = B_WRDY + 32, B_HRDY = B_HTRIG + 8,
              NBAR = 2 * NS + NSTEP + 16;
constexpr int SM_PACE = SM_BAR + NBAR * 8;
constexpr int SM_TOTAL = SM_PACE + 24;
static_assert(SM_TOTAL <= 232448, "smem");

constexpr int NKV = 2 * NT * G;
constexpr int ITEMS_ATT = 5 + NKV + 2 + 6;
constexpr int ITEMS_FFN = 80;

struct Maps { CUtensorMap k, v, wq, wo, w1, w3, w2; };

struct alignas(32) Sync { unsigned epoch, inits, prog[2]; };
__device__ Sync g_sync;
__device__ __align__(128) float g_qpart[NATT * NB * VS];
__device__ __align__(128) float g_ml[NATT * G * MLS];
__device__ __align__(128) float g_h[NB * FF];
__device__ __align__(128) float4 g_oacc[NATT * 8 * OAL];
__device__ __align__(128) float4 g_acc[NB * 4 * NCW * ACS];

constexpr unsigned SPIN_LIMIT = 1u << 22;

__device__ __forceinline__ void mbar_init(uint32_t bar, int cnt) {
    asm volatile("mbarrier.init.shared::cta.b64 [%0], %1;" ::"r"(bar), "r"(cnt) : "memory");
}
__device__ __forceinline__ void mbar_expect_tx(uint32_t bar, uint32_t bytes) {
    asm volatile("mbarrier.arrive.expect_tx.shared::cta.b64 _, [%0], %1;" ::"r"(bar), "r"(bytes) : "memory");
}
__device__ __forceinline__ void mbar_arrive(uint32_t bar) {
    asm volatile("mbarrier.arrive.shared::cta.b64 _, [%0];" ::"r"(bar) : "memory");
}
__device__ __forceinline__ void mbar_wait(uint32_t bar, uint32_t parity) {
    asm volatile("{\n.reg .pred p, q;\n.reg .u32 n;\nmov.u32 n, 0;\n"
                 "W: mbarrier.try_wait.parity.shared::cta.b64 p, [%0], %1;\n"
                 "@p bra D;\nadd.u32 n, n, 1;\nsetp.lt.u32 q, n, %2;\n@q bra W;\ntrap;\nD:\n}"
                 ::"r"(bar), "r"(parity), "n"(SPIN_LIMIT) : "memory");
}
__device__ __forceinline__ bool mbar_test(uint32_t bar, uint32_t parity) {
    uint32_t ok;
    asm volatile("{\n.reg .pred p;\nmbarrier.test_wait.parity.shared::cta.b64 p, [%1], %2;\nselp.u32 %0, 1, 0, p;\n}"
                 : "=r"(ok) : "r"(bar), "r"(parity) : "memory");
    return ok;
}
__device__ __forceinline__ void tma3d(uint32_t dst, const CUtensorMap* map, int c1, int c2, uint32_t bar) {
    const uint64_t pol = 0x12F0000000000000ull;
    asm volatile("cp.async.bulk.tensor.3d.shared::cluster.global.mbarrier::complete_tx::bytes.L2::cache_hint "
                 "[%0], [%1, {%2, %3, %4}], [%5], %6;"
                 ::"r"(dst), "l"(map), "r"(0), "r"(c1), "r"(c2), "r"(bar), "l"(pol) : "memory");
}
__device__ __forceinline__ void ldsm_x4(uint32_t addr, uint32_t (&r)[4]) {
    asm volatile("ldmatrix.sync.aligned.m8n8.x4.shared.b16 {%0,%1,%2,%3}, [%4];"
                 : "=r"(r[0]), "=r"(r[1]), "=r"(r[2]), "=r"(r[3]) : "r"(addr) : "memory");
}
__device__ __forceinline__ void ldsm_x4_t(uint32_t addr, uint32_t (&r)[4]) {
    asm volatile("ldmatrix.sync.aligned.m8n8.x4.trans.shared.b16 {%0,%1,%2,%3}, [%4];"
                 : "=r"(r[0]), "=r"(r[1]), "=r"(r[2]), "=r"(r[3]) : "r"(addr) : "memory");
}
__device__ __forceinline__ void lds128(uint32_t addr, uint32_t (&r)[4]) {
    asm volatile("ld.shared.v4.u32 {%0,%1,%2,%3}, [%4];"
                 : "=r"(r[0]), "=r"(r[1]), "=r"(r[2]), "=r"(r[3]) : "r"(addr) : "memory");
}
__device__ __forceinline__ void mma16816(float (&c)[4], const uint32_t (&a)[4], uint32_t b0, uint32_t b1) {
    asm volatile("mma.sync.aligned.m16n8k16.row.col.f32.bf16.bf16.f32 {%0,%1,%2,%3}, {%4,%5,%6,%7}, {%8,%9}, {%0,%1,%2,%3};"
                 : "+f"(c[0]), "+f"(c[1]), "+f"(c[2]), "+f"(c[3])
                 : "r"(a[0]), "r"(a[1]), "r"(a[2]), "r"(a[3]), "r"(b0), "r"(b1));
}
__device__ __forceinline__ void cons_bar() { asm volatile("bar.sync 1, 256;" ::: "memory"); }

__device__ __forceinline__ float bf_round(float v) { return __bfloat162float(__float2bfloat16_rn(v)); }
__device__ __forceinline__ uint32_t pack_bf2(float lo, float hi) {
    __nv_bfloat162 t = __floats2bfloat162_rn(lo, hi);
    return *reinterpret_cast<uint32_t*>(&t);
}
__device__ __forceinline__ float bf_lo(uint32_t u) { return __uint_as_float(u << 16); }
__device__ __forceinline__ float bf_hi(uint32_t u) { return __uint_as_float(u & 0xffff0000u); }
__device__ __forceinline__ float shx(float v, int o) { return __shfl_xor_sync(0xffffffffu, v, o); }

__device__ __forceinline__ uint32_t frag_off(uint32_t k) {
    return ((k >> 1) & 3) * 16 + ((k >> 3) & 1) * 8 + ((k >> 4) & 1) * 4 + (k & 1) * 2;
}

__device__ __forceinline__ void st_tag2(float* p, float a, float b, uint32_t tag) {
    asm volatile("{\n.reg .b64 w;\n.reg .b32 x;\nlop3.b32 x, %1, 0xfffffffe, %3, 0xea;\nmov.b64 w, {x, %2};\n"
                 "st.relaxed.gpu.global.b64 [%0], w;\n}"
                 ::"l"(p), "r"(__float_as_uint(a)), "r"(__float_as_uint(b)), "r"(tag) : "memory");
}
__device__ __forceinline__ void st_fill4(float* p, uint32_t v) {
    asm volatile("{\n.reg .b64 w;\nmov.b64 w, {%1, %1};\nst.relaxed.gpu.global.v2.b64 [%0], {w, w};\n}" ::"l"(p), "r"(v) : "memory");
}
__device__ __forceinline__ uint2 ld_word(const float* p) {
    uint2 v;
    asm volatile("{\n.reg .b64 w;\nld.relaxed.gpu.global.b64 w, [%2];\nmov.b64 {%0,%1}, w;\n}" : "=r"(v.x), "=r"(v.y) : "l"(p) : "memory");
    return v;
}
__device__ __forceinline__ uint4 ld_word2(const float* p) {
    uint4 v;
    asm volatile("{\n.reg .b64 w0, w1;\nld.relaxed.gpu.global.v2.b64 {w0, w1}, [%4];\nmov.b64 {%0,%1}, w0;\nmov.b64 {%2,%3}, w1;\n}"
                 : "=r"(v.x), "=r"(v.y), "=r"(v.z), "=r"(v.w) : "l"(p) : "memory");
    return v;
}

__device__ __forceinline__ void add_out(const float4* acc, bf16* out, const float (&lo)[3][4], const float (&hi)[3][4],
                                        bool odd, bool third, bool live, uint32_t epoch) {
    const float v0 = odd ? lo[0][1] + hi[0][3] : lo[0][0] + hi[0][2];
    const float v1 = odd ? lo[1][1] + hi[1][3] : lo[1][0] + hi[1][2];
    const float v2 = odd ? lo[2][1] + hi[2][3] : lo[2][0] + hi[2][2];
    float o0, o1, o2, n = 0.f;
    asm volatile("{\n.reg .pred p;\nsetp.ne.u32 p, %5, 0;\n"
                 "@p atom.relaxed.gpu.global.add.v4.f32 {%0,%1,%2,%3}, [%4], {%6,%7,%8,%9};\n}"
                 : "=f"(o0), "=f"(o1), "=f"(o2), "+f"(n)
                 : "l"(acc), "r"((uint32_t)live), "f"(v0), "f"(v1), "f"(v2), "f"(1.0f) : "memory");
    asm volatile("{\n.reg .pred p, q;\nsetp.eq.f32 p, %4, %5;\nsetp.ne.and.u32 q, %6, 0, p;\n"
                 "@p st.global.u16 [%0], %1;\n@p st.global.u16 [%0+128], %2;\n@q st.global.u16 [%0+256], %3;\n}"
                 ::"l"(out), "h"(__bfloat16_as_ushort(__float2bfloat16_rn(o0 + v0))),
                   "h"(__bfloat16_as_ushort(__float2bfloat16_rn(o1 + v1))), "h"(__bfloat16_as_ushort(__float2bfloat16_rn(o2 + v2))),
                   "f"(n), "f"((float)(NSRC - 1)), "r"((uint32_t)third) : "memory");
    if (acc == g_acc && n == (float)(NSRC - 1))
        asm volatile("st.relaxed.gpu.global.u32 [%0], %1;" ::"l"(&g_sync.epoch), "r"(epoch + 1u) : "memory");
}

__device__ __forceinline__ int pair_of(int sg, uint32_t j) { return sg * G + (j % (G / 4)) * 4 + j / (G / 4); }
__device__ __forceinline__ int order_of(int r, int b) { return b * (G / 4) + (r >> 2); }

__device__ __forceinline__ int window_row(int sg, uint32_t u, bool& isv) {
    const uint32_t blk = u / 4;
    isv = blk >= 2 * NSTEP - LA || (blk >= LA && ((blk - LA) & 1));
    const uint32_t step = blk < LA ? blk : blk >= 2 * NSTEP - LA ? blk - NSTEP : (blk - LA) / 2 + (isv ? 0 : LA);
    const int pair = pair_of(sg, step * WPS + (u % 4) / NT);
    return ((pair & 3) * NH + (pair >> 2)) * SK + (SK - WIN);
}

__device__ __forceinline__ float4* ocell(uint32_t pair, uint32_t i) {
    return g_oacc + (pair * 8 + (i >> 3)) * OAL + (i & 7);
}

__device__ __forceinline__ void settle(int cycles) {
    const uint32_t t0 = (uint32_t)clock();
    while ((uint32_t)clock() - t0 < (uint32_t)cycles) __nanosleep(20);
}

struct Ring {
    uint32_t full, addr, phase, first_full;
    __device__ __forceinline__ void wait() const { mbar_wait(full, phase); }
    __device__ __forceinline__ void skip(int n) {
        full += n * 8; addr += n * SLOT;
        if (full >= first_full + NS * 8) { full -= NS * 8; addr -= NS * SLOT; phase ^= 1; }
    }
    __device__ __forceinline__ void release(int lane) {
        __syncwarp();
        if (lane == 0) mbar_arrive(full + NS * 8);
        full += 8; addr += SLOT;
        if (full == first_full + NS * 8) { full = first_full; addr -= NS * SLOT; phase ^= 1; }
    }
};

__device__ __forceinline__ void pin3(uint32_t (&v)[3]) {
    asm volatile("" : "+r"(v[0]), "+r"(v[1]), "+r"(v[2]));
}
__device__ __forceinline__ void gemv_loop(Ring& ring, int n, uint32_t a_addr, uint32_t a_step, uint32_t (&off)[3],
                                          float (&lo)[3][4], float (&hi)[3][4], int lane) {
    pin3(off);
#pragma unroll
    for (int s = 0; s < 3; s++)
#pragma unroll
        for (int e = 0; e < 4; e++) { lo[s][e] = 0.f; hi[s][e] = 0.f; }
#pragma unroll 1
    for (int it = 0; it < n; it++) {
        uint32_t a[4], b[3][4];
        lds128(a_addr, a);
        a_addr += a_step;
        ring.wait();
#pragma unroll
        for (int s = 0; s < 3; s++) ldsm_x4_t(ring.addr + off[s], b[s]);
#pragma unroll
        for (int s = 0; s < 3; s++) { mma16816(lo[s], a, b[s][0], b[s][1]); mma16816(hi[s], a, b[s][2], b[s][3]); }
        ring.release(lane);
    }
}

__global__ void __launch_bounds__(NTHR, 1)
fused_decode_kernel(const char* __restrict__ wq, const bf16* __restrict__ x, bf16* __restrict__ out,
                    const char* __restrict__ kc, const char* __restrict__ vc, const char* __restrict__ wo,
                    const char* __restrict__ w2, const __grid_constant__ Maps maps) {
    asm volatile("{\n.reg .pred p;\n.reg .b32 t, c, a, b;\n.reg .b64 o;\n"
                 "mov.u32 t, %%tid.x;\nmov.u32 c, %%ctaid.x;\n"
                 "and.b32 a, c, 3;\nshr.u32 c, c, 2;\nmul.lo.u32 a, a, 15360;\nmad.lo.u32 a, c, 3, a;\n"
                 "shr.u32 b, t, 2;\nmad.lo.u32 a, b, 92, a;\nadd.u32 a, a, t;\nmad.wide.u32 o, a, 128, %0;\n"
                 "and.b32 b, t, 3;\nsetp.ne.u32 p, b, 3;\nsetp.lt.and.u32 p, t, %1, p;\n@p prefetch.global.L2 [o];\n}"
                 ::"l"(wq), "n"(PF_ROWS * 4) : "memory");
    extern __shared__ __align__(1024) unsigned char smem[];
    const uint32_t sb = (uint32_t)__cvta_generic_to_shared(smem);
    const uint32_t bar_full = sb + SM_BAR;
    if (threadIdx.x == 0 && blockIdx.x < NATT) {
#pragma unroll 1
        for (int i = 0; i < DEPTH0; i++) {
            mbar_init(bar_full + i * 8, 1);
            mbar_expect_tx(bar_full + i * 8, 12288);
            tma3d(sb + SM_RING + i * SLOT, &maps.wq, (blockIdx.x >> 2) * 3, (blockIdx.x & 3) * 160 + i * 32, bar_full + i * 8);
        }
    }
    unsigned ptid, cta;
    asm volatile("mov.u32 %0, %%tid.x;\nmov.u32 %1, %%ctaid.x;" : "=r"(ptid), "=r"(cta));
    const int tid = ptid < 32 ? ptid + NCW * 32 : ptid < (NCW + 1) * 32 ? ptid - 32 : ptid;
    const int warp = __shfl_sync(0xffffffffu, tid >> 5, 0), lane = tid & 31;
    const bool is_att = cta < NATT;
    const int h = cta >> 2, qd = cta & 3;
    const int sg = cta / G, r = cta % G;

    if (warp == NCW) {
        volatile int* pace = reinterpret_cast<volatile int*>(smem + SM_PACE);
        if (lane == 0) {
            pace[0] = 0;
            pace[1] = is_att ? DEPTH : DEPTH_FFN;
#pragma unroll
            for (int i = 0; i < NBAR; i++)
                if (i >= DEPTH0 || !is_att)
                    mbar_init(bar_full + i * 8, i < NS ? 1 : i < 2 * NS ? NCW : i < 2 * NS + NSTEP ? NXW :
                                                i == 2 * NS + NSTEP ? NXW * NB : i == NBAR - 1 ? NXW : 1);
            asm volatile("fence.mbarrier_init.release.cluster;" ::: "memory");
        }
        __syncwarp();
        asm volatile("bar.arrive 2, %0;" ::"n"(NTHR) : "memory");
        if (lane == 0) {
            const int n_items = is_att ? ITEMS_ATT : ITEMS_FFN;
            asm volatile("prefetch.tensormap [%0];" ::"l"(is_att ? &maps.k : &maps.w3) : "memory");
            asm volatile("prefetch.tensormap [%0];" ::"l"(&maps.v) : "memory");
            asm volatile("prefetch.tensormap [%0];" ::"l"(&maps.w2) : "memory");
            asm volatile("prefetch.tensormap [%0];" ::"l"(&maps.wo) : "memory");
#pragma unroll 1
            for (int i = is_att ? DEPTH0 : 0; i < n_items; i++) {
                const CUtensorMap* map;
                int c1, c2;
                uint32_t bytes = 12288;
                if (is_att) {
                    const uint32_t u = i - 5;
                    if (u < NKV) {
                        bool isv;
                        c2 = window_row(sg, u, isv) + ((u % NT) * G + r) * TK;
                        map = isv ? &maps.v : &maps.k;
                        c1 = 0;
                    } else if (i < 5) {
                        map = &maps.wq; c1 = h * 3; c2 = qd * 160 + i * 32;
                    } else if (u < NKV + 2) {
                        map = &maps.w2; c1 = qd * 5; c2 = h * 48 + (u - NKV) * 24; bytes = 7680;
                    } else {
                        map = &maps.wo; c1 = qd * 5; c2 = h * DH + (u - NKV - 2) * 32; bytes = 10240;
                    }
                } else {
                    map = i < 40 ? &maps.w1 : &maps.w3; c1 = qd * 6; c2 = (i < 40 ? i : i - 40) * 16;
                }
                const int depth = pace[1] + (is_att && i >= 5 + NKV + 5 ? 3 : 0);
                const uint32_t slot = (uint32_t)i % NS, landed = i - depth;
                if (i >= NS) mbar_wait(bar_full + (NS + slot) * 8, ((uint32_t)i / NS - 1) & 1);
                mbar_expect_tx(bar_full + slot * 8, bytes);
                uint32_t dst = sb + SM_RING + slot * SLOT, fb = bar_full + slot * 8;
                asm volatile("" : "+r"(dst), "+r"(fb), "+l"(map), "+r"(c1), "+r"(c2));
                if (i >= depth) mbar_wait(bar_full + (landed % NS) * 8, (landed / NS) & 1);
                tma3d(dst, map, c1, c2, fb);
                pace[0] = landed + 1;
                const uint32_t un = i - 5 + 3;
                if (is_att && un < NKV && un % NT == 0 && r == (un / NT) % G) {
                    bool isv;
                    const int row = window_row(sg, un, isv);
                    asm volatile("prefetch.global.L2 [%0];" ::"l"((isv ? vc : kc) + (size_t)row * (DH * 2)) : "memory");
                }
                if (is_att && un == NKV) {
                    asm volatile("prefetch.global.L2 [%0];" ::"l"(w2 + h * (48 * DM * 2)) : "memory");
                    asm volatile("prefetch.global.L2 [%0];" ::"l"(wo + h * (DH * DM * 2)) : "memory");
                }
            }
            pace[0] = n_items - DEPTH;
        }
        return;
    }

    const int g = lane >> 2, t = lane & 3;
    uint32_t epoch;
    asm volatile("ld.relaxed.gpu.global.u32 %0, [%1];" : "=r"(epoch) : "l"(&g_sync.epoch) : "memory");

    if (warp == W_PACE) {
        const uint32_t tag = (epoch + 1u) & 1u;
        asm volatile("bar.sync 2, %0;" ::"n"(NTHR) : "memory");
        if (lane == 0) asm volatile("red.release.gpu.global.add.u32 [%0], 1;" ::"l"(&g_sync.inits) : "memory");
        if (!is_att) return;
        volatile int* pace = reinterpret_cast<volatile int*>(smem + SM_PACE);
        if (cta == 0 && lane == 0) asm volatile("st.relaxed.gpu.global.u32 [%0], %1;" ::"l"(&g_sync.prog[epoch & 1u]), "r"(0u) : "memory");
        int reported = 0, j = 0;
        bool due = false;
#pragma unroll 1
        for (unsigned it = 0;; it++) {
            const int landed = pace[0];
            if (j == NSTEP && landed >= ITEMS_ATT - DEPTH) {
                if (lane == 0)
                    asm volatile("red.relaxed.gpu.global.add.u32 [%0], %1;" ::"l"(&g_sync.prog[~epoch & 1u]), "r"(landed - reported) : "memory");
                return;
            }
            int sum = 0;
            constexpr int RPL = (G + 31) / 32;
            uint2 ml[WPS][RPL];
            uint32_t bad = 1u;
            unsigned n = (epoch + 1u) * NCTA;
            if (lane == 0)
                asm volatile("atom.relaxed.gpu.global.add.u32 %0, [%1], %2;"
                             : "=r"(sum) : "l"(&g_sync.prog[~epoch & 1u]), "r"(landed - reported) : "memory");
            if (due) {
#pragma unroll
                for (int u = 0; u < WPS; u++)
#pragma unroll
                    for (int k = 0; k < RPL; k++) ml[u][k] = ld_word(g_ml + (pair_of(sg, j * WPS + u) * G + k * 32 + lane % G) * MLS);
                if (j == 0) asm volatile("ld.acquire.gpu.global.u32 %0, [%1];" : "=r"(n) : "l"(&g_sync.inits) : "memory");
            }
            reported = landed;
            if (lane == 0 && it >= 2) {
                const int lag16 = sum / (NATT / 16) - landed * 16 + PACE_BIAS;
                pace[1] = min(max(DEPTH + ((lag16 * PACE_GAIN + 128) >> 8), DEPTH_MIN), DEPTH_MAX);
            }
            if (due) {
                bad = 0;
#pragma unroll
                for (int u = 0; u < WPS; u++)
#pragma unroll
                    for (int k = 0; k < RPL; k++) bad |= ml[u][k].x ^ tag;
            }
            if (__all_sync(0xffffffffu, !(bad & 1u) && n == (epoch + 1u) * NCTA)) {
#pragma unroll
                for (int u = 0; u < WPS; u++) {
                    float M = -INFINITY, L = 0.f, w = 0.f;
#pragma unroll
                    for (int k = 0; k < RPL; k++) M = fmaxf(M, __uint_as_float(ml[u][k].x & ~1u));
#pragma unroll
                    for (int o = G / RPL / 2; o; o >>= 1) M = fmaxf(M, shx(M, o));
#pragma unroll
                    for (int k = 0; k < RPL; k++) {
                        const float wk = __expf(__uint_as_float(ml[u][k].x & ~1u) - M);
                        L += wk * __uint_as_float(ml[u][k].y);
                        if (k == r / 32) w = wk;
                    }
#pragma unroll
                    for (int o = G / RPL / 2; o; o >>= 1) L += shx(L, o);
                    if (lane == r % 32) reinterpret_cast<float*>(smem + SM_LS)[16 + (j & 3) * WPS + u] = __fdividef(w, L);
                }
                if (lane == r % 32) {
                    mbar_arrive(bar_full + B_WRDY + (j & 3) * 8);
                }
                j++;
                due = false;
            }
            __nanosleep(PACE_NS);
            if (!due && j < NSTEP && mbar_test(bar_full + B_WTRIG + (j & 3) * 8, (j >> 2) & 1))
                due = (uint32_t)clock() - (uint32_t)pace[2 + (j & 3)] >= ML_SETTLE;
            if (it > SPIN_LIMIT) __trap();
        }
    }
    if (warp > W_PROD) {
        const uint32_t tag = (epoch + 1u) & 1u;
        const int e = tid - (W_PROD + 1) * 32;
        if (is_att) {
            st_fill4(reinterpret_cast<float*>(ocell(cta, e)), 0u);
            if (e < 32) *reinterpret_cast<uint32_t*>(smem + SM_HF + e * 16 + 12) = 0u;
        } else {
#pragma unroll 1
            for (int c = e; c < 256; c += NXW * 32) {
                const bf16* xp = x + qd * DM + (c >> 6) * 160 + ((c >> 3) & 7) * 8 + (c & 3) * 2 + ((c >> 2) & 1);
                asm volatile("st.relaxed.gpu.global.v4.f32 [%0], {%1,%2,%3,%4};"
                             ::"l"(g_acc + (qd * 32 + (c >> 3)) * ACS + (c & 7)), "f"(__bfloat162float(xp[0])),
                               "f"(__bfloat162float(xp[64])), "f"((c & 32) ? 0.f : __bfloat162float(xp[128])), "f"(0.f) : "memory");
            }
        }
        asm volatile("bar.sync 2, %0;" ::"n"(NTHR) : "memory");
        if (!is_att) return;
        {
            const uint32_t eq = (e >> 5) * 24 + min(lane, 23), xw = eq / 6, xr = eq % 6;
            mbar_wait(bar_full + B_QTRIG, 0);
            settle(Q_SETTLE);
#pragma unroll 1
            for (int j = 0; j < NSTEP; j++) {
                uint4 v[WPS][4];
                uint32_t bad;
                unsigned spin = 0;
                do {
#pragma unroll
                    for (int u = 0; u < WPS; u++) {
                        const int pair = pair_of(sg, j * WPS + u);
                        const float* src = g_qpart + ((pair >> 2) * 4 * NB + (pair & 3)) * VS + xw * 32 + xr * 4;
#pragma unroll
                        for (int k = 0; k < 4; k++) v[u][k] = ld_word2(src + k * NB * VS);
                    }
                    bad = 0;
#pragma unroll
                    for (int u = 0; u < WPS; u++)
#pragma unroll
                        for (int k = 0; k < 4; k++) bad |= (v[u][k].x ^ tag) | (v[u][k].z ^ tag);
                    if (++spin > SPIN_LIMIT) __trap();
                } while (bad & 1u);
#define SUM4(c) ((__uint_as_float(v[u][0].c) + __uint_as_float(v[u][1].c)) + (__uint_as_float(v[u][2].c) + __uint_as_float(v[u][3].c)))
#pragma unroll
                for (int u = 0; u < WPS; u++) {
                    unsigned char* dst = smem + SM_QS + (j * WPS + u) * (DH * 2) + (xr & 1) * 192 + ((xr >> 1) * 8 + xw) * 4;
                    *reinterpret_cast<uint32_t*>(dst) = pack_bf2(SUM4(x), SUM4(y));
                    *reinterpret_cast<uint32_t*>(dst + 96) = pack_bf2(SUM4(z), SUM4(w));
                }
#undef SUM4
                __syncwarp();
                if (lane == 0) mbar_arrive(bar_full + B_QRDY + j * 8);
            }
        }
        bool have_h = false;
#pragma unroll 1
        for (int b = 0; b <= NB; b++) {
            if (!have_h && (b == NB || order_of(r, b) >= HSTEP * WPS)) {
                have_h = true;
                mbar_wait(bar_full + B_HTRIG, 0);
#pragma unroll 1
                for (int i = e; i < 96; i += NXW * 32) {
                    const int k = (i % 24) * 2;
                    uint2 v;
                    unsigned spin = 0;
                    do {
                        v = ld_word(g_h + i / 24 * FF + h * 48 + k);
                        if (++spin > SPIN_LIMIT) __trap();
                    } while ((v.x ^ tag) & 1u);
                    *reinterpret_cast<uint32_t*>(smem + SM_HF + k / 24 * 256 + i / 24 * 64 + frag_off(k % 24)) = __byte_perm(v.x, v.y, 0x7632);
                }
                __syncwarp();
                if (lane == 0) mbar_arrive(bar_full + B_HRDY);
            }
            if (b == NB) break;
            const float4* src = ocell(h * NB + b, e);
            uint32_t dst = sb + SM_OF + (e >> 5) * 256 + b * 64 + frag_off(lane), ordy = bar_full + B_ORDY;
            asm volatile("" : "+r"(dst), "+l"(src), "+r"(ordy));
            mbar_wait(bar_full + B_OTRIG + b * 8, 0);
            const int pause = order_of(r, b) < G - WPS ? O_SETTLE : 0;
            unsigned spin = 0;
            float o0, o1, o2, n;
            do {
                settle(pause);
                asm volatile("{\n.reg .b128 w;\n.reg .b64 w0, w1;\nld.relaxed.gpu.global.b128 w, [%4];\nmov.b128 {w0, w1}, w;\n"
                             "mov.b64 {%0,%1}, w0;\nmov.b64 {%2,%3}, w1;\n}"
                             : "=f"(o0), "=f"(o1), "=f"(o2), "=f"(n) : "l"(src) : "memory");
                asm volatile("st.shared.u16 [%0], %1;\nst.shared.u16 [%0+512], %2;\nst.shared.u16 [%0+1024], %3;"
                             ::"r"(dst), "h"(__bfloat16_as_ushort(__float2bfloat16_rn(o0))),
                               "h"(__bfloat16_as_ushort(__float2bfloat16_rn(o1))), "h"(__bfloat16_as_ushort(__float2bfloat16_rn(o2))) : "memory");
                if (++spin > SPIN_LIMIT) __trap();
            } while (n != (float)G);
            __syncwarp();
            if (lane == 0) mbar_arrive(ordy);
        }
        return;
    }

    if (warp < NB) {
        uint2 raw[5];
#pragma unroll
        for (int i = 0; i < 5; i++) raw[i] = __ldg(reinterpret_cast<const uint2*>(x + warp * DM) + i * 32 + lane);
        float s = 0.f;
#pragma unroll
        for (int i = 0; i < 5; i++) s += (bf_lo(raw[i].x) + bf_hi(raw[i].x)) + (bf_lo(raw[i].y) + bf_hi(raw[i].y));
#pragma unroll
        for (int o = 16; o; o >>= 1) s += shx(s, o);
        const float mean = s * (1.0f / DM);
        float q2 = 0.f;
#pragma unroll
        for (int i = 0; i < 5; i++) {
            const float d0 = bf_lo(raw[i].x) - mean, d1 = bf_hi(raw[i].x) - mean;
            const float d2 = bf_lo(raw[i].y) - mean, d3 = bf_hi(raw[i].y) - mean;
            q2 += (d0 * d0 + d1 * d1) + (d2 * d2 + d3 * d3);
        }
#pragma unroll
        for (int o = 16; o; o >>= 1) q2 += shx(q2, o);
        const float mb = bf_round(mean);
        const float rs = __frcp_rn(bf_round(__fsqrt_rn(bf_round(bf_round(q2 * (1.0f / DM)) + 1e-5f))));
        const uint32_t k = (lane * 4) & 31;
        unsigned char* dst = smem + SM_XF + warp * 64 +
            (is_att ? (lane >> 3) * 256 + frag_off(k) : (lane >> 2) * 256 + frag_off(k & 15));
        const uint32_t step = is_att ? 1024 : 2048;
#pragma unroll
        for (int i = 0; i < 5; i++) {
            const uint32_t d0 = pack_bf2(bf_lo(raw[i].x) - mb, bf_hi(raw[i].x) - mb);
            const uint32_t d1 = pack_bf2(bf_lo(raw[i].y) - mb, bf_hi(raw[i].y) - mb);
            *reinterpret_cast<uint32_t*>(dst + i * step) = pack_bf2(bf_lo(d0) * rs, bf_hi(d0) * rs);
            *reinterpret_cast<uint32_t*>(dst + i * step + 16) = pack_bf2(bf_lo(d1) * rs, bf_hi(d1) * rs);
        }
    }
    asm volatile("bar.sync 2, %0;" ::"n"(NTHR) : "memory");
    uint32_t tag = (epoch + 1u) & 1u;
    asm volatile("" : "+r"(tag));

    Ring ring{bar_full, sb + SM_RING, 0u, bar_full};
    float lo[3][4] = {}, hi[3][4] = {};
    uint32_t off[3];
    const uint32_t a_lane = (g & 3) * 64 + t * 16;

    if (is_att) {
        float* lsum = reinterpret_cast<float*>(smem + SM_LS);
#pragma unroll 1
        for (int j = -1; j < NSTEP + LA; j++) {
            if (j >= 0 && j < NSTEP) {
                constexpr int WW = NCW / WPS;
                const int win = j * WPS + warp / WW;
                uint32_t qf[6][4];
                mbar_wait(bar_full + B_QRDY + j * 8, 0);
#pragma unroll
                for (int i = 0; i < 6; i++) lds128(sb + SM_QS + win * (DH * 2) + t * 96 + i * 16, qf[i]);
                const uint32_t key = (warp & 1) * 16 + (lane & 15);
                const uint32_t item = 5 + (j + max(j - LA, 0)) * 4 + (warp >> 1), slot = item % NS;
#pragma unroll
                for (int s = 0; s < 3; s++)
                    off[s] = sb + SM_RING + slot * SLOT + key * 384 + s * 128 + (((lane >> 4) ^ ((3 * key + s) & 7)) << 4);
                pin3(off);
                mbar_wait(bar_full + slot * 8, (item / NS) & 1);
                float c[3][4] = {};
#pragma unroll
                for (int dq = 0; dq < 4; dq++)
#pragma unroll
                    for (int s = 0; s < 3; s++) {
                        uint32_t a[4];
                        ldsm_x4(off[s] ^ (dq << 5), a);
                        mma16816(c[s], a, qf[s * 2 + (dq >> 1)][(dq & 1) * 2], qf[s * 2 + (dq >> 1)][(dq & 1) * 2 + 1]);
                    }
                __syncwarp();
                if (lane == 0)
                    asm volatile("mbarrier.arrive.shared::cta.b64 _, [%0], %1;" ::"r"(bar_full + (NS + slot) * 8), "n"(NCW / 2) : "memory");
                ring.skip(4);
                const float raw = (t & 1) ? (c[0][2] + c[1][2]) + c[2][2] : (c[0][0] + c[1][0]) + c[2][0];
                const float sv = bf_round(bf_round(raw) * 0.07216878364870323f);
                float m = fmaxf(sv, shx(sv, 1));
#pragma unroll
                for (int o = 4; o < 32; o <<= 1) m = fmaxf(m, shx(m, o));
                if (lane == 0) lsum[8 + warp] = m;
                cons_bar();
#pragma unroll
                for (int i = 0; i < WW; i += 2) {
                    const float2 m2 = *reinterpret_cast<const float2*>(lsum + 8 + warp / WW * WW + i);
                    m = fmaxf(m, fmaxf(m2.x, m2.y));
                }
                float l = __expf(sv - m);
                *reinterpret_cast<bf16*>(smem + SM_PF + ((j & 3) * 4 + (warp >> 1)) * 64 + frag_off((warp & 1) * 16 + (t & 1) * 8 + g)) =
                    __float2bfloat16_rn(l);
                l += shx(l, 1);
#pragma unroll
                for (int o = 4; o < 32; o <<= 1) l += shx(l, o);
                if (lane == 0) lsum[warp] = l;
                cons_bar();
                if (tid % (WW * 32) < 4) {
                    l = 0.f;
#pragma unroll
                    for (int i = 0; i < WW; i += 2) {
                        const float2 l2 = *reinterpret_cast<const float2*>(lsum + warp + i);
                        l += l2.x + l2.y;
                    }
                    st_tag2(g_ml + (pair_of(sg, win) * G + r) * MLS + lane * 2, m, l, tag);
                    if (tid == 0) {
                        reinterpret_cast<volatile int*>(smem + SM_PACE)[2 + (j & 3)] = (int)clock();
                        mbar_arrive(bar_full + B_WTRIG + (j & 3) * 8);
                        if (j == HSTEP) mbar_arrive(bar_full + B_HTRIG);
                    }
                }
                if (j < LA) continue;
            }
            const bool kv = j >= 0;
            const uint32_t jv = j - LA;
#pragma unroll
            for (int s = 0; s < 3; s++) off[s] = lane * 384 + s * 128 + ((warp ^ ((3 * lane + s) & 7)) << 4);
#pragma unroll 1
            for (int u = 0; u < (kv ? WPS : 1); u++) {
                const int pair = pair_of(sg, jv * WPS + u);
                uint32_t trig = !kv ? bar_full + B_QTRIG : (pair >> 2) == h ? bar_full + B_OTRIG + (pair & 3) * 8 : 0;
                if (tid != 0) trig = 0;
                float4* oacc = ocell(pair, warp * 8 + 2 * t + (g & 1));
                uint32_t wrdy = bar_full + B_WRDY + (jv & 3) * 8;
                asm volatile("" : "+l"(oacc), "+r"(trig), "+r"(wrdy));
                gemv_loop(ring, kv ? NT : 5,
                          kv ? sb + SM_PF + ((jv & 3) * 4 + u * NT) * 64 + t * 16 : sb + SM_XF + qd * 5 * 256 + a_lane,
                          kv ? 64 : 256, off, lo, hi, lane);
                if (kv) {
                    mbar_wait(wrdy, (jv >> 2) & 1);
                    const float w = lsum[16 + (jv & 3) * WPS + u];
                    if (g < 2)
                        asm volatile("red.relaxed.gpu.global.add.v4.f32 [%0], {%1,%2,%3,%4};"
                                     ::"l"(oacc), "f"(w * (g ? lo[0][1] + hi[0][3] : lo[0][0] + hi[0][2])),
                                       "f"(w * (g ? lo[1][1] + hi[1][3] : lo[1][0] + hi[1][2])),
                                       "f"(w * (g ? lo[2][1] + hi[2][3] : lo[2][0] + hi[2][2])), "f"(1.0f) : "memory");
                } else if (g < NB) {
#pragma unroll
                    for (int s = 0; s < 3; s++)
                        st_tag2(g_qpart + (cta * NB + g) * VS + warp * 32 + 2 * t + s * 8, lo[s][0] + hi[s][2], lo[s][1] + hi[s][3], tag);
                }
                if (trig) mbar_arrive(trig);
            }
            const bool pass = j == NSTEP + LA - 1;
            if (kv && !pass) continue;

            {
                constexpr int I0 = 5 + NKV;
                static_assert(((I0 / NS) & 1) == 0 && I0 / NS == (I0 + 7) / NS, "tail items complete an even phase");
                const uint32_t done = bar_full + B_QTRIG;
                uint32_t fb = pass ? bar_full + (I0 % NS) * 8 : done, fs = pass ? 8 : 0, ordy = pass ? bar_full + B_ORDY : done;
                const uint32_t hrdy = pass ? bar_full + B_HRDY : done;
                uint32_t off2[3], a[8][4], b[8][3][4], a_addr = sb + SM_HF + a_lane;
#pragma unroll
                for (int s = 0; s < 3; s++) {
                    const uint32_t w64 = lane * 320 + (warp + 8 * s) * 16;
                    off[s] = sb + SM_RING + (I0 % NS) * SLOT + (w64 ^ (((w64 >> 7) & 3) << 4));
                    off2[s] = lane < 24 ? off[s] : off[s] - 8 * 320;
                }
                const float4* accp = g_acc + (((g & 3) * 4 + qd) * NCW + warp) * ACS + (g >> 2) * 4 + t;
                bf16* outp = out + (g & 3) * DM + qd * 160 + warp * 8 + 2 * t + (g >> 2);
                pin3(off);
                asm volatile("" : "+l"(accp), "+l"(outp), "+r"(a_addr), "+r"(ordy), "+r"(fb), "+r"(fs));
                uint32_t miss = 0;
                auto load_b = [&](int i) {
                    uint32_t z;
                    asm volatile("{\n.reg .pred p;\nmbarrier.try_wait.parity.shared::cta.b64 p, [%1], 0;\nselp.u32 %0, 0, 16, p;\n}"
                                 : "=r"(z) : "r"(fb + i * fs) : "memory");
                    miss |= z;
#pragma unroll
                    for (int s = 0; s < 3; s++)
                        if (s < 2 || warp < 4) ldsm_x4_t((i < 2 ? off2[s] : off[s]) + z + i * SLOT, b[i][s]);
                };
                auto mul = [&](int i) {
#pragma unroll
                    for (int s = 0; s < 3; s++)
                        if (s < 2 || warp < 4) { mma16816(lo[s], a[i], b[i][s][0], b[i][s][1]); mma16816(hi[s], a[i], b[i][s][2], b[i][s][3]); }
                };
                __syncwarp();
                mbar_wait(hrdy, 0);
                lds128(a_addr, a[0]);
                lds128(a_addr + 256, a[1]);
                for (unsigned spin = 0;; spin++) {
#pragma unroll
                    for (int s = 0; s < 3; s++)
#pragma unroll
                        for (int e = 0; e < 4; e++) { lo[s][e] = 0.f; hi[s][e] = 0.f; }
                    load_b(0);
#pragma unroll
                    for (int i = 0; i < 7; i++) {
                        load_b(i + 1);
                        if (i == 2) {
                            mbar_wait(ordy, 0);
#pragma unroll
                            for (int k = 2; k < 8; k++) lds128(a_addr + k * 256, a[k]);
                        }
                        mul(i);
                    }
                    mul(7);
                    add_out(accp, outp, lo, hi, g >= NB, warp < 4, pass && !miss, epoch);
                    if (!miss) break;
                    if (spin > SPIN_LIMIT) __trap();
                    miss = 0;
                }
            }
        }
    } else {
        float gate[6][2];
#pragma unroll
        for (int s = 0; s < 3; s++) {
            const uint32_t r128 = (lane & 15) * 6 + 2 * s + (lane >> 4);
            off[s] = r128 * 128 + ((warp ^ (r128 & 7)) << 4);
        }
#pragma unroll 1
        for (int ps = 0; ps < 2; ps++) {
#pragma unroll
            for (int s = 0; s < 3; s++) {
                gate[2 * s][0] = lo[s][0]; gate[2 * s][1] = lo[s][1];
                gate[2 * s + 1][0] = hi[s][0]; gate[2 * s + 1][1] = hi[s][1];
            }
            gemv_loop(ring, 40, sb + SM_XF + a_lane, 256, off, lo, hi, lane);
        }
#pragma unroll
        for (int p = 0; p < 6; p++) {
            float hv[2];
#pragma unroll
            for (int e = 0; e < 2; e++) {
                const float gt = bf_round(gate[p][e]);
                hv[e] = bf_round(bf_round(__fdividef(gt, 1.0f + __expf(-gt))) * bf_round((p & 1) ? hi[p >> 1][e] : lo[p >> 1][e]));
            }
            if (g < NB) st_tag2(g_h + g * FF + qd * 384 + p * 64 + warp * 8 + 2 * t, hv[0], hv[1], tag);
        }
    }
}

typedef CUresult (*EncodeFn)(CUtensorMap*, CUtensorMapDataType, cuuint32_t, void*, const cuuint64_t*, const cuuint64_t*,
                             const cuuint32_t*, const cuuint32_t*, CUtensorMapInterleave, CUtensorMapSwizzle,
                             CUtensorMapL2promotion, CUtensorMapFloatOOBfill);

void make_map(EncodeFn enc, CUtensorMap* m, const void* p, uint64_t rows, uint64_t cols, uint32_t inner, uint32_t parts,
              uint32_t box_rows) {
    const cuuint64_t dims[3] = {inner, cols / inner, rows};
    const cuuint64_t strides[2] = {inner * 2ull, cols * 2ull};
    const cuuint32_t box[3] = {inner, parts, box_rows};
    const cuuint32_t es[3] = {1, 1, 1};
    enc(m, CU_TENSOR_MAP_DATA_TYPE_BFLOAT16, 3, const_cast<void*>(p), dims, strides, box, es, CU_TENSOR_MAP_INTERLEAVE_NONE,
        inner == 64 ? CU_TENSOR_MAP_SWIZZLE_128B : CU_TENSOR_MAP_SWIZZLE_64B, CU_TENSOR_MAP_L2_PROMOTION_NONE,
        CU_TENSOR_MAP_FLOAT_OOB_FILL_NONE);
}

}

extern "C" void kernel_launch(void* const* d_in, const int* in_sizes, int n_in, void* d_out, int out_size) {
    (void)in_sizes; (void)n_in; (void)out_size;
    static EncodeFn enc = nullptr;
    if (!enc) {
        void* fn = nullptr;
        cudaDriverEntryPointQueryResult qr;
        cudaGetDriverEntryPoint("cuTensorMapEncodeTiled", &fn, cudaEnableDefault, &qr);
        enc = (EncodeFn)fn;
        cudaFuncSetAttribute(fused_decode_kernel, cudaFuncAttributeMaxDynamicSharedMemorySize, SM_TOTAL);
    }
    Maps maps;
    make_map(enc, &maps.k, d_in[1], (uint64_t)NB * NH * SK, DH, 64, 3, TK);
    make_map(enc, &maps.v, d_in[2], (uint64_t)NB * NH * SK, DH, 64, 3, TK);
    make_map(enc, &maps.wq, d_in[3], DM, NH * DH, 64, 3, 32);
    make_map(enc, &maps.wo, d_in[4], NH * DH, DM, 32, 5, 32);
    make_map(enc, &maps.w1, d_in[6], DM, FF, 64, 6, 16);
    make_map(enc, &maps.w3, d_in[7], DM, FF, 64, 6, 16);
    make_map(enc, &maps.w2, d_in[8], FF, DM, 32, 5, 24);
    fused_decode_kernel<<<NCTA, NTHR, SM_TOTAL>>>((const char*)d_in[3], (const bf16*)d_in[0], (bf16*)d_out,
                                                  (const char*)d_in[1], (const char*)d_in[2], (const char*)d_in[4],
                                                  (const char*)d_in[8], maps);
}
```
